```python
import torch

def _softmax(x, axis=-1):
    return torch.softmax(x, dim=axis)

def _gelu(x):
    return torch.nn.functional.gelu(x, approximate='tanh')

def _silu(x):
    return torch.nn.functional.silu(x)

def _sigmoid(x):
    return torch.sigmoid(x)

def _layernorm(x, axis=-1, eps=1e-05):
    m = x.mean(dim=axis, keepdim=True)
    v = x.var(dim=axis, keepdim=True, unbiased=False)
    return (x - m) / torch.sqrt(v + eps)

def _scatter_add(tgt, idx, src, axis=0):
    return tgt.clone().index_add_(axis, idx, src)

def _segment_sum(src, seg, n):
    out = torch.zeros((n,) + src.shape[1:], dtype=src.dtype)
    return out.index_add_(0, seg, src)

def _pad(x, pw):
    flat = tuple((v for pair in reversed(pw) for v in pair))
    return torch.nn.functional.pad(x, flat)
kernel_name = 'adaLN_cond__sliding_block_cached__glu_gated_reglu__decode'

def setup_inputs():

    _w = lambda a: (lambda t: t.to(torch.bfloat16) if t.is_floating_point() else t)(torch.as_tensor(a))

    def _A_setup():
        B, Sq, D = (2, 1, 576)
        Hq, Hkv, Sk, Dh = (32, 16, 32768, 128)
        assert Hq % Hkv == 0, (Hq, Hkv)
        return {'x': _w((lambda *s: torch.randn(*s, dtype=torch.bfloat16) * 0.1)(B, Sq, D)), 'k_cache': _w((lambda *s: torch.randn(*s, dtype=torch.bfloat16) * 0.8)(B, Hkv, Sk, Dh)), 'v_cache': _w((lambda *s: torch.randn(*s, dtype=torch.bfloat16) * 3.2)(B, Hkv, Sk, Dh)), 'wq': _w((lambda *s: torch.randn(*s, dtype=torch.bfloat16) * 0.8)(D, Hq * Dh) * D ** (-0.5)), 'wo': _w((lambda *s: torch.randn(*s, dtype=torch.bfloat16) * 3.2)(Hq * Dh, D) * (Hq * Dh) ** (-0.5))}
    _A_in = _A_setup()

    def _B_setup():
        B, S, D, F = (2, 1, 576, 4608)
        return {'x': _w((lambda *s: torch.randn(*s, dtype=torch.bfloat16) * 0.1)(B, S, D)), 'W_gate': _w((lambda *s: torch.randn(*s, dtype=torch.bfloat16) * 3.2)(D, F) * (2.0 / D) ** 0.5), 'W_up': _w((lambda *s: torch.randn(*s, dtype=torch.bfloat16) * 3.2)(D, F) * (2.0 / D) ** 0.5), 'W_down': _w((lambda *s: torch.randn(*s, dtype=torch.bfloat16) * 3.2)(F, D) * (1.0 / F) ** 0.5)}
    _B_in = _B_setup()
    return {'A_x': _A_in['x'], 'A_k_cache': _A_in['k_cache'], 'A_v_cache': _A_in['v_cache'], 'A_wq': _A_in['wq'], 'A_wo': _A_in['wo'], 'B_x': _B_in['x'], 'B_W_gate': _B_in['W_gate'], 'B_W_up': _B_in['W_up'], 'B_W_down': _B_in['W_down'], 'c': _w((lambda *s: torch.randn(*s, dtype=torch.bfloat16) * 0.8)(2, 576) * 8.0), 'w_mod': _w((lambda *s: torch.randn(*s, dtype=torch.bfloat16) * 0.8)(576, 6 * 576) * 576 ** (-0.5) * 8.0)}

def reference(A_x, A_k_cache, A_v_cache, A_wq, A_wo, B_x, B_W_gate, B_W_up, B_W_down, c, w_mod):

    def _A_ref(x, k_cache, v_cache, wq, wo):
        B, Sq, D = x.shape
        Hq, Dh = (32, 128)
        Hkv, Sk = (k_cache.shape[1], k_cache.shape[2])
        W = min(4096, max(256, Sk // 4))
        rep = Hq // Hkv
        q = (lambda x, *d: x.permute(*d))((x @ wq).reshape(B, Sq, Hq, Dh), 0, 2, 1, 3)
        k = (lambda x, n, axis: torch.repeat_interleave(x, n, dim=axis))(k_cache[:, :, Sk - W:, :], rep, axis=1)
        v = (lambda x, n, axis: torch.repeat_interleave(x, n, dim=axis))(v_cache[:, :, Sk - W:, :], rep, axis=1)
        scores = torch.einsum('bhqd,bhkd->bhqk', q, k) * Dh ** (-0.5)
        p = _softmax(scores, axis=-1)
        o = torch.einsum('bhqk,bhkd->bhqd', p, v)
        return (lambda x, *d: x.permute(*d))(o, 0, 2, 1, 3).reshape(B, Sq, Hq * Dh) @ wo

    def _B_ref(x, W_gate, W_up, W_down):
        gate = torch.einsum('bsd,df->bsf', x, W_gate)
        up = torch.einsum('bsd,df->bsf', x, W_up)
        gate = gate * (lambda x, dt: x.to(dt))(gate > 0, gate.dtype)
        h = gate * up
        return torch.einsum('bsf,fd->bsd', h, W_down)
    x = A_x
    mod = (_silu(c) @ w_mod).reshape(c.shape[0], 6, 1, -1)
    sa, ca, ga, sb, cb, gb = (mod[:, 0].clone(), mod[:, 1].clone(), mod[:, 2].clone(), mod[:, 3].clone(), mod[:, 4].clone(), mod[:, 5].clone())
    h = _layernorm(x, axis=-1) * (1 + ca) + sa
    x = x + ga * _A_ref(h, A_k_cache, A_v_cache, A_wq, A_wo)
    h = _layernorm(x, axis=-1) * (1 + cb) + sb
    x = x + gb * _B_ref(h, B_W_gate, B_W_up, B_W_down)
    return x
```

```cpp
#include <cuda_runtime.h>
#include <cuda.h>
#include <cuda_bf16.h>
#include <stdint.h>

namespace {

constexpr int DM = 576;
constexpr int NCTA = 128;
constexpr int NCW = 9;
constexpr int NCT = NCW * 32;
constexpr int NTHR = NCT + 32;
constexpr int NMOD = 108;

#define WIN_MAIN 4
#define WIN_TAIL 3
#define EARLY_PF 2

constexpr int IT_WMOD = 0, IT_WQ = 2, IT_K = 4, IT_V = 20, IT_WO = 36, IT_GU = 38, IT_WD = 44, N_IT = 47;
constexpr int EM_WMOD = 0, EM_WQ = 1, EM_K = 2, EM_V = 18, N_EM = 34;

constexpr int RING = 13 * 16384;
constexpr int OFF_WMOD = 0, OFF_WQ = 36864, OFF_K0 = 73728;
constexpr int OFF_WO0 = 180224, OFF_WO1 = 0, OFF_G = 18432, OFF_U = 64512;
constexpr int OFF_D0 = 110592, OFF_D2 = 147456;
constexpr int PSTR = 2064;
constexpr int OFF_P = RING;
constexpr int ASTR = 1168;
constexpr int OFF_ACT = OFF_P + 4224;
constexpr int OFF_REDC = OFF_ACT + 2432;
constexpr int OFF_REDA = OFF_REDC;
constexpr int OFF_REDB = OFF_REDA + 2304;
constexpr int OFF_QS = OFF_REDC + 5760;
constexpr int OFF_OF = OFF_QS + 576;
constexpr int OFF_HH = OFF_OF + 512;
constexpr int OFF_STAT = OFF_HH + 256;
constexpr int OFF_WMX = OFF_STAT + 320;
constexpr int OFF_BAR = OFF_WMX + 128;
constexpr int SMEM_USED = OFF_BAR + (N_IT + N_EM) * 8;
constexpr int SMEM_BYTES = SMEM_USED + 1024;
static_assert(SMEM_BYTES <= 232448, "smem");

struct Maps { CUtensorMap k, v, wmod, wq, wg, wu, wo, wd, wd4; };

__device__ unsigned g_epoch;
__device__ __align__(128) unsigned g_mod[3456 * 2];
__device__ __align__(128) unsigned g_q[2 * 4096];
__device__ __align__(128) unsigned g_ml[NCTA * 8];
__device__ __align__(128) unsigned g_op[NCTA * 256];
__device__ __align__(128) unsigned g_p1[144 * NCTA * 8];
__device__ __align__(128) unsigned g_x1[1152];
__device__ __align__(128) unsigned g_p2[144 * NCTA * 8];

constexpr int SPIN_LIMIT = 1 << 20;

__device__ __forceinline__ uint32_t smem_u32(const void* p) { return (uint32_t)__cvta_generic_to_shared(p); }
__device__ __forceinline__ void mbar_init(uint32_t bar, int cnt) {
    asm volatile("mbarrier.init.shared::cta.b64 [%0], %1;" ::"r"(bar), "r"(cnt) : "memory");
}
__device__ __forceinline__ void mbar_expect_tx(uint32_t bar, uint32_t bytes) {
    asm volatile("mbarrier.arrive.expect_tx.shared::cta.b64 _, [%0], %1;" ::"r"(bar), "r"(bytes) : "memory");
}
__device__ __forceinline__ void mbar_arrive(uint32_t bar) {
    asm volatile("mbarrier.arrive.shared::cta.b64 _, [%0];" ::"r"(bar) : "memory");
}
__device__ __forceinline__ void mbar_wait(uint32_t bar) {
    uint32_t ok;
    int it = 0;
    do {
        asm volatile("{\n.reg .pred p;\nmbarrier.try_wait.parity.shared::cta.b64 p, [%1], 0;\nselp.u32 %0, 1, 0, p;\n}"
                     : "=r"(ok) : "r"(bar) : "memory");
    } while (!ok && ++it < SPIN_LIMIT);
}
__device__ __forceinline__ void tma2d(uint32_t dst, const CUtensorMap* m, int x, int y, uint32_t bar) {
    asm volatile("cp.async.bulk.tensor.2d.shared::cluster.global.mbarrier::complete_tx::bytes [%0], [%1, {%3, %4}], [%2];"
                 ::"r"(dst), "l"(m), "r"(bar), "r"(x), "r"(y) : "memory");
}
__device__ __forceinline__ void tma3d(uint32_t dst, const CUtensorMap* m, int x, int y, int z, uint32_t bar) {
    asm volatile("cp.async.bulk.tensor.3d.shared::cluster.global.mbarrier::complete_tx::bytes [%0], [%1, {%3, %4, %5}], [%2];"
                 ::"r"(dst), "l"(m), "r"(bar), "r"(x), "r"(y), "r"(z) : "memory");
}
__device__ __forceinline__ void bar_consumers() { asm volatile("bar.sync 1, 288;" ::: "memory"); }

__device__ __forceinline__ void ldsm4(uint32_t (&a)[4], uint32_t addr) {
    asm volatile("ldmatrix.sync.aligned.m8n8.x4.shared.b16 {%0,%1,%2,%3}, [%4];"
                 : "=r"(a[0]), "=r"(a[1]), "=r"(a[2]), "=r"(a[3]) : "r"(addr) : "memory");
}
__device__ __forceinline__ void ldsm4t(uint32_t (&a)[4], uint32_t addr) {
    asm volatile("ldmatrix.sync.aligned.m8n8.x4.trans.shared.b16 {%0,%1,%2,%3}, [%4];"
                 : "=r"(a[0]), "=r"(a[1]), "=r"(a[2]), "=r"(a[3]) : "r"(addr) : "memory");
}
__device__ __forceinline__ void mma16816(float (&c)[4], const uint32_t (&a)[4], uint32_t b0, uint32_t b1) {
    asm volatile("mma.sync.aligned.m16n8k16.row.col.f32.bf16.bf16.f32 {%0,%1,%2,%3}, {%4,%5,%6,%7}, {%8,%9}, {%0,%1,%2,%3};"
                 : "+f"(c[0]), "+f"(c[1]), "+f"(c[2]), "+f"(c[3])
                 : "r"(a[0]), "r"(a[1]), "r"(a[2]), "r"(a[3]), "r"(b0), "r"(b1));
}
__device__ __forceinline__ uint32_t lds32(uint32_t a) { uint32_t v; asm volatile("ld.shared.u32 %0, [%1];" : "=r"(v) : "r"(a) : "memory"); return v; }
__device__ __forceinline__ float ldsf(uint32_t a) { float v; asm volatile("ld.shared.f32 %0, [%1];" : "=f"(v) : "r"(a) : "memory"); return v; }
__device__ __forceinline__ uint4 lds128(uint32_t a) {
    uint4 v; asm volatile("ld.shared.v4.u32 {%0,%1,%2,%3}, [%4];" : "=r"(v.x), "=r"(v.y), "=r"(v.z), "=r"(v.w) : "r"(a) : "memory"); return v;
}
__device__ __forceinline__ void sts16(uint32_t a, uint32_t v) { asm volatile("st.shared.u16 [%0], %1;" ::"r"(a), "h"((unsigned short)v) : "memory"); }
__device__ __forceinline__ void sts32(uint32_t a, uint32_t v) { asm volatile("st.shared.u32 [%0], %1;" ::"r"(a), "r"(v) : "memory"); }
__device__ __forceinline__ void stsf(uint32_t a, float v) { asm volatile("st.shared.f32 [%0], %1;" ::"r"(a), "f"(v) : "memory"); }
__device__ __forceinline__ void sts64(uint32_t a, uint32_t x, uint32_t y) { asm volatile("st.shared.v2.u32 [%0], {%1,%2};" ::"r"(a), "r"(x), "r"(y) : "memory"); }
__device__ __forceinline__ void sts128(uint32_t a, uint4 v) {
    asm volatile("st.shared.v4.u32 [%0], {%1,%2,%3,%4};" ::"r"(a), "r"(v.x), "r"(v.y), "r"(v.z), "r"(v.w) : "memory");
}
__device__ __forceinline__ uint4 ldg_rlx4(const unsigned* p) {
    uint4 v; asm volatile("ld.relaxed.gpu.global.v4.u32 {%0,%1,%2,%3}, [%4];" : "=r"(v.x), "=r"(v.y), "=r"(v.z), "=r"(v.w) : "l"(p) : "memory"); return v;
}
__device__ __forceinline__ void stg_rlx1(unsigned* p, unsigned x) { asm volatile("st.relaxed.gpu.global.u32 [%0], %1;" ::"l"(p), "r"(x) : "memory"); }
__device__ __forceinline__ void stg_rlx2(unsigned* p, unsigned x, unsigned y) { asm volatile("st.relaxed.gpu.global.v2.u32 [%0], {%1,%2};" ::"l"(p), "r"(x), "r"(y) : "memory"); }
__device__ __forceinline__ void stg_rlx4(unsigned* p, uint4 v) {
    asm volatile("st.relaxed.gpu.global.v4.u32 [%0], {%1,%2,%3,%4};" ::"l"(p), "r"(v.x), "r"(v.y), "r"(v.z), "r"(v.w) : "memory");
}
__device__ __forceinline__ bool valid4(const uint4& v, unsigned tag) {
    return tag ? ((v.x & v.y & v.z & v.w) & 1u) : !((v.x | v.y | v.z | v.w) & 1u);
}
__device__ __forceinline__ uint4 poll4(const unsigned* p, unsigned tag) {
    uint4 v = ldg_rlx4(p);
    int it = 0;
    while (!valid4(v, tag) && ++it < SPIN_LIMIT) v = ldg_rlx4(p);
    return v;
}
__device__ __forceinline__ unsigned tagf(float v, unsigned tag) { return (__float_as_uint(v) & ~1u) | tag; }
__device__ __forceinline__ float untagf(unsigned w) { return __uint_as_float(w & ~1u); }
__device__ __forceinline__ float rbf(float v) { return __bfloat162float(__float2bfloat16_rn(v)); }
__device__ __forceinline__ uint32_t bfbits(float v) { return (uint32_t)__bfloat16_as_ushort(__float2bfloat16_rn(v)); }
__device__ __forceinline__ uint32_t pack2(float lo, float hi) {
    uint32_t r; asm("cvt.rn.bf16x2.f32 %0, %1, %2;" : "=r"(r) : "f"(hi), "f"(lo)); return r;
}
__device__ __forceinline__ float bflo(uint32_t w) { return __uint_as_float(w << 16); }
__device__ __forceinline__ float bfhi(uint32_t w) { return __uint_as_float(w & 0xffff0000u); }
__device__ __forceinline__ float warp_sum(float v) {
#pragma unroll
    for (int o = 16; o > 0; o >>= 1) v += __shfl_xor_sync(0xffffffffu, v, o);
    return v;
}
#define TS(cond, slot) do { } while (0)

__device__ __forceinline__ void ln_stage1(const float (&v)[2][2], uint32_t s_stat, int warp, int lane) {
#pragma unroll
    for (int b = 0; b < 2; b++) {
        float mw = warp_sum(v[b][0] + v[b][1]) * (1.0f / 64.0f);
        float d0 = v[b][0] - mw, d1 = v[b][1] - mw;
        float m2 = warp_sum(d0 * d0 + d1 * d1);
        if (lane == 0) sts64(s_stat + (warp * 4 + b * 2) * 4, __float_as_uint(mw), __float_as_uint(m2));
    }
}
__device__ __forceinline__ void ln_stage2(const float (&v)[2][2], float (&y)[2][2], uint32_t s_stat) {
    float mw[2][NCW], m2[2] = {0.f, 0.f}, ms[2] = {0.f, 0.f};
#pragma unroll
    for (int w = 0; w < NCW; w++) {
        uint4 s = lds128(s_stat + w * 16);
        mw[0][w] = __uint_as_float(s.x); m2[0] += __uint_as_float(s.y);
        mw[1][w] = __uint_as_float(s.z); m2[1] += __uint_as_float(s.w);
        ms[0] += mw[0][w]; ms[1] += mw[1][w];
    }
#pragma unroll
    for (int b = 0; b < 2; b++) {
        float mean = ms[b] * (1.0f / NCW);
        float acc = 0.f;
#pragma unroll
        for (int w = 0; w < NCW; w++) { float d = mw[b][w] - mean; acc += d * d; }
        float var = (m2[b] + 64.0f * acc) * (1.0f / DM);
        float mb = rbf(mean), vb = rbf(var);
        float den = rbf(sqrtf(rbf(vb + 1e-5f)));
        y[b][0] = rbf(rbf(v[b][0] - mb) / den);
        y[b][1] = rbf(rbf(v[b][1] - mb) / den);
    }
}

__device__ __forceinline__ void gemv32(uint32_t s_w, uint32_t s_act, uint32_t s_red, int warp, int lane) {
    const int g = lane >> 2, t = lane & 3, mi = lane >> 3, r = lane & 7;
    float c[2][4] = {};
#pragma unroll
    for (int ks = 0; ks < 4; ks++) {
        const int k0 = warp * 64 + ks * 16;
        uint32_t baddr = s_act + (g & 1) * ASTR + (k0 + 2 * t) * 2;
        uint32_t b0 = lds32(baddr), b1 = lds32(baddr + 16);
        const int row = k0 + r + 8 * (mi >> 1);
#pragma unroll
        for (int mt = 0; mt < 2; mt++) {
            uint32_t a[4];
            const int ch = 2 * mt + (mi & 1);
            ldsm4t(a, s_w + row * 64 + ((ch ^ ((row >> 1) & 3)) << 4));
            mma16816(c[mt], a, b0, b1);
        }
    }
    if (t == 0) {
#pragma unroll
        for (int mt = 0; mt < 2; mt++) {
            sts64(s_red + (warp * 64 + (mt * 16 + g) * 2) * 4, __float_as_uint(c[mt][0]), __float_as_uint(c[mt][1]));
            sts64(s_red + (warp * 64 + (mt * 16 + g + 8) * 2) * 4, __float_as_uint(c[mt][2]), __float_as_uint(c[mt][3]));
        }
    }
}

__device__ __forceinline__ void publish_partials(unsigned* part, const float (&c)[4][4], int warp, int lane, int src, unsigned tag) {
    const int g = lane >> 2, t = lane & 3;
    if (t == 0) {
#pragma unroll
        for (int mt = 0; mt < 4; mt++) {
            const int col = warp * 64 + mt * 16 + g;
            unsigned* p = part + ((col >> 2) * NCTA + src) * 8 + (col & 3) * 2;
            stg_rlx2(p, tagf(c[mt][0], tag), tagf(c[mt][1], tag));
            stg_rlx2(p + 2 * NCTA * 8, tagf(c[mt][2], tag), tagf(c[mt][3], tag));
        }
    }
}

__device__ __forceinline__ void reduce_unit(const unsigned* part, int unit, int lane, unsigned tag, float (&s)[4]) {
    const unsigned* p = part + unit * (NCTA * 8) + lane * 4;
    uint4 v[8];
#pragma unroll
    for (int i = 0; i < 8; i++) v[i] = ldg_rlx4(p + i * 128);
    int it = 0;
    while (true) {
        bool ok = true;
#pragma unroll
        for (int i = 0; i < 8; i++) {
            if (!valid4(v[i], tag)) { ok = false; v[i] = ldg_rlx4(p + i * 128); }
        }
        if (ok || ++it >= SPIN_LIMIT) break;
    }
    s[0] = s[1] = s[2] = s[3] = 0.f;
#pragma unroll
    for (int i = 0; i < 8; i++) {
        s[0] += untagf(v[i].x); s[1] += untagf(v[i].y); s[2] += untagf(v[i].z); s[3] += untagf(v[i].w);
    }
    __syncwarp();
#pragma unroll
    for (int o = 2; o <= 16; o <<= 1) {
#pragma unroll
        for (int i = 0; i < 4; i++) s[i] += __shfl_xor_sync(0xffffffffu, s[i], o);
    }
}

__device__ __forceinline__ uint32_t k_off(int i) { return i < 8 ? OFF_K0 + i * 16384 : (i - 8) * 16384; }
__device__ __forceinline__ uint32_t v_off(int i) { return i < 5 ? (8 + i) * 16384 : (i - 5) * 16384; }

__global__ void __launch_bounds__(NTHR, 1)
fused_block_kernel(const __grid_constant__ Maps maps, const __nv_bfloat16* __restrict__ xin,
                   const __nv_bfloat16* __restrict__ cin, const __nv_bfloat16* __restrict__ kcache,
                   __nv_bfloat16* __restrict__ out) {
    extern __shared__ unsigned char smem_raw[];
    const uint32_t sb = (smem_u32(smem_raw) + 1023u) & ~1023u;
    const int tid = threadIdx.x, warp = tid >> 5, lane = tid & 31;
    const int c = blockIdx.x;
    const int kvh = c >> 3, j = c & 7, bb = j & 1, sp = j >> 1;
    const int kvrow0 = (bb * 16 + kvh) * 32768 + 28672 + sp * 1024;
    const uint32_t s_full = sb + OFF_BAR, s_empty = s_full + N_IT * 8;

    if (warp == NCW) {
        TS(lane == 0, 0);
        if (lane < EARLY_PF) {
            const char* p = (const char*)kcache + ((size_t)kvrow0 + lane * 64) * 256;
            asm volatile("cp.async.bulk.prefetch.L2.global [%0], %1;" ::"l"(p), "r"(16384) : "memory");
        }
        for (int i = lane; i < N_IT + N_EM; i += 32) {
            int cnt = 1;
            if (i >= N_IT) { int e = i - N_IT; cnt = e < EM_K ? NCW : (e < EM_V ? 4 : 8); }
            mbar_init(s_full + i * 8, cnt);
        }
        asm volatile("fence.mbarrier_init.release.cluster;" ::: "memory");
        asm volatile("fence.proxy.async.shared::cta;" ::: "memory");
        __syncwarp();
        asm volatile("bar.arrive 2, 320;" ::: "memory");
        if (lane == 0) {
            const int first = (c < NMOD) ? 0 : 2;
            const int gcol = (c * 36) & ~7;
#pragma unroll 1
            for (int i = first; i < N_IT; i++) {
                const int win = (i >= IT_WO) ? WIN_TAIL : WIN_MAIN;
                if (i - win >= first) mbar_wait(s_full + (i - win) * 8);
                const uint32_t bar = s_full + i * 8;
                if (i < IT_WQ) {
                    mbar_expect_tx(bar, 18432);
                    tma3d(sb + OFF_WMOD + i * 18432, &maps.wmod, c * 32, 0, i * 2, bar);
                } else if (i < IT_K) {
                    mbar_expect_tx(bar, 18432);
                    tma3d(sb + OFF_WQ + (i - IT_WQ) * 18432, &maps.wq, c * 32, 0, (i - IT_WQ) * 2, bar);
                } else if (i < IT_V) {
                    const int k = i - IT_K;
                    if (k == 8 && c < NMOD) mbar_wait(s_empty + EM_WMOD * 8);
                    if (k == 10) mbar_wait(s_empty + EM_WQ * 8);
                    if (k >= 12) mbar_wait(s_empty + (EM_K + k - 12) * 8);
                    mbar_expect_tx(bar, 16384);
                    tma3d(sb + k_off(k), &maps.k, 0, kvrow0 + k * 64, 0, bar);
                } else if (i < IT_WO) {
                    const int k = i - IT_V;
                    if (k < 4) mbar_wait(s_empty + (EM_K + 4 + k) * 8);
                    else if (k >= 5 && k < 13) mbar_wait(s_empty + (EM_K + 3 + k) * 8);
                    else if (k >= 13) mbar_wait(s_empty + (EM_V + k - 13) * 8);
                    mbar_expect_tx(bar, 16384);
                    tma3d(sb + v_off(k), &maps.v, 0, kvrow0 + k * 64, 0, bar);
                } else if (i < IT_GU) {
                    const int k = i - IT_WO;
                    mbar_wait(s_empty + (EM_V + (k ? 6 : 4)) * 8);
                    mbar_expect_tx(bar, 18432);
                    tma3d(sb + (k ? OFF_WO1 : OFF_WO0), &maps.wo, 0, kvh * 256 + k * 128 + j * 16, 0, bar);
                } else if (i < IT_WD) {
                    const int k = i - IT_GU, part = k >> 1, up = k & 1;
                    const uint32_t off = (up ? OFF_U : OFF_G) + part * 15360;
                    mbar_wait(s_empty + (EM_V + 5 + ((off + 15359) >> 14)) * 8);
                    mbar_expect_tx(bar, 15360);
                    tma2d(sb + off, up ? &maps.wu : &maps.wg, gcol, part * 192, bar);
                } else {
                    const int k = i - IT_WD;
                    mbar_wait(s_empty + (EM_V + 12 + k) * 8);
                    mbar_expect_tx(bar, k < 2 ? 18432 : 4608);
                    tma3d(sb + OFF_D0 + k * 18432, k < 2 ? &maps.wd : &maps.wd4, 0, c * 36 + k * 16, 0, bar);
                }
                TS(i == IT_WO, 1);
            }
            TS(true, 2);
        }
        return;
    }

    const int g = lane >> 2, t = lane & 3, mi = lane >> 3, r = lane & 7;
    const uint32_t s_act = sb + OFF_ACT, s_p = sb + OFF_P, s_stat = sb + OFF_STAT;

    unsigned ep;
    asm volatile("ld.relaxed.gpu.global.u32 %0, [%1];" : "=r"(ep) : "l"(&g_epoch) : "memory");
    float xv[2][2];
    {
        uint32_t xw[2], cw[2];
#pragma unroll
        for (int b = 0; b < 2; b++) {
            xw[b] = __ldg((const unsigned*)(xin + b * DM) + tid);
            cw[b] = __ldg((const unsigned*)(cin + b * DM) + tid);
        }
#pragma unroll
        for (int b = 0; b < 2; b++) {
            xv[b][0] = bflo(xw[b]); xv[b][1] = bfhi(xw[b]);
            float c0 = bflo(cw[b]), c1 = bfhi(cw[b]);
            float s0 = c0 / (1.0f + expf(-c0)), s1 = c1 / (1.0f + expf(-c1));
            sts32(s_act + b * ASTR + tid * 4, pack2(s0, s1));
        }
    }
    const unsigned tag = (ep + 1u) & 1u;
    ln_stage1(xv, s_stat, warp, lane);
    asm volatile("bar.sync 2, 320;" ::: "memory");

    if (c < NMOD) {
        if (warp <= 4) mbar_wait(s_full + (IT_WMOD + 0) * 8);
        if (warp >= 4) mbar_wait(s_full + (IT_WMOD + 1) * 8);
        gemv32(sb + OFF_WMOD, s_act, sb + OFF_REDA, warp, lane);
        __syncwarp();
        if (lane == 0) mbar_arrive(s_empty + EM_WMOD * 8);
        bar_consumers();
        if (tid < 64) {
            float s = 0.f;
#pragma unroll
            for (int w = 0; w < NCW; w++) s += ldsf(sb + OFF_REDA + (w * 64 + tid) * 4);
            stg_rlx1(g_mod + c * 64 + tid, (bfbits(s) << 16) | tag);
        }
    }
    TS(tid == 0, 4);
    {
        float y[2][2];
        ln_stage2(xv, y, s_stat);
        uint4 sa = poll4(g_mod + tid * 4, tag);
        uint4 ca = poll4(g_mod + 1152 + tid * 4, tag);
        float h00 = rbf(rbf(y[0][0] * rbf(1.0f + bfhi(ca.x))) + bfhi(sa.x));
        float h10 = rbf(rbf(y[1][0] * rbf(1.0f + bfhi(ca.y))) + bfhi(sa.y));
        float h01 = rbf(rbf(y[0][1] * rbf(1.0f + bfhi(ca.z))) + bfhi(sa.z));
        float h11 = rbf(rbf(y[1][1] * rbf(1.0f + bfhi(ca.w))) + bfhi(sa.w));
        __syncwarp();
        sts32(s_act + tid * 4, pack2(h00, h01));
        sts32(s_act + ASTR + tid * 4, pack2(h10, h11));
        __syncwarp();
    }
    TS(tid == 0, 5);
    if (warp <= 4) mbar_wait(s_full + (IT_WQ + 0) * 8);
    if (warp >= 4) mbar_wait(s_full + (IT_WQ + 1) * 8);
    gemv32(sb + OFF_WQ, s_act, sb + OFF_REDB, warp, lane);
    __syncwarp();
    if (lane == 0) mbar_arrive(s_empty + EM_WQ * 8);
    bar_consumers();
    if (tid < 64) {
        float s = 0.f;
#pragma unroll
        for (int w = 0; w < NCW; w++) s += ldsf(sb + OFF_REDB + (w * 64 + tid) * 4);
        stg_rlx1(g_q + (tid & 1) * 4096 + c * 32 + (tid >> 1), (bfbits(s) << 16) | tag);
        uint4 qv = poll4(g_q + bb * 4096 + kvh * 256 + tid * 4, tag);
        sts64(sb + OFF_QS + (tid >> 5) * 272 + (tid & 31) * 8,
              (qv.x >> 16) | (qv.y & 0xffff0000u), (qv.z >> 16) | (qv.w & 0xffff0000u));
    }
    bar_consumers();
    TS(tid == 0, 6);

    const int unit = (warp == 0) ? c : NCTA + c;
    const bool is_red = (warp == 0) || (warp == 1 && c < 16);

    if (warp < 8) {
        uint32_t qf[8][2];
#pragma unroll
        for (int ks = 0; ks < 8; ks++) {
            uint32_t a = sb + OFF_QS + (g & 1) * 272 + (ks * 16 + 2 * t) * 2;
            qf[ks][0] = lds32(a); qf[ks][1] = lds32(a + 16);
        }
        const int mt = warp & 3;
        const int key = mt * 16 + r + 8 * (mi & 1);
        const uint32_t rowoff = key * 128;
        float mx0 = -INFINITY, mx1 = -INFINITY;
#pragma unroll 1
        for (int i = (warp >> 2); i < 16; i += 2) {
            mbar_wait(s_full + (IT_K + i) * 8);
            const uint32_t base = sb + k_off(i) + rowoff;
            float c0[4] = {}, c1[4] = {};
#pragma unroll
            for (int ks = 0; ks < 4; ks++) {
                uint32_t a[4], a2[4];
                const uint32_t sw = (((2 * ks + (mi >> 1)) ^ r) << 4);
                ldsm4(a, base + sw);
                ldsm4(a2, base + 8192 + sw);
                mma16816(c0, a, qf[ks][0], qf[ks][1]);
                mma16816(c1, a2, qf[ks + 4][0], qf[ks + 4][1]);
            }
            __syncwarp();
            if (lane == 0) mbar_arrive(s_empty + (EM_K + i) * 8);
            if (t == 0) {
                const float sc = 0.08838834764831845f;
                float s00 = rbf(rbf(c0[0] + c1[0]) * sc), s01 = rbf(rbf(c0[1] + c1[1]) * sc);
                float s10 = rbf(rbf(c0[2] + c1[2]) * sc), s11 = rbf(rbf(c0[3] + c1[3]) * sc);
                mx0 = fmaxf(mx0, fmaxf(s00, s10)); mx1 = fmaxf(mx1, fmaxf(s01, s11));
                const uint32_t pa = s_p + (i * 64 + 16 * (g >> 1) + 4 * mt + (g & 1)) * 2;
                sts16(pa, __float_as_uint(s00) >> 16);
                sts16(pa + 4, __float_as_uint(s10) >> 16);
                sts16(pa + PSTR, __float_as_uint(s01) >> 16);
                sts16(pa + PSTR + 4, __float_as_uint(s11) >> 16);
            }
        }
#pragma unroll
        for (int o = 4; o <= 16; o <<= 1) {
            mx0 = fmaxf(mx0, __shfl_xor_sync(0xffffffffu, mx0, o));
            mx1 = fmaxf(mx1, __shfl_xor_sync(0xffffffffu, mx1, o));
        }
        if (lane == 0) sts64(sb + OFF_WMX + warp * 8, __float_as_uint(mx0), __float_as_uint(mx1));
    }
    bar_consumers();
    TS(tid == 0, 7);
    float sv[8];
    float mloc = -INFINITY;
    const int hd = (warp >> 2) & 1;
    const float L2E = 1.4426950408889634f;
    if (warp < 8) {
#pragma unroll
        for (int w = 0; w < 8; w++) mloc = fmaxf(mloc, ldsf(sb + OFF_WMX + w * 8 + hd * 4));
        uint4 sw = lds128(s_p + hd * PSTR + (tid & 127) * 16);
        sv[0] = bflo(sw.x); sv[1] = bfhi(sw.x); sv[2] = bflo(sw.y); sv[3] = bfhi(sw.y);
        sv[4] = bflo(sw.z); sv[5] = bfhi(sw.z); sv[6] = bflo(sw.w); sv[7] = bfhi(sw.w);
        float e = 0.f;
#pragma unroll
        for (int i = 0; i < 8; i++) e += exp2f((sv[i] - mloc) * L2E);
        e = warp_sum(e);
        if (lane == 0) stsf(sb + OFF_WMX + 64 + warp * 4, e);
    }
    bar_consumers();
    if (warp < 8) {
        uint4 l0 = lds128(sb + OFF_WMX + 64), l1 = lds128(sb + OFF_WMX + 80);
        float ll0 = (__uint_as_float(l0.x) + __uint_as_float(l0.y)) + (__uint_as_float(l0.z) + __uint_as_float(l0.w));
        float ll1 = (__uint_as_float(l1.x) + __uint_as_float(l1.y)) + (__uint_as_float(l1.z) + __uint_as_float(l1.w));
        if (warp == 0 && lane < 2) {
            float m1 = -INFINITY;
#pragma unroll
            for (int w = 0; w < 8; w++) m1 = fmaxf(m1, ldsf(sb + OFF_WMX + w * 8 + 4));
            stg_rlx4(g_ml + c * 8 + lane * 4, make_uint4(tagf(mloc, tag), tagf(ll0, tag), tagf(m1, tag), tagf(ll1, tag)));
        }
        float ms = mloc, ls = untagf(__float_as_uint(hd ? ll1 : ll0));
        const int s2 = lane & 3;
        if (lane < 4 && s2 != sp) {
            uint4 v = poll4(g_ml + (kvh * 8 + s2 * 2 + bb) * 8, tag);
            ms = untagf(hd ? v.z : v.x); ls = untagf(hd ? v.w : v.y);
        }
        __syncwarp();
        float mg = fmaxf(ms, __shfl_xor_sync(0xffffffffu, ms, 1));
        mg = fmaxf(mg, __shfl_xor_sync(0xffffffffu, mg, 2));
        float lg = ls * exp2f((ms - mg) * L2E);
        lg += __shfl_xor_sync(0xffffffffu, lg, 1);
        lg += __shfl_xor_sync(0xffffffffu, lg, 2);
        mg = __shfl_sync(0xffffffffu, mg, 0);
        lg = __shfl_sync(0xffffffffu, lg, 0);
        const float inv = 1.0f / lg;
        float p[8];
#pragma unroll
        for (int i = 0; i < 8; i++) p[i] = exp2f((sv[i] - mg) * L2E) * inv;
        sts128(s_p + hd * PSTR + (tid & 127) * 16,
               make_uint4(pack2(p[0], p[1]), pack2(p[2], p[3]), pack2(p[4], p[5]), pack2(p[6], p[7])));
    }
    uint4 sbv = poll4(g_mod + 3 * 1152 + tid * 4, tag);
    uint4 cbv = poll4(g_mod + 4 * 1152 + tid * 4, tag);
    uint4 gav = make_uint4(0, 0, 0, 0), gbv = gav;
    float xr[4] = {0.f, 0.f, 0.f, 0.f};
    if (is_red) {
        gav = poll4(g_mod + 2 * 1152 + unit * 8 + (lane & 1) * 4, tag);
        gbv = poll4(g_mod + 5 * 1152 + unit * 8 + (lane & 1) * 4, tag);
        const int col = unit * 4 + (lane & 1) * 2;
        uint32_t x0 = __ldg((const unsigned*)(xin + col)), x1 = __ldg((const unsigned*)(xin + DM + col));
        xr[0] = bflo(x0); xr[1] = bflo(x1); xr[2] = bfhi(x0); xr[3] = bfhi(x1);
    }
    bar_consumers();
    TS(tid == 0, 8);

    if (warp < 8) {
        float c0[4] = {}, c1[4] = {};
        const uint32_t vo = (warp >> 2) * 8192 + (r + 8 * (mi >> 1)) * 128 + ((((2 * warp + (mi & 1)) & 7) ^ r) << 4);
        const uint32_t pa = s_p + (g & 1) * PSTR + t * 32;
#pragma unroll 1
        for (int i = 0; i < 16; i++) {
            uint4 pb0 = lds128(pa + i * 128), pb1 = lds128(pa + i * 128 + 16);
            mbar_wait(s_full + (IT_V + i) * 8);
            const uint32_t base = sb + v_off(i) + vo;
            uint32_t a0[4], a1[4], a2[4], a3[4];
            ldsm4t(a0, base); ldsm4t(a1, base + 2048); ldsm4t(a2, base + 4096); ldsm4t(a3, base + 6144);
            mma16816(c0, a0, pb0.x, pb0.y);
            mma16816(c1, a1, pb0.z, pb0.w);
            mma16816(c0, a2, pb1.x, pb1.y);
            mma16816(c1, a3, pb1.z, pb1.w);
            __syncwarp();
            if (lane == 0) mbar_arrive(s_empty + (EM_V + i) * 8);
        }
        if (t == 0) {
            unsigned* p = g_op + c * 256 + (warp * 16 + g) * 2;
            stg_rlx2(p, tagf(c0[0] + c1[0], tag), tagf(c0[1] + c1[1], tag));
            stg_rlx2(p + 16, tagf(c0[2] + c1[2], tag), tagf(c0[3] + c1[3], tag));
        }
        TS(tid == 0, 9);
    } else {
        mbar_wait(s_full + (IT_V + 15) * 8);
        const unsigned* p = g_op + (kvh * 8 + g) * 256 + (j * 16 + 2 * t) * 2;
        uint4 lo = ldg_rlx4(p), hi = ldg_rlx4(p + 16);
        int it = 0;
        while (true) {
            bool ok = true;
            if (!valid4(lo, tag)) { ok = false; lo = ldg_rlx4(p); }
            if (!valid4(hi, tag)) { ok = false; hi = ldg_rlx4(p + 16); }
            if (ok || ++it >= SPIN_LIMIT) break;
        }
        float o[8] = {untagf(lo.x), untagf(lo.y), untagf(lo.z), untagf(lo.w), untagf(hi.x), untagf(hi.y), untagf(hi.z), untagf(hi.w)};
        __syncwarp();
#pragma unroll
        for (int sft = 8; sft <= 16; sft <<= 1) {
#pragma unroll
            for (int i = 0; i < 8; i++) o[i] += __shfl_xor_sync(0xffffffffu, o[i], sft);
        }
        sts128(sb + OFF_OF + lane * 16, make_uint4(pack2(o[0], o[2]), pack2(o[4], o[6]), pack2(o[1], o[3]), pack2(o[5], o[7])));
        TS(lane == 0, 10);
    }

    {
        uint32_t a[2][4][4];
        const uint32_t wo_in = warp * 2048 + (r + 8 * (mi >> 1)) * 128;
        mbar_wait(s_full + (IT_WO + 0) * 8);
#pragma unroll
        for (int mt = 0; mt < 4; mt++) ldsm4t(a[0][mt], sb + OFF_WO0 + wo_in + (((2 * mt + (mi & 1)) ^ r) << 4));
        mbar_wait(s_full + (IT_WO + 1) * 8);
#pragma unroll
        for (int mt = 0; mt < 4; mt++) ldsm4t(a[1][mt], sb + OFF_WO1 + wo_in + (((2 * mt + (mi & 1)) ^ r) << 4));
        bar_consumers();
        uint4 of = lds128(sb + OFF_OF + lane * 16);
        float cc[4][4] = {};
#pragma unroll
        for (int mt = 0; mt < 4; mt++) mma16816(cc[mt], a[0][mt], of.x, of.y);
#pragma unroll
        for (int mt = 0; mt < 4; mt++) mma16816(cc[mt], a[1][mt], of.z, of.w);
        publish_partials(g_p1, cc, warp, lane, c, tag);
    }
    TS(tid == 0, 11);
    float x1r[4] = {0.f, 0.f, 0.f, 0.f};
    if (is_red) {
        float s[4];
        reduce_unit(g_p1, unit, lane, tag, s);
        x1r[0] = rbf(xr[0] + rbf(bfhi(gav.x) * rbf(s[0])));
        x1r[1] = rbf(xr[1] + rbf(bfhi(gav.y) * rbf(s[1])));
        x1r[2] = rbf(xr[2] + rbf(bfhi(gav.z) * rbf(s[2])));
        x1r[3] = rbf(xr[3] + rbf(bfhi(gav.w) * rbf(s[3])));
        if (lane < 2)
            stg_rlx4(g_x1 + unit * 8 + lane * 4,
                     make_uint4(__float_as_uint(x1r[0]) | tag, __float_as_uint(x1r[1]) | tag,
                                __float_as_uint(x1r[2]) | tag, __float_as_uint(x1r[3]) | tag));
    }
    TS(tid == 0, 12);
    bar_consumers();
    {
        uint4 xw = poll4(g_x1 + tid * 4, tag);
        float v[2][2] = {{bfhi(xw.x), bfhi(xw.z)}, {bfhi(xw.y), bfhi(xw.w)}};
        __syncwarp();
        ln_stage1(v, s_stat + 160, warp, lane);
        bar_consumers();
        TS(tid == 0, 13);
        float y[2][2];
        ln_stage2(v, y, s_stat + 160);
        float h00 = rbf(rbf(y[0][0] * rbf(1.0f + bfhi(cbv.x))) + bfhi(sbv.x));
        float h10 = rbf(rbf(y[1][0] * rbf(1.0f + bfhi(cbv.y))) + bfhi(sbv.y));
        float h01 = rbf(rbf(y[0][1] * rbf(1.0f + bfhi(cbv.z))) + bfhi(sbv.z));
        float h11 = rbf(rbf(y[1][1] * rbf(1.0f + bfhi(cbv.w))) + bfhi(sbv.w));
        sts32(s_act + tid * 4, pack2(h00, h01));
        sts32(s_act + ASTR + tid * 4, pack2(h10, h11));
        __syncwarp();
    }
    {
        uint32_t bf[4][2];
#pragma unroll
        for (int ks = 0; ks < 4; ks++) {
            uint32_t baddr = s_act + (g & 1) * ASTR + (warp * 64 + ks * 16 + 2 * t) * 2;
            bf[ks][0] = lds32(baddr); bf[ks][1] = lds32(baddr + 16);
        }
        const int part = warp / 3;
        mbar_wait(s_full + (IT_GU + 2 * part) * 8);
        mbar_wait(s_full + (IT_GU + 2 * part + 1) * 8);
        float cc[5][4] = {};
        const uint32_t abase = sb + ((mi & 1) ? OFF_U : OFF_G) + (warp * 64 + r + 8 * (mi >> 1)) * 80;
#pragma unroll
        for (int ks = 0; ks < 4; ks++) {
#pragma unroll
            for (int q = 0; q < 5; q++) {
                uint32_t a[4];
                ldsm4t(a, abase + ks * 1280 + q * 16);
                mma16816(cc[q], a, bf[ks][0], bf[ks][1]);
            }
        }
        if (t == 0) {
#pragma unroll
            for (int q = 0; q < 5; q++)
                sts128(sb + OFF_REDC + (warp * 160 + (q * 8 + g) * 4) * 4,
                       make_uint4(__float_as_uint(cc[q][0]), __float_as_uint(cc[q][1]), __float_as_uint(cc[q][2]), __float_as_uint(cc[q][3])));
        }
    }
    bar_consumers();
    TS(tid == 0, 14);
    if (tid < 160) {
        float s = 0.f;
#pragma unroll
        for (int w = 0; w < NCW; w++) s += ldsf(sb + OFF_REDC + (w * 160 + tid) * 4);
        s = rbf(s);
        float u = __shfl_down_sync(0xffffffffu, s, 2);
        const int rr = (tid >> 2) - (c & 1) * 4;
        if ((tid & 2) == 0 && rr >= 0 && rr < 36) {
            float gt = s * (s > 0.f ? 1.0f : 0.0f);
            sts16(sb + OFF_HH + (tid & 1) * 112 + rr * 2, bfbits(gt * u));
        }
    } else if (tid < 172) {
        const int i = tid - 160;
        sts32(sb + OFF_HH + (i / 6) * 112 + 72 + (i % 6) * 4, 0u);
    }
    bar_consumers();
    {
        float cc[4][4] = {};
        const uint32_t hb = sb + OFF_HH + (g & 1) * 112 + t * 4;
#pragma unroll
        for (int ks = 0; ks < 2; ks++) {
            uint32_t b0 = lds32(hb + ks * 32), b1 = lds32(hb + ks * 32 + 16);
            mbar_wait(s_full + (IT_WD + ks) * 8);
            const uint32_t base = sb + OFF_D0 + ks * 18432 + warp * 2048 + (r + 8 * (mi >> 1)) * 128;
#pragma unroll
            for (int mt = 0; mt < 4; mt++) {
                uint32_t a[4];
                ldsm4t(a, base + (((2 * mt + (mi & 1)) ^ r) << 4));
                mma16816(cc[mt], a, b0, b1);
            }
        }
        {
            uint32_t b0 = lds32(hb + 64), b1 = lds32(hb + 80);
            mbar_wait(s_full + (IT_WD + 2) * 8);
            const int row = warp * 4 + (r & 3);
            const uint32_t base = sb + OFF_D2 + row * 128;
#pragma unroll
            for (int mt = 0; mt < 4; mt++) {
                uint32_t a[4];
                ldsm4t(a, base + (((2 * mt + (mi & 1)) ^ (row & 7)) << 4));
                mma16816(cc[mt], a, b0, b1);
            }
        }
        publish_partials(g_p2, cc, warp, lane, c, tag);
    }
    TS(tid == 0, 15);
    if (is_red) {
        float s[4];
        reduce_unit(g_p2, unit, lane, tag, s);
        if (lane < 2) {
            float o0 = x1r[0] + rbf(bfhi(gbv.x) * rbf(s[0]));
            float o1 = x1r[1] + rbf(bfhi(gbv.y) * rbf(s[1]));
            float o2 = x1r[2] + rbf(bfhi(gbv.z) * rbf(s[2]));
            float o3 = x1r[3] + rbf(bfhi(gbv.w) * rbf(s[3]));
            const int col = unit * 4 + lane * 2;
            *(unsigned*)(out + col) = pack2(o0, o2);
            *(unsigned*)(out + DM + col) = pack2(o1, o3);
        }
        if (c == 0 && tid == 0) stg_rlx1(&g_epoch, ep + 1u);
        TS(tid == 0, 16);
    }
}

typedef CUresult (*EncodeFn)(CUtensorMap*, CUtensorMapDataType, cuuint32_t, void*, const cuuint64_t*, const cuuint64_t*,
                             const cuuint32_t*, const cuuint32_t*, CUtensorMapInterleave, CUtensorMapSwizzle,
                             CUtensorMapL2promotion, CUtensorMapFloatOOBfill);

void make_map(EncodeFn enc, CUtensorMap* m, const void* p, int rank, cuuint64_t d0, cuuint64_t d1, cuuint64_t d2,
              cuuint64_t s1, cuuint64_t s2, cuuint32_t b0, cuuint32_t b1, cuuint32_t b2, CUtensorMapSwizzle sw) {
    cuuint64_t dims[3] = {d0, d1, d2};
    cuuint64_t str[2] = {s1, s2};
    cuuint32_t box[3] = {b0, b1, b2};
    cuuint32_t es[3] = {1, 1, 1};
    enc(m, CU_TENSOR_MAP_DATA_TYPE_BFLOAT16, rank, const_cast<void*>(p), dims, str, box, es,
        CU_TENSOR_MAP_INTERLEAVE_NONE, sw, CU_TENSOR_MAP_L2_PROMOTION_L2_256B, CU_TENSOR_MAP_FLOAT_OOB_FILL_NONE);
}

}

extern "C" void kernel_launch(void* const* d_in, const int* in_sizes, int n_in, void* d_out, int out_size) {
    (void)in_sizes; (void)n_in; (void)out_size;
    void* fn = nullptr;
    cudaDriverEntryPointQueryResult qr;
    cudaGetDriverEntryPoint("cuTensorMapEncodeTiled", &fn, cudaEnableDefault, &qr);
    EncodeFn enc = (EncodeFn)fn;
    cudaFuncSetAttribute(fused_block_kernel, cudaFuncAttributeMaxDynamicSharedMemorySize, SMEM_BYTES);

    const void *x = d_in[0], *kc = d_in[1], *vc = d_in[2], *wq = d_in[3], *wo = d_in[4];
    const void *wg = d_in[6], *wu = d_in[7], *wd = d_in[8], *cc = d_in[9], *wmod = d_in[10];
    const CUtensorMapSwizzle S128 = CU_TENSOR_MAP_SWIZZLE_128B, S64 = CU_TENSOR_MAP_SWIZZLE_64B, S0 = CU_TENSOR_MAP_SWIZZLE_NONE;
    Maps m;
    make_map(enc, &m.k, kc, 3, 64, 32ull * 32768, 2, 256, 128, 64, 64, 2, S128);
    make_map(enc, &m.v, vc, 3, 64, 32ull * 32768, 2, 256, 128, 64, 64, 2, S128);
    make_map(enc, &m.wmod, wmod, 3, 3456, 144, 4, 3456 * 2, 3456 * 2 * 144, 32, 144, 2, S64);
    make_map(enc, &m.wq, wq, 3, 4096, 144, 4, 4096 * 2, 4096 * 2 * 144, 32, 144, 2, S64);
    make_map(enc, &m.wg, wg, 2, 4608, 576, 1, 4608 * 2, 0, 40, 192, 1, S0);
    make_map(enc, &m.wu, wu, 2, 4608, 576, 1, 4608 * 2, 0, 40, 192, 1, S0);
    make_map(enc, &m.wo, wo, 3, 64, 4096, 9, 1152, 128, 64, 16, 9, S128);
    make_map(enc, &m.wd, wd, 3, 64, 4608, 9, 1152, 128, 64, 16, 9, S128);
    make_map(enc, &m.wd4, wd, 3, 64, 4608, 9, 1152, 128, 64, 4, 9, S128);
    fused_block_kernel<<<NCTA, NTHR, SMEM_BYTES>>>(m, (const __nv_bfloat16*)x, (const __nv_bfloat16*)cc,
                                                   (const __nv_bfloat16*)kc, (__nv_bfloat16*)d_out);
}
```

```cpp
#include <cuda_runtime.h>
#include <cuda.h>
#include <cuda_bf16.h>
#include <stdint.h>

namespace {

constexpr int DM = 576;
constexpr int NCTA = 128;
constexpr int NCW = 9;
#define NWARM 4
constexpr int NTHR = (NCW + 1 + NWARM) * 32;
constexpr int NMOD = 108;

#define WIN_MAIN 4
#define WIN_TAIL 3
#define EARLY_PF 2

constexpr int IT_WMOD = 0, IT_WQ = 2, IT_K = 4, IT_V = 20, IT_WO = 36, IT_GU = 38, IT_WD = 44, N_IT = 47;
constexpr int EM_WMOD = 0, EM_WQ = 1, EM_K = 2, EM_V = 18, N_EM = 34;

constexpr int RING = 13 * 16384;
constexpr int OFF_WMOD = 0, OFF_WQ = 36864, OFF_K0 = 73728;
constexpr int OFF_WO0 = 180224, OFF_WO1 = 0, OFF_G = 18432, OFF_U = 64512;
constexpr int OFF_D0 = 110592, OFF_D1 = 129024, OFF_D2 = 147456;
constexpr int PSTR = 2064;
constexpr int OFF_P = RING;
constexpr int OFF_S = OFF_P + 4160;
constexpr int OFF_RED = OFF_S + 4096;
constexpr int OFF_QS = OFF_RED + 5760;
constexpr int OFF_FR = OFF_QS + 640;
constexpr int OFF_STAT = OFF_FR + 384;
constexpr int OFF_WMX = OFF_STAT + 320;
constexpr int OFF_BAR = OFF_WMX + 128;
constexpr int SMEM_USED = OFF_BAR + (N_IT + N_EM) * 8;
constexpr int SMEM_BYTES = SMEM_USED + 1024;
static_assert(SMEM_BYTES <= 232448, "smem");

struct Maps { CUtensorMap m[9]; };
enum { M_K, M_V, M_WMOD, M_WQ, M_WG, M_WU, M_WO, M_WD, M_WD4 };

constexpr int G_EPOCH = 0;
constexpr int G_MOD = 32;
constexpr int G_X1 = G_MOD + 6912;
constexpr int G_Q = G_X1 + 1152;
constexpr int G_ML = G_Q + 8192;
constexpr int G_OP = G_ML + NCTA * 8;
constexpr int G_PART = G_OP + NCTA * 256;
constexpr int PART_WORDS = 144 * NCTA * 8;
constexpr int G_WORDS = G_PART + 2 * PART_WORDS;
__device__ __align__(128) unsigned g_scr[G_WORDS];

constexpr int SPIN_LIMIT = 1 << 20;

__device__ __forceinline__ uint32_t smem_u32(const void* p) { return (uint32_t)__cvta_generic_to_shared(p); }
__device__ __forceinline__ void mbar_init(uint32_t bar, int cnt) {
    asm volatile("mbarrier.init.shared::cta.b64 [%0], %1;" ::"r"(bar), "r"(cnt) : "memory");
}
__device__ __forceinline__ void mbar_expect_tx(uint32_t bar, uint32_t bytes) {
    asm volatile("mbarrier.arrive.expect_tx.shared::cta.b64 _, [%0], %1;" ::"r"(bar), "r"(bytes) : "memory");
}
__device__ __forceinline__ void mbar_arrive(uint32_t bar) {
    asm volatile("mbarrier.arrive.shared::cta.b64 _, [%0];" ::"r"(bar) : "memory");
}
__device__ __forceinline__ void mbar_wait(uint32_t bar) {
    asm volatile("{\n.reg .pred p;\nW_%=:\nmbarrier.try_wait.parity.shared::cta.b64 p, [%0], 0;\n@!p bra W_%=;\n}"
                 ::"r"(bar) : "memory");
}
__device__ __forceinline__ void tma3d(uint32_t dst, const CUtensorMap* m, int x, int y, int z, uint32_t bar) {
    asm volatile("cp.async.bulk.tensor.3d.shared::cluster.global.mbarrier::complete_tx::bytes [%0], [%1, {%3, %4, %5}], [%2];"
                 ::"r"(dst), "l"(m), "r"(bar), "r"(x), "r"(y), "r"(z) : "memory");
}
__device__ __forceinline__ void bar_consumers() { asm volatile("bar.sync 1, 288;" ::: "memory"); }

__device__ __forceinline__ void ldsm4(uint32_t (&a)[4], uint32_t addr) {
    asm volatile("ldmatrix.sync.aligned.m8n8.x4.shared.b16 {%0,%1,%2,%3}, [%4];"
                 : "=r"(a[0]), "=r"(a[1]), "=r"(a[2]), "=r"(a[3]) : "r"(addr) : "memory");
}
__device__ __forceinline__ void ldsm4t(uint32_t (&a)[4], uint32_t addr) {
    asm volatile("ldmatrix.sync.aligned.m8n8.x4.trans.shared.b16 {%0,%1,%2,%3}, [%4];"
                 : "=r"(a[0]), "=r"(a[1]), "=r"(a[2]), "=r"(a[3]) : "r"(addr) : "memory");
}
__device__ __forceinline__ void mma16816(float (&c)[4], const uint32_t (&a)[4], uint32_t b0, uint32_t b1) {
    asm volatile("mma.sync.aligned.m16n8k16.row.col.f32.bf16.bf16.f32 {%0,%1,%2,%3}, {%4,%5,%6,%7}, {%8,%9}, {%0,%1,%2,%3};"
                 : "+f"(c[0]), "+f"(c[1]), "+f"(c[2]), "+f"(c[3])
                 : "r"(a[0]), "r"(a[1]), "r"(a[2]), "r"(a[3]), "r"(b0), "r"(b1));
}
__device__ __forceinline__ float ldsf(uint32_t a) { float v; asm volatile("ld.shared.f32 %0, [%1];" : "=f"(v) : "r"(a) : "memory"); return v; }
__device__ __forceinline__ uint2 lds64(uint32_t a) {
    uint2 v; asm volatile("ld.shared.v2.u32 {%0,%1}, [%2];" : "=r"(v.x), "=r"(v.y) : "r"(a) : "memory"); return v;
}
__device__ __forceinline__ uint4 lds128(uint32_t a) {
    uint4 v; asm volatile("ld.shared.v4.u32 {%0,%1,%2,%3}, [%4];" : "=r"(v.x), "=r"(v.y), "=r"(v.z), "=r"(v.w) : "r"(a) : "memory"); return v;
}
__device__ __forceinline__ void sts16(uint32_t a, uint32_t v) { asm volatile("st.shared.u16 [%0], %1;" ::"r"(a), "h"((unsigned short)v) : "memory"); }
__device__ __forceinline__ void sts32(uint32_t a, uint32_t v) { asm volatile("st.shared.u32 [%0], %1;" ::"r"(a), "r"(v) : "memory"); }
__device__ __forceinline__ void sts64(uint32_t a, uint32_t x, uint32_t y) { asm volatile("st.shared.v2.u32 [%0], {%1,%2};" ::"r"(a), "r"(x), "r"(y) : "memory"); }
__device__ __forceinline__ void sts128(uint32_t a, uint32_t x, uint32_t y, uint32_t z, uint32_t w) {
    asm volatile("st.shared.v4.u32 [%0], {%1,%2,%3,%4};" ::"r"(a), "r"(x), "r"(y), "r"(z), "r"(w) : "memory");
}
__device__ __forceinline__ void sts128f(uint32_t a, const float (&c)[4]) {
    asm volatile("st.shared.v4.f32 [%0], {%1,%2,%3,%4};" ::"r"(a), "f"(c[0]), "f"(c[1]), "f"(c[2]), "f"(c[3]) : "memory");
}
__device__ __forceinline__ unsigned ldg_rlx1(const unsigned* p) {
    unsigned v; asm volatile("ld.relaxed.gpu.global.u32 %0, [%1];" : "=r"(v) : "l"(p) : "memory"); return v;
}
__device__ __forceinline__ uint4 ldg_rlx4(const unsigned* p) {
    uint4 v; asm volatile("ld.relaxed.gpu.global.v4.u32 {%0,%1,%2,%3}, [%4];" : "=r"(v.x), "=r"(v.y), "=r"(v.z), "=r"(v.w) : "l"(p) : "memory"); return v;
}
__device__ __forceinline__ uint4 ldg_pkt(const unsigned* p) {
    uint4 v;
    asm volatile("{\n.reg .b128 t;\n.reg .b64 lo, hi;\nld.relaxed.gpu.global.b128 t, [%4];\nmov.b128 {lo, hi}, t;\n"
                 "mov.b64 {%0,%1}, lo;\nmov.b64 {%2,%3}, hi;\n}"
                 : "=r"(v.x), "=r"(v.y), "=r"(v.z), "=r"(v.w) : "l"(p) : "memory");
    return v;
}
__device__ __forceinline__ void stg_pkt(unsigned* p, float a, float b, float c, float d, unsigned tag) {
    unsigned x = (__float_as_uint(a) & ~1u) | tag;
    asm volatile("{\n.reg .b128 t;\n.reg .b64 lo, hi;\nmov.b64 lo, {%1,%2};\nmov.b64 hi, {%3,%4};\nmov.b128 t, {lo, hi};\n"
                 "st.relaxed.gpu.global.b128 [%0], t;\n}"
                 ::"l"(p), "r"(x), "r"(__float_as_uint(b)), "r"(__float_as_uint(c)), "r"(__float_as_uint(d)) : "memory");
}
__device__ __forceinline__ void stg_rlx1(unsigned* p, unsigned x) { asm volatile("st.relaxed.gpu.global.u32 [%0], %1;" ::"l"(p), "r"(x) : "memory"); }
__device__ __forceinline__ unsigned bad4(const uint4& v, unsigned tag) {
    return ((v.x ^ tag) | (v.y ^ tag)) | ((v.z ^ tag) | (v.w ^ tag));
}
__device__ __forceinline__ float untagf(unsigned w) { return __uint_as_float(w & ~1u); }
__device__ __forceinline__ uint32_t pack2(float lo, float hi) {
    uint32_t r; asm("cvt.rn.bf16x2.f32 %0, %1, %2;" : "=r"(r) : "f"(hi), "f"(lo)); return r;
}
__device__ __forceinline__ float bflo(uint32_t w) { return __uint_as_float(w << 16); }
__device__ __forceinline__ float bfhi(uint32_t w) { return __uint_as_float(w & 0xffff0000u); }
__device__ __forceinline__ uint32_t hi2(uint32_t a, uint32_t b) { return __byte_perm(a, b, 0x7632); }
__device__ __forceinline__ uint32_t badd2(uint32_t a, uint32_t b) { uint32_t r; asm("add.rn.bf16x2 %0, %1, %2;" : "=r"(r) : "r"(a), "r"(b)); return r; }
__device__ __forceinline__ uint32_t bsub2(uint32_t a, uint32_t b) { uint32_t r; asm("sub.rn.bf16x2 %0, %1, %2;" : "=r"(r) : "r"(a), "r"(b)); return r; }
__device__ __forceinline__ uint32_t bmul2(uint32_t a, uint32_t b) { uint32_t r; asm("mul.rn.bf16x2 %0, %1, %2;" : "=r"(r) : "r"(a), "r"(b)); return r; }
__device__ __forceinline__ uint32_t bmax2(uint32_t a, uint32_t b) { uint32_t r; asm("max.bf16x2 %0, %1, %2;" : "=r"(r) : "r"(a), "r"(b)); return r; }
__device__ __forceinline__ float ex2(float x) { float r; asm("ex2.approx.ftz.f32 %0, %1;" : "=f"(r) : "f"(x)); return r; }
__device__ __forceinline__ float rcp(float x) { float r; asm("rcp.approx.ftz.f32 %0, %1;" : "=f"(r) : "f"(x)); return r; }
__device__ __forceinline__ float fsqrt(float x) { float r; asm("sqrt.approx.ftz.f32 %0, %1;" : "=f"(r) : "f"(x)); return r; }
__device__ __forceinline__ float shx(float v, int m) { return __shfl_xor_sync(0xffffffffu, v, m); }
#define TS(cond, slot) do { } while (0)

__device__ __forceinline__ uint32_t k_off(int i) { return i < 8 ? OFF_K0 + i * 16384 : (i - 8) * 16384; }
__device__ __forceinline__ uint32_t v_off(int i) { return i < 5 ? (8 + i) * 16384 : (i - 5) * 16384; }

enum { SEG_LN = 1, SEG_GEMV = 2, SEG_K = 4, SEG_SM = 8, SEG_V = 16, SEG_GU = 32, SEG_ROW = 64, SEG_ALL = 127 };

__global__ void __launch_bounds__(NTHR, 1)
fused_block_kernel(const __grid_constant__ Maps maps, const __nv_bfloat16* __restrict__ xin,
                   const __nv_bfloat16* __restrict__ cin, const __nv_bfloat16* __restrict__ kcache,
                   __nv_bfloat16* __restrict__ out) {
    extern __shared__ unsigned char smem_raw[];
    const int c = blockIdx.x;
    const int kvh = c >> 3, j = c & 7, bb = j & 1, sp = j >> 1;
    const int kvrow0 = (bb * 16 + kvh) * 32768 + 28672 + sp * 1024;
    if (threadIdx.x < EARLY_PF) {
        const char* p = (const char*)kcache + ((size_t)kvrow0 + threadIdx.x * 64) * 256;
        asm volatile("cp.async.bulk.prefetch.L2.global [%0], %1;" ::"l"(p), "r"(16384) : "memory");
    }
    TS(threadIdx.x == 0, 0);
    const uint32_t sb = (smem_u32(smem_raw) + 1023u) & ~1023u;
    const int warp = threadIdx.x >> 5, lane = threadIdx.x & 31;
    const uint32_t s_full = sb + OFF_BAR, s_empty = s_full + N_IT * 8;

    if (warp == NCW) {
        if (lane < 9) asm volatile("prefetch.tensormap [%0];" ::"l"(&maps.m[lane]) : "memory");
        for (int i = lane; i < N_IT + N_EM; i += 32) {
            int cnt = 1;
            if (i >= N_IT) { int e = i - N_IT; cnt = e < EM_K ? NCW : (e < EM_V ? 4 : 8); }
            mbar_init(s_full + i * 8, cnt);
        }
        asm volatile("fence.mbarrier_init.release.cluster;" ::: "memory");
        asm volatile("fence.proxy.async.shared::cta;" ::: "memory");
        __syncwarp();
        asm volatile("bar.arrive 2, 320;" ::: "memory");
        uint32_t w0[2], w1[2], w2[2];
#pragma unroll
        for (int h = 0; h < 2; h++) {
            const int i = lane + 32 * h;
            int off, map, dep = -1, x = 0, y = 0, z = 0, sz = 36;
            if (i < IT_K) {
                off = i * 18432; map = M_WMOD + (i >> 1); x = c * 32; z = (i & 1) * 2;
            } else if (i < IT_V) {
                const int k = i - IT_K;
                off = k_off(k); map = M_K; y = kvrow0 + k * 64; sz = 32;
                if (k == 8 && c < NMOD) dep = EM_WMOD;
                if (k == 10) dep = EM_WQ;
                if (k >= 12) dep = EM_K + k - 12;
            } else if (i < IT_WO) {
                const int k = i - IT_V;
                off = v_off(k); map = M_V; y = kvrow0 + k * 64; sz = 32;
                dep = EM_K + 3 + k + (k < 4);
            } else if (i < IT_GU) {
                const int k = i - IT_WO;
                off = k ? OFF_WO1 : OFF_WO0; map = M_WO; y = kvh * 256 + k * 128 + j * 16; dep = EM_V + 4 + 2 * k;
            } else if (i < IT_WD) {
                const int k = i - IT_GU;
                off = ((k & 1) ? OFF_U : OFF_G) + (k >> 1) * 15360; map = M_WG + (k & 1);
                x = (c * 36) & ~7; y = (k >> 1) * 192; sz = 30; dep = EM_V + 5 + ((off + 15359) >> 14);
            } else {
                const int k = i - IT_WD;
                off = OFF_D0 + k * 18432; map = M_WD + (k >> 1); y = c * 36 + k * 16; sz = k < 2 ? 36 : 9; dep = EM_V + 12 + k;
            }
            w0[h] = off | (map << 18) | ((dep + 1) << 22) | (z << 28);
            w1[h] = y | (sz << 24);
            w2[h] = x;
        }
        const int first = (c < NMOD) ? 0 : 2;
#pragma unroll 1
        for (int i = first; i < N_IT; i++) {
            const bool hi = i >= 32;
            const uint32_t a = __shfl_sync(0xffffffffu, hi ? w0[1] : w0[0], i);
            const uint32_t b = __shfl_sync(0xffffffffu, hi ? w1[1] : w1[0], i);
            const uint32_t x = __shfl_sync(0xffffffffu, hi ? w2[1] : w2[0], i);
            if (lane == 0) {
                const int prev = i - ((i >= IT_WO) ? WIN_TAIL : WIN_MAIN);
                if (prev >= first) mbar_wait(s_full + prev * 8);
                const int dep = (a >> 22) & 63;
                if (dep) mbar_wait(s_empty + (dep - 1) * 8);
                const uint32_t bar = s_full + i * 8;
                mbar_expect_tx(bar, (b >> 24) * 512);
                tma3d(sb + (a & 0x3ffff), &maps.m[(a >> 18) & 15], x, b & 0xffffff, a >> 28, bar);
                TS(i == IT_WO, 1);
                TS(i == first, 17);
            }
            __syncwarp();
        }
        return;
    }

    const bool real = warp < NCW;
    const int vw = real ? warp : 0;
    const int tid = vw * 32 + lane;
    unsigned segs = SEG_ALL;
    int p0 = 0, p1 = 3;
    if (!real) {
        const int k = warp - NCW - 1;
        segs = k == 0 ? (SEG_LN | SEG_GEMV) : k == 1 ? (SEG_K | SEG_SM) : k == 2 ? (SEG_V | SEG_ROW) : (SEG_LN | SEG_GU | SEG_ROW);
        p0 = k == 3 ? 2 : 1; p1 = p0 + 1;
    }
    const int g = lane >> 2, t = lane & 3, mi = lane >> 3, r = lane & 7;
    const int bat = g & 1;
    unsigned* const scr = g_scr;
    const int vecw = tid * 4 - (lane & 7) * 4 + t * 8 + bat * 4;
    const int unit = (vw == 0) ? c : NCTA + c;
    const bool is_red = (vw == 0) || (vw == 1 && c < 16);
    const int rcol = (unit >> 2) * 16 + (unit & 3) * 2 + (lane & 1) + (lane & 2) * 4 + bat * DM;

    unsigned ep = 0, tag = 0;
    uint32_t xw0 = 0, xw1 = 0, aw0 = 0, aw1 = 0, xold = 0;
    if (real) {
        ep = ldg_rlx1(scr + G_EPOCH);
        const int col0 = bat * DM + (vw * 4 + mi) * 16 + 2 * t;
        const uint32_t cw0 = __ldg((const unsigned*)(cin + col0)), cw1 = __ldg((const unsigned*)(cin + col0 + 8));
        xw0 = __ldg((const unsigned*)(xin + col0)); xw1 = __ldg((const unsigned*)(xin + col0 + 8));
        if (is_red) xold = __ldg((const unsigned short*)xin + rcol);
        if (tid < 8) sts64(sb + OFF_FR + tid * 48 + 16, 0u, 0u);
        float cv[4] = {bflo(cw0), bfhi(cw0), bflo(cw1), bfhi(cw1)};
#pragma unroll
        for (int i = 0; i < 4; i++) cv[i] = cv[i] * rcp(1.0f + ex2(-1.4426950408889634f * cv[i]));
        aw0 = pack2(cv[0], cv[1]); aw1 = pack2(cv[2], cv[3]);
        tag = (ep + 1u) & 1u;
        asm volatile("bar.sync 2, 320;" ::: "memory");
    }
    uint32_t sc0 = 0, sc1 = 0, sh0 = 0, sh1 = 0, gcur = 0, gnext = 0;

#pragma unroll 1
    for (int p = p0; p < p1; p++) {
        if (p > 0 && (segs & SEG_LN)) {
            if (p == 2) {
                uint4 v = make_uint4(0, 0, 0, 0);
                if (real) {
                    int it = 0;
                    do { v = ldg_rlx4(scr + G_X1 + vecw); } while ((bad4(v, tag) & 1u) && ++it < SPIN_LIMIT);
                }
                xw0 = hi2(v.x, v.y); xw1 = hi2(v.z, v.w);
                __syncwarp();
            }
            const float piv = __shfl_sync(0xffffffffu, bflo(xw0), lane & 4);
            const float d0 = bflo(xw0) - piv, d1 = bfhi(xw0) - piv, d2 = bflo(xw1) - piv, d3 = bfhi(xw1) - piv;
            float s1 = (d0 + d1) + (d2 + d3), s2 = (d0 * d0 + d1 * d1) + (d2 * d2 + d3 * d3);
            s1 += shx(s1, 1); s2 += shx(s2, 1);
            s1 += shx(s1, 2); s2 += shx(s2, 2);
            s1 += shx(s1, 8); s2 += shx(s2, 8);
            s1 += shx(s1, 16); s2 += shx(s2, 16);
            const uint32_t st = sb + OFF_STAT + (p - 1) * 160 + bat * 80;
            if (real) {
                if ((lane & 27) == 0)
                    sts64(st + vw * 8, __float_as_uint(piv + s1 * (1.0f / 64.0f)), __float_as_uint(s2 - s1 * s1 * (1.0f / 64.0f)));
                bar_consumers();
            }
            TS(tid == 0 && real && p == 2, 13);
            float mw[NCW], ms = 0.f, m2 = 0.f;
#pragma unroll
            for (int w = 0; w < 8; w += 2) {
                uint4 s = lds128(st + w * 8);
                mw[w] = __uint_as_float(s.x); mw[w + 1] = __uint_as_float(s.z);
                ms += mw[w] + mw[w + 1]; m2 += __uint_as_float(s.y) + __uint_as_float(s.w);
            }
            { uint2 s = lds64(st + 64); mw[8] = __uint_as_float(s.x); ms += mw[8]; m2 += __uint_as_float(s.y); }
            const float mean = ms * (1.0f / NCW);
            float acc = 0.f;
#pragma unroll
            for (int w = 0; w < NCW; w++) { float d = mw[w] - mean; acc += d * d; }
            const float var = (m2 + 64.0f * acc) * (1.0f / DM);
            const uint32_t mv = pack2(mean, var);
            const float ve = bflo(pack2(bfhi(mv) + 1e-5f, 0.f));
            const float rinv = rcp(bflo(pack2(fsqrt(ve), 0.f)));
            const uint32_t mm = __byte_perm(mv, mv, 0x1010);
            const uint32_t e0 = bsub2(xw0, mm), e1 = bsub2(xw1, mm);
            const uint32_t y0 = pack2(bflo(e0) * rinv, bfhi(e0) * rinv), y1 = pack2(bflo(e1) * rinv, bfhi(e1) * rinv);
            uint32_t c0 = sc0, c1 = sc1, h0 = sh0, h1 = sh1;
            if (p == 1) {
                uint4 a = make_uint4(0, 0, 0, 0), b = a, d = a, e = a;
                if (real) {
                    int it = 0;
                    unsigned bad;
                    do {
                        a = ldg_rlx4(scr + G_MOD + vecw); b = ldg_rlx4(scr + G_MOD + 1152 + vecw);
                        d = ldg_rlx4(scr + G_MOD + 3 * 1152 + vecw); e = ldg_rlx4(scr + G_MOD + 4 * 1152 + vecw);
                        bad = bad4(a, tag) | bad4(b, tag) | bad4(d, tag) | bad4(e, tag);
                        if (is_red) {
                            gcur = ldg_rlx1(scr + G_MOD + 2 * 1152 + unit * 8 + r);
                            gnext = ldg_rlx1(scr + G_MOD + 5 * 1152 + unit * 8 + r);
                            bad |= (gcur ^ tag) | (gnext ^ tag);
                        }
                    } while ((bad & 1u) && ++it < SPIN_LIMIT);
                }
                __syncwarp();
                const uint32_t one2 = 0x3f803f80u;
                h0 = hi2(a.x, a.y); h1 = hi2(a.z, a.w);
                c0 = badd2(one2, hi2(b.x, b.y)); c1 = badd2(one2, hi2(b.z, b.w));
                sh0 = hi2(d.x, d.y); sh1 = hi2(d.z, d.w);
                sc0 = badd2(one2, hi2(e.x, e.y)); sc1 = badd2(one2, hi2(e.z, e.w));
                gcur >>= 16; gnext >>= 16;
            }
            aw0 = badd2(bmul2(y0, c0), h0); aw1 = badd2(bmul2(y1, c1), h1);
            TS(tid == 0 && real && p == 1, 5);
        }
        uint32_t bf[4][2];
#pragma unroll
        for (int ks = 0; ks < 4; ks++) {
            bf[ks][0] = __shfl_sync(0xffffffffu, aw0, ks * 8 + r);
            bf[ks][1] = __shfl_sync(0xffffffffu, aw1, ks * 8 + r);
        }
        if (p < 2 && (segs & SEG_GEMV) && (p == 1 || c < NMOD)) {
            if (real) {
                if (vw <= 4) mbar_wait(s_full + (2 * p) * 8);
                if (vw >= 4) mbar_wait(s_full + (2 * p + 1) * 8);
            }
            float cc[2][4] = {};
            const uint32_t abase = sb + p * OFF_WQ + (vw * 64 + r + 8 * (mi >> 1)) * 64;
            const uint32_t sw = ((mi & 1) ^ (r >> 1)) << 4;
#pragma unroll
            for (int ks = 0; ks < 4; ks++) {
#pragma unroll
                for (int mt = 0; mt < 2; mt++) {
                    uint32_t a[4];
                    ldsm4t(a, abase + ks * 1024 + (sw ^ (mt * 32)));
                    mma16816(cc[mt], a, bf[ks][0], bf[ks][1]);
                }
            }
            const uint32_t red = sb + OFF_RED + p * 2304;
            if (real) {
                if (t == 0) { sts128f(red + vw * 256 + g * 16, cc[0]); sts128f(red + vw * 256 + 128 + g * 16, cc[1]); }
                __syncwarp();
                if (lane == 0) mbar_arrive(s_empty + p * 8);
                bar_consumers();
            }
            if (tid < 64) {
                const uint32_t ra = red + ((tid & 58) | ((tid & 1) << 2) | ((tid >> 2) & 1)) * 4;
                float s = 0.f;
#pragma unroll
                for (int w = 0; w < NCW; w++) s += ldsf(ra + w * 256);
                const int wd = p ? G_Q + bat * 4096 + c * 32 + (tid >> 3) * 4 + t : G_MOD + c * 64 + tid;
                if (real) stg_rlx1(scr + wd, (pack2(0.f, s)) | tag);
                if (p == 1) {
                    uint4 v = make_uint4(0, 0, 0, 0);
                    if (real) {
                        int it = 0;
                        do { v = ldg_rlx4(scr + G_Q + bb * 4096 + kvh * 256 + tid * 4); } while ((bad4(v, tag) & 1u) && ++it < SPIN_LIMIT);
                        sts64(sb + OFF_QS + (vw * 4 + t) * 80 + g * 8, hi2(v.x, v.y), hi2(v.z, v.w));
                    }
                }
            }
            if (real && p == 1) bar_consumers();
            TS(tid == 0 && real, 4 + 2 * p);
        }
        if (p == 1) {
            if (vw < 8 && (segs & SEG_K)) {
                uint4 qf[4];
#pragma unroll
                for (int i = 0; i < 4; i++) qf[i] = lds128(sb + OFF_QS + r * 80 + i * 16);
                const int mt = vw & 3;
                const uint32_t rowoff = (mt * 16 + r + 8 * (mi & 1)) * 128;
                const uint32_t sw = ((mi >> 1) ^ r) << 4;
                uint32_t mx = 0xff80ff80u;
                const int iend = real ? 16 : 1;
#pragma unroll 1
                for (int i = (vw >> 2); i < iend; i += 2) {
                    if (real) mbar_wait(s_full + (IT_K + i) * 8);
                    const uint32_t base = sb + k_off(i) + rowoff;
                    float c0[4] = {}, c1[4] = {};
                    uint32_t a[4];
                    ldsm4(a, base + sw);               mma16816(c0, a, qf[0].x, qf[0].y);
                    ldsm4(a, base + 8192 + sw);        mma16816(c1, a, qf[2].x, qf[2].y);
                    ldsm4(a, base + (sw ^ 32));        mma16816(c0, a, qf[0].z, qf[0].w);
                    ldsm4(a, base + 8192 + (sw ^ 32)); mma16816(c1, a, qf[2].z, qf[2].w);
                    ldsm4(a, base + (sw ^ 64));        mma16816(c0, a, qf[1].x, qf[1].y);
                    ldsm4(a, base + 8192 + (sw ^ 64)); mma16816(c1, a, qf[3].x, qf[3].y);
                    ldsm4(a, base + (sw ^ 96));        mma16816(c0, a, qf[1].z, qf[1].w);
                    ldsm4(a, base + 8192 + (sw ^ 96)); mma16816(c1, a, qf[3].z, qf[3].w);
                    __syncwarp();
                    if (real && lane == 0) mbar_arrive(s_empty + (EM_K + i) * 8);
                    const float scl = 0.08838834764831845f;
                    uint32_t u0 = pack2(c0[0] + c1[0], c0[1] + c1[1]), u1 = pack2(c0[2] + c1[2], c0[3] + c1[3]);
                    u0 = pack2(bflo(u0) * scl, bfhi(u0) * scl); u1 = pack2(bflo(u1) * scl, bfhi(u1) * scl);
                    mx = bmax2(mx, bmax2(u0, u1));
                    if (real && t == 0) {
                        const uint32_t pa = sb + OFF_S + (i * 64 + 16 * (g >> 1) + 4 * mt + bat) * 4;
                        sts32(pa, u0); sts32(pa + 8, u1);
                    }
                }
#pragma unroll
                for (int o = 4; o <= 16; o <<= 1) mx = bmax2(mx, __shfl_xor_sync(0xffffffffu, mx, o));
                if (real && lane == 0) sts32(sb + OFF_WMX + vw * 4, mx);
            }
            if (real) bar_consumers();
            TS(tid == 0 && real, 7);
            if (segs & SEG_SM) {
                const float L2E = 1.4426950408889634f;
                uint4 sv = make_uint4(0, 0, 0, 0);
                float m0 = 0.f, m1 = 0.f;
                if (vw < 8) {
                    uint4 ma = lds128(sb + OFF_WMX), mb = lds128(sb + OFF_WMX + 16);
                    const uint32_t mx = bmax2(bmax2(bmax2(ma.x, ma.y), bmax2(ma.z, ma.w)), bmax2(bmax2(mb.x, mb.y), bmax2(mb.z, mb.w)));
                    m0 = bflo(mx); m1 = bfhi(mx);
                    sv = lds128(sb + OFF_S + tid * 16);
                    float e0 = (ex2((bflo(sv.x) - m0) * L2E) + ex2((bflo(sv.y) - m0) * L2E)) + (ex2((bflo(sv.z) - m0) * L2E) + ex2((bflo(sv.w) - m0) * L2E));
                    float e1 = (ex2((bfhi(sv.x) - m1) * L2E) + ex2((bfhi(sv.y) - m1) * L2E)) + (ex2((bfhi(sv.z) - m1) * L2E) + ex2((bfhi(sv.w) - m1) * L2E));
#pragma unroll
                    for (int o = 16; o > 0; o >>= 1) { e0 += shx(e0, o); e1 += shx(e1, o); }
                    if (real && lane == 0) sts64(sb + OFF_WMX + 32 + vw * 8, __float_as_uint(e0), __float_as_uint(e1));
                }
                if (real) bar_consumers();
                if (vw < 8) {
                    float l0 = 0.f, l1 = 0.f;
#pragma unroll
                    for (int w = 0; w < 4; w++) {
                        uint4 s = lds128(sb + OFF_WMX + 32 + w * 16);
                        l0 += __uint_as_float(s.x) + __uint_as_float(s.z); l1 += __uint_as_float(s.y) + __uint_as_float(s.w);
                    }
                    if (real && tid < 2) stg_pkt(scr + G_ML + c * 8 + tid * 4, m0, l0, m1, l1, tag);
                    if (real && lane < 4 && lane != sp) {
                        uint4 v;
                        int it = 0;
                        do { v = ldg_pkt(scr + G_ML + (kvh * 8 + lane * 2 + bb) * 8); } while (((v.x ^ tag) & 1u) && ++it < SPIN_LIMIT);
                        m0 = untagf(v.x); l0 = __uint_as_float(v.y); m1 = __uint_as_float(v.z); l1 = __uint_as_float(v.w);
                    }
                    __syncwarp();
                    float g0 = fmaxf(m0, shx(m0, 1)), g1 = fmaxf(m1, shx(m1, 1));
                    g0 = fmaxf(g0, shx(g0, 2)); g1 = fmaxf(g1, shx(g1, 2));
                    l0 *= ex2((m0 - g0) * L2E); l1 *= ex2((m1 - g1) * L2E);
                    l0 += shx(l0, 1); l1 += shx(l1, 1);
                    l0 += shx(l0, 2); l1 += shx(l1, 2);
                    g0 = __shfl_sync(0xffffffffu, g0, 0); g1 = __shfl_sync(0xffffffffu, g1, 0);
                    const float i0 = 1.0f / __shfl_sync(0xffffffffu, l0, 0), i1 = 1.0f / __shfl_sync(0xffffffffu, l1, 0);
                    const uint32_t a0 = pack2(ex2((bflo(sv.x) - g0) * L2E) * i0, ex2((bflo(sv.y) - g0) * L2E) * i0);
                    const uint32_t a1 = pack2(ex2((bflo(sv.z) - g0) * L2E) * i0, ex2((bflo(sv.w) - g0) * L2E) * i0);
                    const uint32_t b0 = pack2(ex2((bfhi(sv.x) - g1) * L2E) * i1, ex2((bfhi(sv.y) - g1) * L2E) * i1);
                    const uint32_t b1 = pack2(ex2((bfhi(sv.z) - g1) * L2E) * i1, ex2((bfhi(sv.w) - g1) * L2E) * i1);
                    if (real) { sts64(sb + OFF_P + tid * 8, a0, a1); sts64(sb + OFF_P + PSTR + tid * 8, b0, b1); }
                }
                if (real) bar_consumers();
                TS(tid == 0 && real, 8);
            }
            if (vw < 8 && (segs & SEG_V)) {
                float c0[4] = {}, c1[4] = {};
                const uint32_t vo = (vw >> 2) * 8192 + (r + 8 * (mi >> 1)) * 128 + ((((2 * vw + (mi & 1)) & 7) ^ r) << 4);
                const uint32_t pa = sb + OFF_P + bat * PSTR + t * 32;
                const int iend = real ? 16 : 1;
#pragma unroll 1
                for (int i = 0; i < iend; i++) {
                    uint4 pb0 = lds128(pa + i * 128), pb1 = lds128(pa + i * 128 + 16);
                    if (real) mbar_wait(s_full + (IT_V + i) * 8);
                    const uint32_t base = sb + v_off(i) + vo;
                    uint32_t a0[4], a1[4], a2[4], a3[4];
                    ldsm4t(a0, base); ldsm4t(a1, base + 2048); ldsm4t(a2, base + 4096); ldsm4t(a3, base + 6144);
                    mma16816(c0, a0, pb0.x, pb0.y);
                    mma16816(c1, a1, pb0.z, pb0.w);
                    mma16816(c0, a2, pb1.x, pb1.y);
                    mma16816(c1, a3, pb1.z, pb1.w);
                    __syncwarp();
                    if (real && lane == 0) mbar_arrive(s_empty + (EM_V + i) * 8);
                }
                if (real && t == 0)
                    stg_pkt(scr + G_OP + c * 256 + vw * 32 + g * 4, c0[0] + c1[0], c0[1] + c1[1], c0[2] + c1[2], c0[3] + c1[3], tag);
                TS(tid == 0 && real, 9);
            }
            if ((vw == 8 || !real) && (segs & SEG_V)) {
                uint4 lo = make_uint4(0, 0, 0, 0), hi = lo;
                if (real) {
                    mbar_wait(s_full + (IT_V + 15) * 8);
                    const unsigned* q = scr + G_OP + (kvh * 8 + g) * 256 + j * 32 + t * 8;
                    int it = 0;
                    do { lo = ldg_pkt(q); hi = ldg_pkt(q + 4); } while ((((lo.x ^ tag) | (hi.x ^ tag)) & 1u) && ++it < SPIN_LIMIT);
                }
                float o[8] = {untagf(lo.x), __uint_as_float(lo.y), __uint_as_float(lo.z), __uint_as_float(lo.w),
                              untagf(hi.x), __uint_as_float(hi.y), __uint_as_float(hi.z), __uint_as_float(hi.w)};
                __syncwarp();
#pragma unroll
                for (int sft = 8; sft <= 16; sft <<= 1) {
#pragma unroll
                    for (int i = 0; i < 8; i++) o[i] += shx(o[i], sft);
                }
                if (real && lane < 8)
                    sts128(sb + OFF_FR + lane * 48, pack2(o[0], o[4]), pack2(o[2], o[6]), pack2(o[1], o[5]), pack2(o[3], o[7]));
                TS(lane == 0 && real, 10);
            }
        }
        if (p == 2 && (segs & SEG_GU)) {
            if (real) {
                const int part = vw / 3;
                mbar_wait(s_full + (IT_GU + 2 * part) * 8);
                mbar_wait(s_full + (IT_GU + 2 * part + 1) * 8);
            }
            float cc[5][4] = {};
            const uint32_t abase = sb + ((mi & 1) ? OFF_U : OFF_G) + (vw * 64 + r + 8 * (mi >> 1)) * 80;
#pragma unroll
            for (int ks = 0; ks < 4; ks++) {
#pragma unroll
                for (int q = 0; q < 5; q++) {
                    uint32_t a[4];
                    ldsm4t(a, abase + ks * 1280 + q * 16);
                    mma16816(cc[q], a, bf[ks][0], bf[ks][1]);
                }
            }
            if (real) {
                if (t == 0) {
#pragma unroll
                    for (int q = 0; q < 5; q++) sts128f(sb + OFF_RED + vw * 640 + q * 128 + g * 16, cc[q]);
                }
                bar_consumers();
            }
            TS(tid == 0 && real, 14);
            if (tid < 160) {
                float s = 0.f;
#pragma unroll
                for (int w = 0; w < NCW; w++) s += ldsf(sb + OFF_RED + w * 640 + tid * 4);
                const uint32_t gu = pack2(s, __shfl_down_sync(0xffffffffu, s, 2));
                const float gt = bflo(gu);
                const uint32_t hh = pack2(((gt > 0.f) ? gt : gt * 0.0f) * bfhi(gu), 0.f);
                const int rr = (tid >> 2) - (c & 1) * 4;
                if (real && (tid & 2) == 0 && rr >= 0 && rr < 36)
                    sts16(sb + OFF_FR + ((tid & 1) * 4 + ((rr & 7) >> 1)) * 48 + (rr >> 3) * 4 + (rr & 1) * 2, hh);
            }
        }
        if (p > 0 && (segs & SEG_ROW)) {
            uint32_t a[2][4][4];
            const uint32_t in = vw * 2048 + (r + 8 * (mi >> 1)) * 128;
            const uint32_t sw = ((mi & 1) ^ r) << 4;
            const uint32_t fb = s_full + (p == 1 ? IT_WO : IT_WD) * 8;
            const uint32_t b0 = sb + (p == 1 ? OFF_WO0 : OFF_D0) + in, b1 = sb + (p == 1 ? OFF_WO1 : OFF_D1) + in;
            if (real) mbar_wait(fb);
#pragma unroll
            for (int mt = 0; mt < 4; mt++) ldsm4t(a[0][mt], b0 + (sw ^ (mt * 32)));
            if (real) mbar_wait(fb + 8);
#pragma unroll
            for (int mt = 0; mt < 4; mt++) ldsm4t(a[1][mt], b1 + (sw ^ (mt * 32)));
            if (real) bar_consumers();
            const uint4 fr = lds128(sb + OFF_FR + r * 48);
            float cc[4][4] = {};
#pragma unroll
            for (int mt = 0; mt < 4; mt++) mma16816(cc[mt], a[0][mt], fr.x, fr.y);
#pragma unroll
            for (int mt = 0; mt < 4; mt++) mma16816(cc[mt], a[1][mt], fr.z, fr.w);
            if (p == 2) {
                const uint2 f2 = lds64(sb + OFF_FR + r * 48 + 16);
                if (real) mbar_wait(fb + 16);
                const int row = vw * 4 + (r & 3);
                const uint32_t b2 = sb + OFF_D2 + row * 128, sw2 = ((mi & 1) ^ (row & 7)) << 4;
#pragma unroll
                for (int mt = 0; mt < 4; mt++) {
                    ldsm4t(a[0][mt], b2 + (sw2 ^ (mt * 32)));
                    mma16816(cc[mt], a[0][mt], f2.x, f2.y);
                }
            }
            unsigned* const part = scr + G_PART + (p - 1) * PART_WORDS;
            if (real && t == 0) {
                unsigned* q = part + ((vw * 16 + (g >> 1)) * NCTA + c) * 8 + bat * 4;
#pragma unroll
                for (int mt = 0; mt < 4; mt++) stg_pkt(q + mt * 4 * NCTA * 8, cc[mt][0], cc[mt][1], cc[mt][2], cc[mt][3], tag);
            }
            TS(tid == 0 && real, 7 + 4 * p);
            if (is_red) {
                const unsigned* q = part + unit * (NCTA * 8) + lane * 4;
                uint4 v[8] = {};
                if (real) {
                    int it = 0;
                    unsigned bad;
                    do {
#pragma unroll
                        for (int i = 0; i < 8; i++) v[i] = ldg_pkt(q + i * 128);
                        bad = 0;
#pragma unroll
                        for (int i = 0; i < 8; i += 2) bad |= (v[i].x ^ tag) | (v[i + 1].x ^ tag);
                    } while ((bad & 1u) && ++it < SPIN_LIMIT);
                }
                float s0 = 0.f, s1 = 0.f, s2 = 0.f, s3 = 0.f;
#pragma unroll
                for (int i = 0; i < 8; i++) {
                    s0 += untagf(v[i].x); s1 += __uint_as_float(v[i].y); s2 += __uint_as_float(v[i].z); s3 += __uint_as_float(v[i].w);
                }
                __syncwarp();
                const bool h8 = lane & 2;
                float k0 = (h8 ? s2 : s0) + shx(h8 ? s0 : s2, 2);
                float k1 = (h8 ? s3 : s1) + shx(h8 ? s1 : s3, 2);
                float k = (bat ? k1 : k0) + shx(bat ? k0 : k1, 4);
                k += shx(k, 8);
                k += shx(k, 16);
                xold = badd2(xold, bmul2(gcur, pack2(k, 0.f))) & 0xffffu;
                gcur = gnext;
                if (real && lane < 8) {
                    if (p == 1) stg_rlx1(scr + G_X1 + unit * 8 + lane, (xold << 16) | tag);
                    else ((unsigned short*)out)[rcol] = (unsigned short)xold;
                }
                TS(tid == 0 && real, 8 + 4 * p);
            }
            if (real && p == 1) bar_consumers();
        }
    }
    if (real && c == 0 && tid == 0) stg_rlx1(scr + G_EPOCH, ep + 1u);
}

typedef CUresult (*EncodeFn)(CUtensorMap*, CUtensorMapDataType, cuuint32_t, void*, const cuuint64_t*, const cuuint64_t*,
                             const cuuint32_t*, const cuuint32_t*, CUtensorMapInterleave, CUtensorMapSwizzle,
                             CUtensorMapL2promotion, CUtensorMapFloatOOBfill);

void make_map(EncodeFn enc, CUtensorMap* m, const void* p, cuuint64_t d0, cuuint64_t d1, cuuint64_t d2,
              cuuint64_t s1, cuuint64_t s2, cuuint32_t b0, cuuint32_t b1, cuuint32_t b2, CUtensorMapSwizzle sw) {
    cuuint64_t dims[3] = {d0, d1, d2};
    cuuint64_t str[2] = {s1, s2};
    cuuint32_t box[3] = {b0, b1, b2};
    cuuint32_t es[3] = {1, 1, 1};
    enc(m, CU_TENSOR_MAP_DATA_TYPE_BFLOAT16, 3, const_cast<void*>(p), dims, str, box, es,
        CU_TENSOR_MAP_INTERLEAVE_NONE, sw, CU_TENSOR_MAP_L2_PROMOTION_L2_256B, CU_TENSOR_MAP_FLOAT_OOB_FILL_NONE);
}

}

extern "C" void kernel_launch(void* const* d_in, const int* in_sizes, int n_in, void* d_out, int out_size) {
    (void)in_sizes; (void)n_in; (void)out_size;
    void* fn = nullptr;
    cudaDriverEntryPointQueryResult qr;
    cudaGetDriverEntryPoint("cuTensorMapEncodeTiled", &fn, cudaEnableDefault, &qr);
    EncodeFn enc = (EncodeFn)fn;
    cudaFuncSetAttribute(fused_block_kernel, cudaFuncAttributeMaxDynamicSharedMemorySize, SMEM_BYTES);

    const void *x = d_in[0], *kc = d_in[1], *vc = d_in[2], *wq = d_in[3], *wo = d_in[4];
    const void *wg = d_in[6], *wu = d_in[7], *wd = d_in[8], *cc = d_in[9], *wmod = d_in[10];
    const CUtensorMapSwizzle S128 = CU_TENSOR_MAP_SWIZZLE_128B, S64 = CU_TENSOR_MAP_SWIZZLE_64B, S0 = CU_TENSOR_MAP_SWIZZLE_NONE;
    Maps m;
    make_map(enc, &m.m[M_K], kc, 64, 32ull * 32768, 2, 256, 128, 64, 64, 2, S128);
    make_map(enc, &m.m[M_V], vc, 64, 32ull * 32768, 2, 256, 128, 64, 64, 2, S128);
    make_map(enc, &m.m[M_WMOD], wmod, 3456, 144, 4, 3456 * 2, 3456 * 2 * 144, 32, 144, 2, S64);
    make_map(enc, &m.m[M_WQ], wq, 4096, 144, 4, 4096 * 2, 4096 * 2 * 144, 32, 144, 2, S64);
    make_map(enc, &m.m[M_WG], wg, 4608, 576, 1, 4608 * 2, 4608 * 2 * 576, 40, 192, 1, S0);
    make_map(enc, &m.m[M_WU], wu, 4608, 576, 1, 4608 * 2, 4608 * 2 * 576, 40, 192, 1, S0);
    make_map(enc, &m.m[M_WO], wo, 64, 4096, 9, 1152, 128, 64, 16, 9, S128);
    make_map(enc, &m.m[M_WD], wd, 64, 4608, 9, 1152, 128, 64, 16, 9, S128);
    make_map(enc, &m.m[M_WD4], wd, 64, 4608, 9, 1152, 128, 64, 4, 9, S128);
    fused_block_kernel<<<NCTA, NTHR, SMEM_BYTES>>>(m, (const __nv_bfloat16*)x, (const __nv_bfloat16*)cc,
                                                   (const __nv_bfloat16*)kc, (__nv_bfloat16*)d_out);
}
```

```cpp
#include <cuda_runtime.h>
#include <cuda.h>
#include <cuda_bf16.h>
#include <stdint.h>

namespace {

constexpr int DM = 576;
constexpr int NCTA = 128;
constexpr int NCW = 9;
constexpr int NTHR = (NCW + 3) * 32;
constexpr int NMOD = 108;

#define WIN_MAIN 4
#define WIN_TAIL 4
#define PACE_GBS 3150
#define PACE_LEAD 0
#define PACE_TAIL 2700
#define PACE_D 3300
#define TAIL_GAP 250
#define DELAY_B 300
#define DELAY_C 0
#define BACK_C 0
#define BACK_B 0
#define DELAY_D 300
#define PH_V 7
#define SIDE_V 11
#define NPROBE 8
#define PH_K 8

constexpr int IT_WMOD = 0, IT_WQ = 2, IT_K = 4, IT_V = 20, IT_WO = 36, IT_GU = 38, IT_WD = 44, N_IT = 47;
__device__ __forceinline__ constexpr int it_v(int k) { return IT_V + k; }
constexpr int EM_WMOD = 0, EM_WQ = 1, EM_K = 2, EM_V = 18, EM_PH = 34, EM_X1 = 35, N_EM = 36;

constexpr int RING = 13 * 16384;
constexpr int OFF_WMOD = 0, OFF_WQ = 36864, OFF_K0 = 73728;
constexpr int OFF_WO0 = 180224, OFF_WO1 = 0, OFF_G = 18432, OFF_U = 64512;
constexpr int OFF_D0 = 110592, OFF_D1 = 129024, OFF_D2 = 147456;
constexpr int PSTR = 2064;
constexpr int OFF_P = RING;
constexpr int OFF_S = OFF_P + 4160;
constexpr int OFF_RED = OFF_S + 4096;
constexpr int OFF_QS = OFF_RED + 5760;
constexpr int OFF_FR = OFF_QS + 640;
constexpr int OFF_STAT = OFF_FR + 384;
constexpr int OFF_WMX = OFF_STAT + 320;
constexpr int OFF_BAR = OFF_WMX + 128;
constexpr int SMEM_USED = OFF_BAR + (N_IT + N_EM) * 8;
constexpr int SMEM_BYTES = SMEM_USED + 1024;
static_assert(SMEM_BYTES <= 232448, "smem");

struct Maps { CUtensorMap m[9]; };
enum { M_K, M_V, M_WMOD, M_WQ, M_WG, M_WU, M_WO, M_WD, M_WD4 };

constexpr int HALF = 1024;
constexpr int G_PART = 0;
constexpr int G_OP = G_PART + 144 * 2048;
constexpr int G_X1 = G_OP + 16 * 4096;
constexpr int G_PROBE = G_X1 + 4096;
constexpr int G_SIDE = G_PROBE + 2048;
constexpr int G_EPOCH = G_SIDE + 1024;
constexpr int G_MOD = G_EPOCH + 32;
constexpr int G_Q = G_MOD + 6912;
constexpr int G_ML = G_Q + 8192;
constexpr int G_WORDS = G_ML + NCTA * 8;
static_assert(G_WORDS * 4 <= (2 << 20), "scratch must fit one 2 MB page");
__device__ __align__(128) unsigned g_raw[(2 << 20) / 4 + G_WORDS];
__device__ __forceinline__ int near_half(int w, unsigned side) { return ((__popc(w & 0x2C800) ^ side) & 1) << 10; }

constexpr int SPIN_LIMIT = 1 << 20;

__device__ __forceinline__ uint32_t smem_u32(const void* p) { return (uint32_t)__cvta_generic_to_shared(p); }
__device__ __forceinline__ void mbar_init(uint32_t bar, int cnt) {
    asm volatile("mbarrier.init.shared::cta.b64 [%0], %1;" ::"r"(bar), "r"(cnt) : "memory");
}
__device__ __forceinline__ void mbar_expect_tx(uint32_t bar, uint32_t bytes) {
    asm volatile("mbarrier.arrive.expect_tx.shared::cta.b64 _, [%0], %1;" ::"r"(bar), "r"(bytes) : "memory");
}
__device__ __forceinline__ void mbar_arrive(uint32_t bar) {
    asm volatile("mbarrier.arrive.shared::cta.b64 _, [%0];" ::"r"(bar) : "memory");
}
__device__ __forceinline__ void mbar_wait(uint32_t bar) {
    asm volatile("{\n.reg .pred p;\nW_%=:\nmbarrier.try_wait.parity.shared::cta.b64 p, [%0], 0;\n@!p bra W_%=;\n}"
                 ::"r"(bar) : "memory");
}
__device__ __forceinline__ bool mbar_test(uint32_t bar) {
    uint32_t ok;
    asm volatile("{\n.reg .pred p;\nmbarrier.test_wait.parity.shared::cta.b64 p, [%1], 0;\nselp.u32 %0, 1, 0, p;\n}"
                 : "=r"(ok) : "r"(bar) : "memory");
    return ok;
}
__device__ __forceinline__ uint32_t gtime32() { uint32_t t; asm volatile("mov.u32 %0, %%globaltimer_lo;" : "=r"(t)); return t; }
__device__ __forceinline__ void tma3d(uint32_t dst, const CUtensorMap* m, int x, int y, int z, uint32_t bar) {
    asm volatile("cp.async.bulk.tensor.3d.shared::cluster.global.mbarrier::complete_tx::bytes [%0], [%1, {%3, %4, %5}], [%2];"
                 ::"r"(dst), "l"(m), "r"(bar), "r"(x), "r"(y), "r"(z) : "memory");
}
__device__ __forceinline__ void bar_consumers() { asm volatile("bar.sync 1, 288;" ::: "memory"); }

__device__ __forceinline__ void ldsm4(uint32_t (&a)[4], uint32_t addr) {
    asm volatile("ldmatrix.sync.aligned.m8n8.x4.shared.b16 {%0,%1,%2,%3}, [%4];"
                 : "=r"(a[0]), "=r"(a[1]), "=r"(a[2]), "=r"(a[3]) : "r"(addr) : "memory");
}
__device__ __forceinline__ void ldsm4t(uint32_t (&a)[4], uint32_t addr) {
    asm volatile("ldmatrix.sync.aligned.m8n8.x4.trans.shared.b16 {%0,%1,%2,%3}, [%4];"
                 : "=r"(a[0]), "=r"(a[1]), "=r"(a[2]), "=r"(a[3]) : "r"(addr) : "memory");
}
__device__ __forceinline__ void mma16816(float (&c)[4], const uint32_t (&a)[4], uint32_t b0, uint32_t b1) {
    asm volatile("mma.sync.aligned.m16n8k16.row.col.f32.bf16.bf16.f32 {%0,%1,%2,%3}, {%4,%5,%6,%7}, {%8,%9}, {%0,%1,%2,%3};"
                 : "+f"(c[0]), "+f"(c[1]), "+f"(c[2]), "+f"(c[3])
                 : "r"(a[0]), "r"(a[1]), "r"(a[2]), "r"(a[3]), "r"(b0), "r"(b1));
}
__device__ __forceinline__ float ldsf(uint32_t a) { float v; asm volatile("ld.shared.f32 %0, [%1];" : "=f"(v) : "r"(a) : "memory"); return v; }
__device__ __forceinline__ uint2 lds64(uint32_t a) {
    uint2 v; asm volatile("ld.shared.v2.u32 {%0,%1}, [%2];" : "=r"(v.x), "=r"(v.y) : "r"(a) : "memory"); return v;
}
__device__ __forceinline__ uint4 lds128(uint32_t a) {
    uint4 v; asm volatile("ld.shared.v4.u32 {%0,%1,%2,%3}, [%4];" : "=r"(v.x), "=r"(v.y), "=r"(v.z), "=r"(v.w) : "r"(a) : "memory"); return v;
}
__device__ __forceinline__ void sts16(uint32_t a, uint32_t v) { asm volatile("st.shared.u16 [%0], %1;" ::"r"(a), "h"((unsigned short)v) : "memory"); }
__device__ __forceinline__ void sts32(uint32_t a, uint32_t v) { asm volatile("st.shared.u32 [%0], %1;" ::"r"(a), "r"(v) : "memory"); }
__device__ __forceinline__ void sts64(uint32_t a, uint32_t x, uint32_t y) { asm volatile("st.shared.v2.u32 [%0], {%1,%2};" ::"r"(a), "r"(x), "r"(y) : "memory"); }
__device__ __forceinline__ void sts128(uint32_t a, uint32_t x, uint32_t y, uint32_t z, uint32_t w) {
    asm volatile("st.shared.v4.u32 [%0], {%1,%2,%3,%4};" ::"r"(a), "r"(x), "r"(y), "r"(z), "r"(w) : "memory");
}
__device__ __forceinline__ void sts128f(uint32_t a, const float (&c)[4]) {
    asm volatile("st.shared.v4.f32 [%0], {%1,%2,%3,%4};" ::"r"(a), "f"(c[0]), "f"(c[1]), "f"(c[2]), "f"(c[3]) : "memory");
}
__device__ __forceinline__ unsigned ldg_rlx1(const unsigned* p) {
    unsigned v; asm volatile("ld.relaxed.gpu.global.u32 %0, [%1];" : "=r"(v) : "l"(p) : "memory"); return v;
}
__device__ __forceinline__ uint4 ldg_rlx4(const unsigned* p) {
    uint4 v; asm volatile("ld.relaxed.gpu.global.v4.u32 {%0,%1,%2,%3}, [%4];" : "=r"(v.x), "=r"(v.y), "=r"(v.z), "=r"(v.w) : "l"(p) : "memory"); return v;
}
__device__ __forceinline__ uint4 ldg_pkt(const unsigned* p) {
    uint4 v;
    asm volatile("{\n.reg .b128 t;\n.reg .b64 lo, hi;\nld.relaxed.gpu.global.b128 t, [%4];\nmov.b128 {lo, hi}, t;\n"
                 "mov.b64 {%0,%1}, lo;\nmov.b64 {%2,%3}, hi;\n}"
                 : "=r"(v.x), "=r"(v.y), "=r"(v.z), "=r"(v.w) : "l"(p) : "memory");
    return v;
}
__device__ __forceinline__ void ldg_pkt_if(uint4& v, const unsigned* a, unsigned p) {
    asm volatile("{\n.reg .pred q;\n.reg .b128 t;\n.reg .b64 lo, hi;\nsetp.ne.u32 q, %5, 0;\n"
                 "mov.b64 lo, {%0,%1};\nmov.b64 hi, {%2,%3};\nmov.b128 t, {lo, hi};\n"
                 "@q ld.relaxed.gpu.global.b128 t, [%4];\nmov.b128 {lo, hi}, t;\n"
                 "mov.b64 {%0,%1}, lo;\nmov.b64 {%2,%3}, hi;\n}"
                 : "+r"(v.x), "+r"(v.y), "+r"(v.z), "+r"(v.w) : "l"(a), "r"(p) : "memory");
}
__device__ __forceinline__ bool any_lane(unsigned x) { return __any_sync(0xffffffffu, x != 0); }
__device__ __forceinline__ void stg_pkt(unsigned* p, float a, float b, float c, float d, unsigned tag) {
    unsigned x = (__float_as_uint(a) & ~7u) | tag;
    asm volatile("{\n.reg .b128 t;\n.reg .b64 lo, hi;\nmov.b64 lo, {%1,%2};\nmov.b64 hi, {%3,%4};\nmov.b128 t, {lo, hi};\n"
                 "st.relaxed.gpu.global.b128 [%0], t;\n}"
                 ::"l"(p), "r"(x), "r"(__float_as_uint(b)), "r"(__float_as_uint(c)), "r"(__float_as_uint(d)) : "memory");
}
__device__ __forceinline__ void stg_rlx1(unsigned* p, unsigned x) { asm volatile("st.relaxed.gpu.global.u32 [%0], %1;" ::"l"(p), "r"(x) : "memory"); }
__device__ __forceinline__ unsigned bad4(const uint4& v, unsigned tag) {
    return ((v.x ^ tag) | (v.y ^ tag)) | ((v.z ^ tag) | (v.w ^ tag));
}
__device__ __forceinline__ float untagf(unsigned w) { return __uint_as_float(w & ~7u); }
__device__ __forceinline__ uint32_t pack2(float lo, float hi) {
    uint32_t r; asm("cvt.rn.bf16x2.f32 %0, %1, %2;" : "=r"(r) : "f"(hi), "f"(lo)); return r;
}
__device__ __forceinline__ float bflo(uint32_t w) { return __uint_as_float(w << 16); }
__device__ __forceinline__ float bfhi(uint32_t w) { return __uint_as_float(w & 0xffff0000u); }
__device__ __forceinline__ uint32_t hi2(uint32_t a, uint32_t b) { return __byte_perm(a, b, 0x7632); }
__device__ __forceinline__ uint32_t badd2(uint32_t a, uint32_t b) { uint32_t r; asm("add.rn.bf16x2 %0, %1, %2;" : "=r"(r) : "r"(a), "r"(b)); return r; }
__device__ __forceinline__ uint32_t bsub2(uint32_t a, uint32_t b) { uint32_t r; asm("sub.rn.bf16x2 %0, %1, %2;" : "=r"(r) : "r"(a), "r"(b)); return r; }
__device__ __forceinline__ uint32_t bmul2(uint32_t a, uint32_t b) { uint32_t r; asm("mul.rn.bf16x2 %0, %1, %2;" : "=r"(r) : "r"(a), "r"(b)); return r; }
__device__ __forceinline__ uint32_t bmax2(uint32_t a, uint32_t b) { uint32_t r; asm("max.bf16x2 %0, %1, %2;" : "=r"(r) : "r"(a), "r"(b)); return r; }
__device__ __forceinline__ float ex2(float x) { float r; asm("ex2.approx.ftz.f32 %0, %1;" : "=f"(r) : "f"(x)); return r; }
__device__ __forceinline__ float rcp(float x) { float r; asm("rcp.approx.ftz.f32 %0, %1;" : "=f"(r) : "f"(x)); return r; }
__device__ __forceinline__ float fsqrt(float x) { float r; asm("sqrt.approx.ftz.f32 %0, %1;" : "=f"(r) : "f"(x)); return r; }
__device__ __forceinline__ float shx(float v, int m) { return __shfl_xor_sync(0xffffffffu, v, m); }
#define PB() do { } while (0)
#define PE(cond, slot, it) do { } while (0)
#define TS(cond, slot) do { } while (0)

__device__ __forceinline__ uint32_t k_off(int i) { return i < 8 ? OFF_K0 + i * 16384 : (i - 8) * 16384; }
__device__ __forceinline__ uint32_t v_off(int i) { return i < 5 ? (8 + i) * 16384 : (i - 5) * 16384; }

__device__ __forceinline__ void stg_ph(unsigned* p) { stg_pkt(p, 0.f, 0.f, 0.f, 0.f, 2u); }

__device__ __forceinline__ void ln_stage1(uint32_t xw0, uint32_t xw1, uint32_t st, int vw, int lane) {
    const float piv = __shfl_sync(0xffffffffu, bflo(xw0), lane & 4);
    const float d0 = bflo(xw0) - piv, d1 = bfhi(xw0) - piv, d2 = bflo(xw1) - piv, d3 = bfhi(xw1) - piv;
    float s1 = (d0 + d1) + (d2 + d3), s2 = (d0 * d0 + d1 * d1) + (d2 * d2 + d3 * d3);
    s1 += shx(s1, 1); s2 += shx(s2, 1);
    s1 += shx(s1, 2); s2 += shx(s2, 2);
    s1 += shx(s1, 8); s2 += shx(s2, 8);
    s1 += shx(s1, 16); s2 += shx(s2, 16);
    if ((lane & 27) == 0)
        sts64(st + vw * 8, __float_as_uint(piv + s1 * (1.0f / 64.0f)), __float_as_uint(s2 - s1 * s1 * (1.0f / 64.0f)));
}
struct LnStat { uint4 a, b, c, d; uint2 e; };
__device__ __forceinline__ LnStat ln_load(uint32_t st) {
    LnStat s; s.a = lds128(st); s.b = lds128(st + 16); s.c = lds128(st + 32); s.d = lds128(st + 48); s.e = lds64(st + 64);
    return s;
}
__device__ __forceinline__ void ln_stage2(const LnStat& s, uint32_t xw0, uint32_t xw1, uint32_t& y0, uint32_t& y1) {
    const float m[9] = {__uint_as_float(s.a.x), __uint_as_float(s.a.z), __uint_as_float(s.b.x), __uint_as_float(s.b.z),
                        __uint_as_float(s.c.x), __uint_as_float(s.c.z), __uint_as_float(s.d.x), __uint_as_float(s.d.z), __uint_as_float(s.e.x)};
    const float mean = (((m[0] + m[1]) + (m[2] + m[3])) + ((m[4] + m[5]) + (m[6] + m[7])) + m[8]) * (1.0f / NCW);
    const float m2 = ((__uint_as_float(s.a.y) + __uint_as_float(s.a.w)) + (__uint_as_float(s.b.y) + __uint_as_float(s.b.w))) +
                     ((__uint_as_float(s.c.y) + __uint_as_float(s.c.w)) + (__uint_as_float(s.d.y) + __uint_as_float(s.d.w))) + __uint_as_float(s.e.y);
    float d[9];
#pragma unroll
    for (int w = 0; w < 9; w++) d[w] = m[w] - mean;
    const float acc = (d[0] * d[0] + d[1] * d[1] + d[2] * d[2]) + (d[3] * d[3] + d[4] * d[4] + d[5] * d[5]) + (d[6] * d[6] + d[7] * d[7] + d[8] * d[8]);
    const float var = (m2 + 64.0f * acc) * (1.0f / DM);
    const uint32_t mv = pack2(mean, var);
    const float ve = bflo(pack2(bfhi(mv) + 1e-5f, 0.f));
    const float rinv = rcp(bflo(pack2(fsqrt(ve), 0.f)));
    const uint32_t mm = __byte_perm(mv, mv, 0x1010);
    const uint32_t e0 = bsub2(xw0, mm), e1 = bsub2(xw1, mm);
    y0 = pack2(bflo(e0) * rinv, bfhi(e0) * rinv); y1 = pack2(bflo(e1) * rinv, bfhi(e1) * rinv);
}
__device__ __forceinline__ void make_bfrags(uint32_t (&bf)[4][2], uint32_t aw0, uint32_t aw1, int r) {
#pragma unroll
    for (int ks = 0; ks < 4; ks++) {
        bf[ks][0] = __shfl_sync(0xffffffffu, aw0, ks * 8 + r);
        bf[ks][1] = __shfl_sync(0xffffffffu, aw1, ks * 8 + r);
    }
}
__device__ __forceinline__ uint32_t gemv32(uint32_t s_w, uint32_t red, uint32_t fullbar, uint32_t emptybar,
                                           uint32_t aw0, uint32_t aw1, int tid) {
    const int vw = tid >> 5, lane = tid & 31, g = lane >> 2, t = lane & 3, mi = lane >> 3, r = lane & 7;
    uint32_t bf[4][2];
    make_bfrags(bf, aw0, aw1, r);
    if (vw <= 4) mbar_wait(fullbar);
    if (vw >= 4) mbar_wait(fullbar + 8);
    float cc[2][4] = {};
    const uint32_t abase = s_w + (vw * 64 + r + 8 * (mi >> 1)) * 64;
    const uint32_t sw = ((mi & 1) ^ (r >> 1)) << 4;
#pragma unroll
    for (int ks = 0; ks < 4; ks++) {
#pragma unroll
        for (int mt = 0; mt < 2; mt++) {
            uint32_t a[4];
            ldsm4t(a, abase + ks * 1024 + (sw ^ (mt * 32)));
            mma16816(cc[mt], a, bf[ks][0], bf[ks][1]);
        }
    }
    if (t == 0) { sts128f(red + vw * 256 + g * 16, cc[0]); sts128f(red + vw * 256 + 128 + g * 16, cc[1]); }
    __syncwarp();
    if (lane == 0) mbar_arrive(emptybar);
    bar_consumers();
    float s = 0.f;
    if (tid < 64) {
        const uint32_t ra = red + ((tid & 58) | ((tid & 1) << 2) | ((tid >> 2) & 1)) * 4;
#pragma unroll
        for (int w = 0; w < NCW; w++) s += ldsf(ra + w * 256);
    }
    return pack2(0.f, s);
}
__device__ __forceinline__ void publish_partials(unsigned* q, unsigned hm, const float (&cc)[4][4], unsigned tag) {
#pragma unroll
    for (int mt = 0; mt < 4; mt++)
        stg_pkt(q + mt * 4 * 2048 + ((hm >> (4 * mt)) & 1) * HALF, cc[mt][0], cc[mt][1], cc[mt][2], cc[mt][3], tag);
}
__device__ __forceinline__ void spin_cycles(unsigned n) {
    const unsigned c0 = clock();
    while ((unsigned)clock() - c0 < n) { }
}
__device__ __forceinline__ float reduce_unit(const unsigned* q, int lane, unsigned tag, bool prof = false) {
    uint4 v[8];
#pragma unroll
    for (int i = 0; i < 8; i++) v[i] = ldg_pkt(q + i * 128);
    int it = 0;
    while (true) {
        unsigned bad = 0;
#pragma unroll
        for (int i = 0; i < 8; i += 2) bad |= (v[i].x ^ tag) | (v[i + 1].x ^ tag);
        if (!any_lane(bad & 7u) || ++it >= SPIN_LIMIT) break;
        spin_cycles(BACK_B);
#pragma unroll
        for (int i = 0; i < 8; i++) ldg_pkt_if(v[i], q + i * 128, (v[i].x ^ tag) & 7u);
    }
    float s0 = 0.f, s1 = 0.f, s2 = 0.f, s3 = 0.f, u0 = 0.f, u1 = 0.f, u2 = 0.f, u3 = 0.f;
#pragma unroll
    for (int i = 0; i < 8; i += 2) {
        s0 += untagf(v[i].x); s1 += __uint_as_float(v[i].y); s2 += __uint_as_float(v[i].z); s3 += __uint_as_float(v[i].w);
        u0 += untagf(v[i + 1].x); u1 += __uint_as_float(v[i + 1].y); u2 += __uint_as_float(v[i + 1].z); u3 += __uint_as_float(v[i + 1].w);
    }
    s0 += u0; s1 += u1; s2 += u2; s3 += u3;
    __syncwarp();
    const bool h8 = lane & 2, bat = lane & 4;
    const float k0 = (h8 ? s2 : s0) + shx(h8 ? s0 : s2, 2);
    const float k1 = (h8 ? s3 : s1) + shx(h8 ? s1 : s3, 2);
    float k = (bat ? k1 : k0) + shx(bat ? k0 : k1, 4);
    k += shx(k, 8);
    k += shx(k, 16);
    return k;
}

__global__ void __launch_bounds__(NTHR, 1)
fused_block_kernel(const __grid_constant__ Maps maps, const __nv_bfloat16* __restrict__ xin,
                   const __nv_bfloat16* __restrict__ cin, __nv_bfloat16* __restrict__ out) {
    extern __shared__ unsigned char smem_raw[];
    const int c = blockIdx.x;
    const int kvh = c >> 3, j = c & 7, bb = j & 1, sp = j >> 1;
    const int kvrow0 = (bb * 16 + kvh) * 32768 + 28672 + sp * 1024;
    TS(threadIdx.x == 0, 0);
    const uint32_t sb = (smem_u32(smem_raw) + 1023u) & ~1023u;
    const int warp = threadIdx.x >> 5, lane = threadIdx.x & 31;
    const uint32_t s_full = sb + OFF_BAR, s_empty = s_full + N_IT * 8;

    if (warp == NCW) {
        const uint32_t t0 = gtime32();
        const int first = (c < NMOD) ? 0 : 2;
        if (lane == 0) {
#pragma unroll
            for (int i = 0; i < 2; i++) mbar_init(s_full + (first + i) * 8, 1);
            asm volatile("fence.proxy.async.shared::cta;" ::: "memory");
#pragma unroll
            for (int i = 0; i < 2; i++) {
                const uint32_t bar = s_full + (first + i) * 8;
                mbar_expect_tx(bar, 18432);
                tma3d(sb + (first + i) * 18432, &maps.m[M_WMOD + (first >> 1)], c * 32, 0, i * 2, bar);
            }
            TS(true, 17);
        }
        __syncwarp();
        uint32_t w0[2], w1[2], w2[2];
#pragma unroll
        for (int h = 0; h < 2; h++) {
            const int i = lane + 32 * h;
            int off, map, dep = -1, x = 0, y = 0, z = 0, sz = 36, cum;
            if (i < IT_K) {
                off = i * 18432; map = M_WMOD + (i >> 1); x = c * 32; z = (i & 1) * 2; cum = 31104 + (i - 2) * 18432;
            } else if (i < IT_V) {
                const int k = i - IT_K;
                off = k_off(k); map = M_K; y = kvrow0 + k * 64; sz = 32; cum = 67968 + k * 16384;
                if (k == 8 && c < NMOD) dep = EM_WMOD;
                if (k == 10) dep = EM_WQ;
                if (k >= 12) dep = EM_K + k - 12;
            } else if (i < IT_WO) {
                const int k = i - IT_V;
                off = v_off(k); map = M_V; y = kvrow0 + k * 64; sz = 32; cum = 330112 + k * 16384;
                dep = EM_K + 3 + k + (k < 4);
            } else if (i < IT_GU) {
                const int k = i - IT_WO;
                off = k ? OFF_WO1 : OFF_WO0; map = M_WO; y = kvh * 256 + k * 128 + j * 16; dep = EM_V + 4 + 2 * k;
                cum = 592256 + k * 18432;
            } else if (i < IT_WD) {
                const int k = i - IT_GU;
                off = ((k & 1) ? OFF_U : OFF_G) + (k >> 1) * 15360; map = M_WG + (k & 1);
                x = (c * 36) & ~7; y = (k >> 1) * 192; sz = 30; dep = EM_V + 5 + ((off + 15359) >> 14);
                cum = 629120 + k * 13824;
            } else {
                const int k = i - IT_WD;
                off = OFF_D0 + k * 18432; map = M_WD + (k >> 1); y = c * 36 + k * 16; sz = k < 2 ? 36 : 9; dep = EM_V + 12 + k;
                cum = 712064 + k * 18432;
            }
            const int stag = ((c * 37) & 127) * 128 - PACE_LEAD;
            int due = (int)((float)(min(cum, 629120) + stag) * (128.0f / PACE_GBS));
            if (i >= IT_GU) due += TAIL_GAP + (int)((float)(min(cum, 712064) - 629120) * (128.0f / PACE_TAIL));
            if (i >= IT_WD) due += (int)((float)(cum - 712064) * (128.0f / PACE_D));
            w0[h] = off | (map << 18) | ((dep + 1) << 22) | (z << 28);
            w1[h] = y | (sz << 24);
            w2[h] = x | (due << 13);
        }
        asm volatile("bar.sync 2, 384;" ::: "memory");
#pragma unroll 1
        for (int i = first + 2; i < N_IT; i++) {
            const bool hi = i >= 32;
            const uint32_t a = __shfl_sync(0xffffffffu, hi ? w0[1] : w0[0], i);
            const uint32_t b = __shfl_sync(0xffffffffu, hi ? w1[1] : w1[0], i);
            const uint32_t x = __shfl_sync(0xffffffffu, hi ? w2[1] : w2[0], i);
            if (lane == 0) {
                const int prev = i - ((i >= IT_WO) ? WIN_TAIL : WIN_MAIN);
                if (prev >= first) mbar_wait(s_full + prev * 8);
                const int dep = (a >> 22) & 63;
                if (dep) mbar_wait(s_empty + (dep - 1) * 8);
                while (gtime32() - t0 < (x >> 13)) { }
                const uint32_t bar = s_full + i * 8;
                mbar_expect_tx(bar, (b >> 24) * 512);
                tma3d(sb + (a & 0x3ffff), &maps.m[(a >> 18) & 15], x & 0x1fff, b & 0xffffff, a >> 28, bar);
                TS(i == IT_WO, 1);
            }
            __syncwarp();
        }
        return;
    }

    const int g = lane >> 2, t = lane & 3, mi = lane >> 3, r = lane & 7;
    const int bat = g & 1;
    unsigned* const scr = (unsigned*)(((uintptr_t)g_raw + 0x1fffff) & ~(uintptr_t)0x1fffff);

    if (warp > NCW) {
        const bool first = warp == NCW + 1, active = first || c < 16;
        const int unit = first ? c : NCTA + c;
        const int rcol = (unit >> 2) * 16 + (unit & 3) * 2 + (lane & 1) + (lane & 2) * 4 + bat * DM;
        const unsigned ep = ldg_rlx1(scr + G_EPOCH);
        uint32_t xold = 0, ga = 0, gb = 0;
        if (active) xold = __ldg((const unsigned short*)xin + rcol);
        asm volatile("bar.sync 2, 384;" ::: "memory");
        const unsigned tag = (ep + 1u) & 1u;
        unsigned side = 0;
        const int x1w = G_X1 + (unit >> 7) * 2048 + (unit & 127) * 8 + r + (lane & 8) * (HALF / 8);
        if (first) {
            unsigned* pr = scr + G_PROBE + c * 8;
            if (lane < 16) stg_rlx1(pr + r + (lane & 8) * (HALF / 8), 0u);
            __syncwarp();
            if (lane == 0) {
                unsigned best0 = ~0u, best1 = ~0u, v = 0, cp = 0;
#pragma unroll 1
                for (int i = 0; i <= 2 * NPROBE; i++) {
                    asm volatile("atom.relaxed.gpu.global.add.u32 %0, [%1], 1;" : "=r"(v) : "l"(pr + (i & 1) * HALF + (v >> 31)) : "memory");
                    const unsigned cn = clock(), d = cn - cp;
                    cp = cn;
                    if (i & 1) best0 = min(best0, d); else if (i) best1 = min(best1, d);
                }
                side = (best1 < best0) ^ (__popc(G_PROBE & 0x2C800) & 1);
                sts32(sb + OFF_WMX + 112, side);
            }
            side = __shfl_sync(0xffffffffu, side, 0);
            mbar_wait(s_full + it_v(PH_V) * 8);
#pragma unroll 1
            for (int u = c; u < 144; u += NCTA) {
                unsigned* q = scr + G_PART + u * 2048 + near_half(G_PART + u * 2048, side) + lane * 4;
#pragma unroll
                for (int i = 0; i < 8; i++) stg_ph(q + i * 128);
                if (lane < 16) stg_rlx1(scr + x1w + (u >> 7) * 2048, 2u);
            }
            unsigned* o = scr + G_OP + kvh * 4096 + (j >> 2) * 2048 + (j & 3) * 256 + lane * 4;
            stg_ph(o); stg_ph(o + 128); stg_ph(o + HALF); stg_ph(o + HALF + 128);
            __threadfence();
            __syncwarp();
            if (lane < 8) stg_rlx1(scr + G_SIDE + c * 8 + lane, (side << 4) | tag);
            if (lane == 0) mbar_arrive(s_empty + EM_PH * 8);
        } else {
            mbar_wait(s_empty + EM_PH * 8);
            side = __float_as_uint(ldsf(sb + OFF_WMX + 112));
        }
        if (active) {
            int it = 0;
            do {
                ga = ldg_rlx1(scr + G_MOD + 2 * 1152 + unit * 8 + r);
                gb = ldg_rlx1(scr + G_MOD + 5 * 1152 + unit * 8 + r);
            } while (any_lane(((ga ^ tag) | (gb ^ tag)) & 7u) && ++it < SPIN_LIMIT);
            ga >>= 16; gb >>= 16;
        }
        __syncwarp();
        if (first) {
            const int ow = G_OP + kvh * 4096 + (g >> 2) * 2048;
            const unsigned* q = scr + ow + near_half(ow, side) + (g & 3) * 256 + j * 32 + t * 8;
            mbar_wait(s_full + it_v(15) * 8);
            uint4 lo, hi;
            int it = 0;
            do { lo = ldg_pkt(q); hi = ldg_pkt(q + 4); } while (any_lane(((lo.x ^ tag) | (hi.x ^ tag)) & 7u) && ++it < SPIN_LIMIT);
            float o[8] = {untagf(lo.x), __uint_as_float(lo.y), __uint_as_float(lo.z), __uint_as_float(lo.w),
                          untagf(hi.x), __uint_as_float(hi.y), __uint_as_float(hi.z), __uint_as_float(hi.w)};
            __syncwarp();
#pragma unroll
            for (int sft = 8; sft <= 16; sft <<= 1) {
#pragma unroll
                for (int i = 0; i < 8; i++) o[i] += shx(o[i], sft);
            }
            if (lane < 8)
                sts128(sb + OFF_FR + lane * 48, pack2(o[0], o[4]), pack2(o[2], o[6]), pack2(o[1], o[5]), pack2(o[3], o[7]));
            TS(lane == 0, 10);
        }
        asm volatile("bar.sync 3, 352;" ::: "memory");
        const unsigned* q = scr + G_PART + unit * 2048 + near_half(G_PART + unit * 2048, side) + lane * 4;
        if (DELAY_B) spin_cycles(DELAY_B);
        if (active) {
            const float k = reduce_unit(q, lane, tag, first);
            xold = badd2(xold, bmul2(ga, pack2(k, 0.f))) & 0xffffu;
            if (lane < 16) stg_rlx1(scr + x1w, (xold << 16) | tag);
            TS(first && lane == 0, 12);
        }
        if (first && lane == 0) mbar_arrive(s_empty + EM_X1 * 8);
        asm volatile("bar.sync 5, 352;" ::: "memory");
        if (active) {
            if (DELAY_D) spin_cycles(DELAY_D);
            const float k = reduce_unit(q, lane, tag | 4u);
            xold = badd2(xold, bmul2(gb, pack2(k, 0.f)));
            if (lane < 8) ((unsigned short*)out)[rcol] = (unsigned short)xold;
            if (c == 0 && first && lane == 0) stg_rlx1(scr + G_EPOCH, ep + 1u);
            TS(first && lane == 0, 16);
        }
        return;
    }

    const int vw = warp, tid = threadIdx.x;
    const int vecw = tid * 4 - (lane & 7) * 4 + t * 8 + bat * 4;
    unsigned* const ppart = scr + G_PART + (vw * 16 + (g >> 1)) * 2048 + c * 8 + bat * 4;
    const unsigned* const pside = scr + G_SIDE + ((vw * 16 + (lane & 15)) & 127) * 8;
    const int qword = G_Q + bat * 4096 + c * 32 + (tid >> 3) * 4 + t;
    const uint32_t one2 = 0x3f803f80u;

    const unsigned ep = ldg_rlx1(scr + G_EPOCH);
    if (tid < 64) {
        if (c < NMOD) stg_rlx1(scr + G_MOD + c * 64 + tid, 2u);
        stg_rlx1(scr + qword, 2u);
    }
    uint32_t xw0, xw1, aw0, aw1;
    {
        const int col0 = bat * DM + (vw * 4 + mi) * 16 + 2 * t;
        const uint32_t cw0 = __ldg((const unsigned*)(cin + col0)), cw1 = __ldg((const unsigned*)(cin + col0 + 8));
        xw0 = __ldg((const unsigned*)(xin + col0)); xw1 = __ldg((const unsigned*)(xin + col0 + 8));
        if (tid < 8) sts64(sb + OFF_FR + tid * 48 + 16, 0u, 0u);
        if (lane == 0) {
            const int lo = (c < NMOD) ? 2 : 4;
#pragma unroll 1
            for (int i = vw; i < N_IT + N_EM; i += NCW) {
                const int e = i - N_IT;
                if (i >= lo) mbar_init(s_full + i * 8, (e < 0 || e >= EM_PH) ? 1 : (e < EM_K ? NCW : (e < EM_V ? 4 : 8)));
            }
            asm volatile("fence.proxy.async.shared::cta;" ::: "memory");
        }
        __syncwarp();
        asm volatile("bar.sync 2, 384;" ::: "memory");
        float cv[4] = {bflo(cw0), bfhi(cw0), bflo(cw1), bfhi(cw1)};
#pragma unroll
        for (int i = 0; i < 4; i++) cv[i] = cv[i] * rcp(1.0f + ex2(-1.4426950408889634f * cv[i]));
        aw0 = pack2(cv[0], cv[1]); aw1 = pack2(cv[2], cv[3]);
    }
    const unsigned tag = (ep + 1u) & 1u;
    const uint32_t st1 = sb + OFF_STAT + bat * 80, st2 = st1 + 160;
    ln_stage1(xw0, xw1, st1, vw, lane);

    if (c < NMOD) {
        const uint32_t m = gemv32(sb + OFF_WMOD, sb + OFF_RED, s_full + IT_WMOD * 8, s_empty + EM_WMOD * 8, aw0, aw1, tid);
        if (tid < 64) stg_rlx1(scr + G_MOD + c * 64 + tid, m | tag);
    } else {
        bar_consumers();
    }
    TS(tid == 0, 4);
    {
        uint32_t y0, y1;
        ln_stage2(ln_load(st1), xw0, xw1, y0, y1);
        uint4 a, b;
        int it = 0;
        do { a = ldg_rlx4(scr + G_MOD + vecw); b = ldg_rlx4(scr + G_MOD + 1152 + vecw); }
        while (any_lane((bad4(a, tag) | bad4(b, tag)) & 7u) && ++it < SPIN_LIMIT);
        __syncwarp();
        aw0 = badd2(bmul2(y0, badd2(one2, hi2(b.x, b.y))), hi2(a.x, a.y));
        aw1 = badd2(bmul2(y1, badd2(one2, hi2(b.z, b.w))), hi2(a.z, a.w));
        TS(tid == 0, 5);
        const uint32_t q = gemv32(sb + OFF_WQ, sb + OFF_RED + 2304, s_full + IT_WQ * 8, s_empty + EM_WQ * 8, aw0, aw1, tid);
        if (tid < 64) {
            stg_rlx1(scr + qword, q | tag);
            uint4 v;
            int it = 0;
            do { v = ldg_rlx4(scr + G_Q + bb * 4096 + kvh * 256 + tid * 4); } while (any_lane(bad4(v, tag) & 7u) && ++it < SPIN_LIMIT);
            sts64(sb + OFF_QS + (vw * 4 + t) * 80 + g * 8, hi2(v.x, v.y), hi2(v.z, v.w));
        }
        bar_consumers();
        TS(tid == 0, 6);
    }
    uint32_t sc0, sc1, sh0, sh1;
    {
        uint4 d, e;
        unsigned bad;
        int it = 0;
        do {
            d = ldg_rlx4(scr + G_MOD + 3 * 1152 + vecw); e = ldg_rlx4(scr + G_MOD + 4 * 1152 + vecw);
            bad = bad4(d, tag) | bad4(e, tag);
        } while (any_lane(bad & 7u) && ++it < SPIN_LIMIT);
        __syncwarp();
        sh0 = hi2(d.x, d.y); sh1 = hi2(d.z, d.w);
        sc0 = badd2(one2, hi2(e.x, e.y)); sc1 = badd2(one2, hi2(e.z, e.w));
    }
    if (vw < 8) {
        uint4 qf[4];
#pragma unroll
        for (int i = 0; i < 4; i++) qf[i] = lds128(sb + OFF_QS + r * 80 + i * 16);
        const int mt = vw & 3;
        const uint32_t rowoff = (mt * 16 + r + 8 * (mi & 1)) * 128;
        const uint32_t sw = ((mi >> 1) ^ r) << 4;
        uint32_t mx = 0xff80ff80u;
#pragma unroll 1
        for (int i = (vw >> 2); i < 16; i += 2) {
            mbar_wait(s_full + (IT_K + i) * 8);
            const uint32_t base = sb + k_off(i) + rowoff;
            float c0[4] = {}, c1[4] = {};
            uint32_t a[4];
            ldsm4(a, base + sw);               mma16816(c0, a, qf[0].x, qf[0].y);
            ldsm4(a, base + 8192 + sw);        mma16816(c1, a, qf[2].x, qf[2].y);
            ldsm4(a, base + (sw ^ 32));        mma16816(c0, a, qf[0].z, qf[0].w);
            ldsm4(a, base + 8192 + (sw ^ 32)); mma16816(c1, a, qf[2].z, qf[2].w);
            ldsm4(a, base + (sw ^ 64));        mma16816(c0, a, qf[1].x, qf[1].y);
            ldsm4(a, base + 8192 + (sw ^ 64)); mma16816(c1, a, qf[3].x, qf[3].y);
            ldsm4(a, base + (sw ^ 96));        mma16816(c0, a, qf[1].z, qf[1].w);
            ldsm4(a, base + 8192 + (sw ^ 96)); mma16816(c1, a, qf[3].z, qf[3].w);
            __syncwarp();
            if (lane == 0) mbar_arrive(s_empty + (EM_K + i) * 8);
            const float scl = 0.08838834764831845f;
            uint32_t u0 = pack2(c0[0] + c1[0], c0[1] + c1[1]), u1 = pack2(c0[2] + c1[2], c0[3] + c1[3]);
            u0 = pack2(bflo(u0) * scl, bfhi(u0) * scl); u1 = pack2(bflo(u1) * scl, bfhi(u1) * scl);
            mx = bmax2(mx, bmax2(u0, u1));
            if (t == 0) {
                const uint32_t pa = sb + OFF_S + (i * 64 + 16 * (g >> 1) + 4 * mt + bat) * 4;
                sts32(pa, u0); sts32(pa + 8, u1);
            }
            if (i == PH_K && tid < 2) stg_pkt(scr + G_ML + c * 8 + tid * 4, 0.f, 0.f, 0.f, 0.f, 2u);
        }
#pragma unroll
        for (int o = 4; o <= 16; o <<= 1) mx = bmax2(mx, __shfl_xor_sync(0xffffffffu, mx, o));
        if (lane == 0) sts32(sb + OFF_WMX + vw * 4, mx);
    }
    bar_consumers();
    TS(tid == 0, 7);
    {
        const float L2E = 1.4426950408889634f;
        uint4 sv = make_uint4(0, 0, 0, 0);
        float m0 = 0.f, m1 = 0.f;
        if (vw < 8) {
            uint4 ma = lds128(sb + OFF_WMX), mb = lds128(sb + OFF_WMX + 16);
            const uint32_t mx = bmax2(bmax2(bmax2(ma.x, ma.y), bmax2(ma.z, ma.w)), bmax2(bmax2(mb.x, mb.y), bmax2(mb.z, mb.w)));
            m0 = bflo(mx); m1 = bfhi(mx);
            sv = lds128(sb + OFF_S + tid * 16);
            float e0 = (ex2((bflo(sv.x) - m0) * L2E) + ex2((bflo(sv.y) - m0) * L2E)) + (ex2((bflo(sv.z) - m0) * L2E) + ex2((bflo(sv.w) - m0) * L2E));
            float e1 = (ex2((bfhi(sv.x) - m1) * L2E) + ex2((bfhi(sv.y) - m1) * L2E)) + (ex2((bfhi(sv.z) - m1) * L2E) + ex2((bfhi(sv.w) - m1) * L2E));
#pragma unroll
            for (int o = 16; o > 0; o >>= 1) { e0 += shx(e0, o); e1 += shx(e1, o); }
            if (lane == 0) sts64(sb + OFF_WMX + 32 + vw * 8, __float_as_uint(e0), __float_as_uint(e1));
        }
        bar_consumers();
        if (vw == 0) {
            float l0 = 0.f, l1 = 0.f;
#pragma unroll
            for (int w = 0; w < 4; w++) {
                uint4 s = lds128(sb + OFF_WMX + 32 + w * 16);
                l0 += __uint_as_float(s.x) + __uint_as_float(s.z); l1 += __uint_as_float(s.y) + __uint_as_float(s.w);
            }
            if (tid < 2) stg_pkt(scr + G_ML + c * 8 + tid * 4, m0, l0, m1, l1, tag);
            {
                const bool rd = lane < 4 && lane != sp;
                uint4 v = make_uint4(rd ? 2u : tag, 0, 0, 0);
                int it = 0;
                do { ldg_pkt_if(v, scr + G_ML + (kvh * 8 + (lane & 3) * 2 + bb) * 8, (v.x ^ tag) & 7u); }
                while (any_lane((v.x ^ tag) & 7u) && ++it < SPIN_LIMIT);
                if (rd) { m0 = untagf(v.x); l0 = __uint_as_float(v.y); m1 = __uint_as_float(v.z); l1 = __uint_as_float(v.w); }
            }
            float g0 = fmaxf(m0, shx(m0, 1)), g1 = fmaxf(m1, shx(m1, 1));
            g0 = fmaxf(g0, shx(g0, 2)); g1 = fmaxf(g1, shx(g1, 2));
            l0 *= ex2((m0 - g0) * L2E); l1 *= ex2((m1 - g1) * L2E);
            l0 += shx(l0, 1); l1 += shx(l1, 1);
            l0 += shx(l0, 2); l1 += shx(l1, 2);
            if (lane == 0)
                sts128(sb + OFF_WMX + 96, __float_as_uint(g0), __float_as_uint(g1), __float_as_uint(1.0f / l0), __float_as_uint(1.0f / l1));
        }
        bar_consumers();
        if (vw < 8) {
            const uint4 gs = lds128(sb + OFF_WMX + 96);
            const float g0 = __uint_as_float(gs.x), g1 = __uint_as_float(gs.y), i0 = __uint_as_float(gs.z), i1 = __uint_as_float(gs.w);
            const uint32_t a0 = pack2(ex2((bflo(sv.x) - g0) * L2E) * i0, ex2((bflo(sv.y) - g0) * L2E) * i0);
            const uint32_t a1 = pack2(ex2((bflo(sv.z) - g0) * L2E) * i0, ex2((bflo(sv.w) - g0) * L2E) * i0);
            const uint32_t b0 = pack2(ex2((bfhi(sv.x) - g1) * L2E) * i1, ex2((bfhi(sv.y) - g1) * L2E) * i1);
            const uint32_t b1 = pack2(ex2((bfhi(sv.z) - g1) * L2E) * i1, ex2((bfhi(sv.w) - g1) * L2E) * i1);
            sts64(sb + OFF_P + tid * 8, a0, a1); sts64(sb + OFF_P + PSTR + tid * 8, b0, b1);
        }
        bar_consumers();
        TS(tid == 0, 8);
    }
    const uint32_t rin = vw * 2048 + (r + 8 * (mi >> 1)) * 128;
    const uint32_t rsw = ((mi & 1) ^ r) << 4;
    uint32_t ra[2][4][4];
    unsigned sidew = 2u;
    if (vw < 8) {
        float c0[4] = {}, c1[4] = {};
        const uint32_t vo = (vw >> 2) * 8192 + (r + 8 * (mi >> 1)) * 128 + ((((2 * vw + (mi & 1)) & 7) ^ r) << 4);
        const uint32_t pa = sb + OFF_P + bat * PSTR + t * 32;
#pragma unroll 1
        for (int i = 0; i < 16; i++) {
            uint4 pb0 = lds128(pa + i * 128), pb1 = lds128(pa + i * 128 + 16);
            mbar_wait(s_full + it_v(i) * 8);
            const uint32_t base = sb + v_off(i) + vo;
            uint32_t a0[4], a1[4], a2[4], a3[4];
            ldsm4t(a0, base); ldsm4t(a1, base + 2048); ldsm4t(a2, base + 4096); ldsm4t(a3, base + 6144);
            mma16816(c0, a0, pb0.x, pb0.y);
            mma16816(c1, a1, pb0.z, pb0.w);
            mma16816(c0, a2, pb1.x, pb1.y);
            mma16816(c1, a3, pb1.z, pb1.w);
            __syncwarp();
            if (lane == 0) mbar_arrive(s_empty + (EM_V + i) * 8);
            if (i == SIDE_V) { mbar_wait(s_empty + EM_PH * 8); sidew = ldg_rlx1(pside); }
        }
        if (t < 2)
            stg_pkt(scr + G_OP + kvh * 4096 + (j >> 2) * 2048 + t * HALF + (j & 3) * 256 + vw * 32 + g * 4,
                    c0[0] + c1[0], c0[1] + c1[1], c0[2] + c1[2], c0[3] + c1[3], tag);
        TS(tid == 0, 9);
    } else {
        mbar_wait(s_full + it_v(SIDE_V) * 8);
        mbar_wait(s_empty + EM_PH * 8);
    }
    unsigned hm;
    {
        int it = 0;
        while (any_lane((sidew ^ tag) & 7u) && ++it < SPIN_LIMIT) sidew = ldg_rlx1(pside);
        __syncwarp();
        const int uw = G_PART + (vw * 16 + (lane & 15)) * 2048;
        hm = __ballot_sync(0xffffffffu, near_half(uw, sidew >> 4)) >> (g >> 1);
    }
    const unsigned side = __float_as_uint(ldsf(sb + OFF_WMX + 112));
    {
        mbar_wait(s_full + IT_WO * 8);
#pragma unroll
        for (int mt = 0; mt < 4; mt++) ldsm4t(ra[0][mt], sb + OFF_WO0 + rin + (rsw ^ (mt * 32)));
        mbar_wait(s_full + (IT_WO + 1) * 8);
#pragma unroll
        for (int mt = 0; mt < 4; mt++) ldsm4t(ra[1][mt], sb + OFF_WO1 + rin + (rsw ^ (mt * 32)));
        asm volatile("bar.sync 3, 352;" ::: "memory");
        const uint4 fr = lds128(sb + OFF_FR + r * 48);
        float cc[4][4] = {};
#pragma unroll
        for (int mt = 0; mt < 4; mt++) mma16816(cc[mt], ra[0][mt], fr.x, fr.y);
#pragma unroll
        for (int mt = 0; mt < 4; mt++) mma16816(cc[mt], ra[1][mt], fr.z, fr.w);
        if (t == 0) publish_partials(ppart, hm, cc, tag);
        __syncwarp();
        TS(tid == 0, 11);
    }
    uint32_t ag[4][5][4];
    const uint32_t gub = s_full + (IT_GU + 2 * (vw / 3)) * 8;
    const uint32_t gbase = sb + ((mi & 1) ? OFF_U : OFF_G) + (vw * 64 + r + 8 * (mi >> 1)) * 80;
    bool gpre;
    while (true) {
        gpre = __all_sync(0xffffffffu, mbar_test(gub) && mbar_test(gub + 8));
        if (gpre || __all_sync(0xffffffffu, mbar_test(s_empty + EM_X1 * 8))) break;
    }
    if (gpre) {
#pragma unroll
        for (int ks = 0; ks < 4; ks++)
#pragma unroll
            for (int q = 0; q < 5; q++) ldsm4t(ag[ks][q], gbase + ks * 1280 + q * 16);
        mbar_wait(s_empty + EM_X1 * 8);
    }
    bool dpre;
    {
        uint4 v;
        int it = 0;
        const int xw = G_X1 + (vw >> 3) * 2048;
        const unsigned* px = scr + xw + near_half(xw, side) + (vecw & 1023);
        spin_cycles(DELAY_C);
        while (true) {
            v = ldg_rlx4(px);
            if (!any_lane(bad4(v, tag) & 7u) || ++it >= SPIN_LIMIT) break;
            spin_cycles(BACK_C);
        }
        xw0 = hi2(v.x, v.y); xw1 = hi2(v.z, v.w);
        __syncwarp();
        ln_stage1(xw0, xw1, st2, vw, lane);
        dpre = __all_sync(0xffffffffu, mbar_test(s_full + IT_WD * 8) && mbar_test(s_full + (IT_WD + 1) * 8));
        bar_consumers();
        TS(tid == 0, 13);
        const LnStat ls = ln_load(st2);
        if (dpre) {
#pragma unroll
            for (int mt = 0; mt < 4; mt++) ldsm4t(ra[0][mt], sb + OFF_D0 + rin + (rsw ^ (mt * 32)));
#pragma unroll
            for (int mt = 0; mt < 4; mt++) ldsm4t(ra[1][mt], sb + OFF_D1 + rin + (rsw ^ (mt * 32)));
        }
        uint32_t y0, y1;
        ln_stage2(ls, xw0, xw1, y0, y1);
        aw0 = badd2(bmul2(y0, sc0), sh0); aw1 = badd2(bmul2(y1, sc1), sh1);
        uint32_t bf[4][2];
        make_bfrags(bf, aw0, aw1, r);
        if (!gpre) {
            mbar_wait(gub); mbar_wait(gub + 8);
#pragma unroll
            for (int ks = 0; ks < 4; ks++)
#pragma unroll
                for (int q = 0; q < 5; q++) ldsm4t(ag[ks][q], gbase + ks * 1280 + q * 16);
        }
        float cc[5][4] = {};
#pragma unroll
        for (int ks = 0; ks < 4; ks++)
#pragma unroll
            for (int q = 0; q < 5; q++) mma16816(cc[q], ag[ks][q], bf[ks][0], bf[ks][1]);
        if (t == 0) {
#pragma unroll
            for (int q = 0; q < 5; q++) sts128f(sb + OFF_RED + vw * 640 + q * 128 + g * 16, cc[q]);
        }
        bar_consumers();
        TS(tid == 0, 14);
        if (tid < 160) {
            float sv[NCW];
#pragma unroll
            for (int w = 0; w < NCW; w++) sv[w] = ldsf(sb + OFF_RED + w * 640 + tid * 4);
            const float s = ((sv[0] + sv[1]) + (sv[2] + sv[3])) + ((sv[4] + sv[5]) + (sv[6] + sv[7])) + sv[8];
            const uint32_t gu = pack2(s, __shfl_down_sync(0xffffffffu, s, 2));
            const float gt = bflo(gu);
            const uint32_t hh = pack2(((gt > 0.f) ? gt : gt * 0.0f) * bfhi(gu), 0.f);
            const int rr = (tid >> 2) - (c & 1) * 4;
            if ((tid & 2) == 0 && rr >= 0 && rr < 36)
                sts16(sb + OFF_FR + ((tid & 1) * 4 + ((rr & 7) >> 1)) * 48 + (rr >> 3) * 4 + (rr & 1) * 2, hh);
        }
    }
    {
        if (!dpre) {
            mbar_wait(s_full + IT_WD * 8);
#pragma unroll
            for (int mt = 0; mt < 4; mt++) ldsm4t(ra[0][mt], sb + OFF_D0 + rin + (rsw ^ (mt * 32)));
            mbar_wait(s_full + (IT_WD + 1) * 8);
#pragma unroll
            for (int mt = 0; mt < 4; mt++) ldsm4t(ra[1][mt], sb + OFF_D1 + rin + (rsw ^ (mt * 32)));
        }
        uint32_t a2[4][4];
        mbar_wait(s_full + (IT_WD + 2) * 8);
        const int row = vw * 4 + (r & 3);
        const uint32_t b2 = sb + OFF_D2 + row * 128, sw2 = ((mi & 1) ^ (row & 7)) << 4;
#pragma unroll
        for (int mt = 0; mt < 4; mt++) ldsm4t(a2[mt], b2 + (sw2 ^ (mt * 32)));
        bar_consumers();
        const uint4 fr = lds128(sb + OFF_FR + r * 48);
        const uint2 f2 = lds64(sb + OFF_FR + r * 48 + 16);
        float cc[4][4] = {};
#pragma unroll
        for (int mt = 0; mt < 4; mt++) mma16816(cc[mt], ra[0][mt], fr.x, fr.y);
#pragma unroll
        for (int mt = 0; mt < 4; mt++) mma16816(cc[mt], ra[1][mt], fr.z, fr.w);
#pragma unroll
        for (int mt = 0; mt < 4; mt++) mma16816(cc[mt], a2[mt], f2.x, f2.y);
        if (t == 0) publish_partials(ppart, hm, cc, tag | 4u);
        __syncwarp();
        asm volatile("bar.arrive 5, 352;" ::: "memory");
        TS(tid == 0, 15);
    }
}

typedef CUresult (*EncodeFn)(CUtensorMap*, CUtensorMapDataType, cuuint32_t, void*, const cuuint64_t*, const cuuint64_t*,
                             const cuuint32_t*, const cuuint32_t*, CUtensorMapInterleave, CUtensorMapSwizzle,
                             CUtensorMapL2promotion, CUtensorMapFloatOOBfill);

void make_map(EncodeFn enc, CUtensorMap* m, const void* p, cuuint64_t d0, cuuint64_t d1, cuuint64_t d2,
              cuuint64_t s1, cuuint64_t s2, cuuint32_t b0, cuuint32_t b1, cuuint32_t b2, CUtensorMapSwizzle sw,
              CUtensorMapL2promotion pr = CU_TENSOR_MAP_L2_PROMOTION_L2_128B) {
    cuuint64_t dims[3] = {d0, d1, d2};
    cuuint64_t str[2] = {s1, s2};
    cuuint32_t box[3] = {b0, b1, b2};
    cuuint32_t es[3] = {1, 1, 1};
    enc(m, CU_TENSOR_MAP_DATA_TYPE_BFLOAT16, 3, const_cast<void*>(p), dims, str, box, es,
        CU_TENSOR_MAP_INTERLEAVE_NONE, sw, pr, CU_TENSOR_MAP_FLOAT_OOB_FILL_NONE);
}

}

extern "C" void kernel_launch(void* const* d_in, const int* in_sizes, int n_in, void* d_out, int out_size) {
    (void)in_sizes; (void)n_in; (void)out_size;
    void* fn = nullptr;
    cudaDriverEntryPointQueryResult qr;
    cudaGetDriverEntryPoint("cuTensorMapEncodeTiled", &fn, cudaEnableDefault, &qr);
    EncodeFn enc = (EncodeFn)fn;
    cudaFuncSetAttribute(fused_block_kernel, cudaFuncAttributeMaxDynamicSharedMemorySize, SMEM_BYTES);

    const void *x = d_in[0], *kc = d_in[1], *vc = d_in[2], *wq = d_in[3], *wo = d_in[4];
    const void *wg = d_in[6], *wu = d_in[7], *wd = d_in[8], *cc = d_in[9], *wmod = d_in[10];
    const CUtensorMapSwizzle S128 = CU_TENSOR_MAP_SWIZZLE_128B, S64 = CU_TENSOR_MAP_SWIZZLE_64B, S0 = CU_TENSOR_MAP_SWIZZLE_NONE;
    Maps m;
    make_map(enc, &m.m[M_K], kc, 64, 32ull * 32768, 2, 256, 128, 64, 64, 2, S128, CU_TENSOR_MAP_L2_PROMOTION_L2_256B);
    make_map(enc, &m.m[M_V], vc, 64, 32ull * 32768, 2, 256, 128, 64, 64, 2, S128, CU_TENSOR_MAP_L2_PROMOTION_L2_256B);
    make_map(enc, &m.m[M_WMOD], wmod, 3456, 144, 4, 3456 * 2, 3456 * 2 * 144, 32, 144, 2, S64);
    make_map(enc, &m.m[M_WQ], wq, 4096, 144, 4, 4096 * 2, 4096 * 2 * 144, 32, 144, 2, S64);
    make_map(enc, &m.m[M_WG], wg, 4608, 576, 1, 4608 * 2, 4608 * 2 * 576, 40, 192, 1, S0);
    make_map(enc, &m.m[M_WU], wu, 4608, 576, 1, 4608 * 2, 4608 * 2 * 576, 40, 192, 1, S0);
    make_map(enc, &m.m[M_WO], wo, 64, 4096, 9, 1152, 128, 64, 16, 9, S128);
    make_map(enc, &m.m[M_WD], wd, 64, 4608, 9, 1152, 128, 64, 16, 9, S128);
    make_map(enc, &m.m[M_WD4], wd, 64, 4608, 9, 1152, 128, 64, 4, 9, S128);
    fused_block_kernel<<<NCTA, NTHR, SMEM_BYTES>>>(m, (const __nv_bfloat16*)x, (const __nv_bfloat16*)cc,
                                                   (__nv_bfloat16*)d_out);
}
```

```cpp
#include <cuda_runtime.h>
#include <cuda.h>
#include <cuda_bf16.h>
#include <stdint.h>

namespace {

constexpr int DM = 576;
constexpr int NCTA = 128;
constexpr int NCW = 9;
constexpr int NTHR = (NCW + 3) * 32;
constexpr int NMOD = 108;

#define WIN_MAIN 4
#define WIN_TAIL 3
#define PACE_GBS 3100
#define PACE_LEAD 28672
#define PACE_TAIL 2700
#define PACE_D 3300
#define TAIL_GAP 250
#define DELAY_B 300
#define NOCATCH 99
#define WIN_SWITCH 38
#define OPEN_WIN 1
#define DELAY_D 300
#define EARLY_PF 8192
#define TM_PF 1
#define XREP 2
#define PH_V 7
#define SIDE_V 11
#define NPROBE 10
#define NPROBE0 3
#define PH_K 8

constexpr int IT_WMOD = 0, IT_WQ = 2, IT_K = 4, IT_V = 20, IT_WO = 36, IT_GU = 38, IT_WD = 44, N_IT = 47;
__device__ __forceinline__ constexpr int it_v(int k) { return IT_V + k; }
constexpr int EM_WMOD = 0, EM_WQ = 1, EM_K = 2, EM_V = 18, EM_PH = 34, EM_X1 = 35, EM_CH = 36, EM_SD = 37, N_EM = 38;

constexpr int RING = 13 * 16384;
constexpr int OFF_WMOD = 0, OFF_WQ = 36864, OFF_K0 = 73728;
constexpr int OFF_WO0 = 180224, OFF_WO1 = 0, OFF_G = 18432, OFF_U = 73728;
constexpr int OFF_D = 129024, DSTR = 14336;
constexpr int PSTR = 2064;
constexpr int OFF_P = RING;
constexpr int OFF_S = OFF_P + 4160;
constexpr int OFF_RED = OFF_S + 4096;
constexpr int OFF_QS = OFF_RED + 5760;
constexpr int OFF_FR = OFF_QS + 640;
constexpr int OFF_STAT = OFF_FR + 384;
constexpr int OFF_WMX = OFF_STAT + 320;
constexpr int OFF_BAR = OFF_WMX + 128;
constexpr int SMEM_USED = OFF_BAR + (N_IT + N_EM) * 8;
constexpr int SMEM_BYTES = SMEM_USED + 1024;
static_assert(SMEM_BYTES <= 232448, "smem");

struct Maps { CUtensorMap m[8]; };
enum { M_K, M_V, M_WMOD, M_WQ, M_WG, M_WU, M_WO, M_WD };

constexpr int HALF = 1024;
constexpr int G_PART = 0;
constexpr int G_OP = G_PART + 144 * 2048;
constexpr int G_X1 = G_OP + 16 * 4096;
constexpr int G_PROBE = G_X1 + XREP * 4096;
constexpr int G_SIDE = G_PROBE + 2048;
constexpr int G_EPOCH = G_SIDE + 1024;
constexpr int G_MOD = G_EPOCH + 1024;
constexpr int G_Q = G_MOD + 7 * 2048;
constexpr int G_ML = G_Q + 8 * 2048;
constexpr int G_WORDS = G_ML + 2048;
static_assert(G_MOD % 2048 == 0 && G_OP % 2048 == 0 && G_X1 % 2048 == 0 && G_PROBE % 2048 == 0, "halves");
static_assert(G_WORDS * 4 <= (2 << 20), "scratch must fit one 2 MB page");
__device__ __align__(128) unsigned g_raw[(2 << 20) / 4 + G_WORDS + 8192];
__device__ __forceinline__ int near_half(int w, unsigned side) { return ((__popc(w & 0x2C800) ^ side) & 1) << 10; }
__device__ __forceinline__ int dual(int base, int i) { return base + i + (i & ~1023); }
__device__ __forceinline__ int dual_near(int base, int i, unsigned side) { const int w = dual(base, i); return w + near_half(w, side); }
#define g_ts ((unsigned long long*)(scr + G_WORDS))

constexpr int SPIN_LIMIT = 1 << 20;

__device__ __forceinline__ uint32_t smem_u32(const void* p) { return (uint32_t)__cvta_generic_to_shared(p); }
__device__ __forceinline__ void mbar_init(uint32_t bar, int cnt) {
    asm volatile("mbarrier.init.shared::cta.b64 [%0], %1;" ::"r"(bar), "r"(cnt) : "memory");
}
__device__ __forceinline__ void mbar_expect_tx(uint32_t bar, uint32_t bytes) {
    asm volatile("mbarrier.arrive.expect_tx.shared::cta.b64 _, [%0], %1;" ::"r"(bar), "r"(bytes) : "memory");
}
__device__ __forceinline__ void mbar_arrive(uint32_t bar) {
    asm volatile("mbarrier.arrive.shared::cta.b64 _, [%0];" ::"r"(bar) : "memory");
}
__device__ __forceinline__ void mbar_wait(uint32_t bar) {
    asm volatile("{\n.reg .pred p;\nW_%=:\nmbarrier.try_wait.parity.shared::cta.b64 p, [%0], 0;\n@!p bra W_%=;\n}"
                 ::"r"(bar) : "memory");
}
__device__ __forceinline__ bool mbar_test(uint32_t bar) {
    uint32_t ok;
    asm volatile("{\n.reg .pred p;\nmbarrier.test_wait.parity.shared::cta.b64 p, [%1], 0;\nselp.u32 %0, 1, 0, p;\n}"
                 : "=r"(ok) : "r"(bar) : "memory");
    return ok;
}
__device__ __forceinline__ uint32_t gtime32() { uint32_t t; asm volatile("mov.u32 %0, %%globaltimer_lo;" : "=r"(t)); return t; }
__device__ __forceinline__ void tma3d(uint32_t dst, const CUtensorMap* m, int x, int y, int z, uint32_t bar) {
    asm volatile("cp.async.bulk.tensor.3d.shared::cluster.global.mbarrier::complete_tx::bytes [%0], [%1, {%3, %4, %5}], [%2];"
                 ::"r"(dst), "l"(m), "r"(bar), "r"(x), "r"(y), "r"(z) : "memory");
}
__device__ __forceinline__ void bar_consumers() { asm volatile("bar.sync 1, 288;" ::: "memory"); }

__device__ __forceinline__ void ldsm4(uint32_t (&a)[4], uint32_t addr) {
    asm volatile("ldmatrix.sync.aligned.m8n8.x4.shared.b16 {%0,%1,%2,%3}, [%4];"
                 : "=r"(a[0]), "=r"(a[1]), "=r"(a[2]), "=r"(a[3]) : "r"(addr) : "memory");
}
__device__ __forceinline__ void ldsm4t(uint32_t (&a)[4], uint32_t addr) {
    asm volatile("ldmatrix.sync.aligned.m8n8.x4.trans.shared.b16 {%0,%1,%2,%3}, [%4];"
                 : "=r"(a[0]), "=r"(a[1]), "=r"(a[2]), "=r"(a[3]) : "r"(addr) : "memory");
}
__device__ __forceinline__ void mma16816(float (&c)[4], const uint32_t (&a)[4], uint32_t b0, uint32_t b1) {
    asm volatile("mma.sync.aligned.m16n8k16.row.col.f32.bf16.bf16.f32 {%0,%1,%2,%3}, {%4,%5,%6,%7}, {%8,%9}, {%0,%1,%2,%3};"
                 : "+f"(c[0]), "+f"(c[1]), "+f"(c[2]), "+f"(c[3])
                 : "r"(a[0]), "r"(a[1]), "r"(a[2]), "r"(a[3]), "r"(b0), "r"(b1));
}
__device__ __forceinline__ float ldsf(uint32_t a) { float v; asm volatile("ld.shared.f32 %0, [%1];" : "=f"(v) : "r"(a) : "memory"); return v; }
__device__ __forceinline__ uint2 lds64(uint32_t a) {
    uint2 v; asm volatile("ld.shared.v2.u32 {%0,%1}, [%2];" : "=r"(v.x), "=r"(v.y) : "r"(a) : "memory"); return v;
}
__device__ __forceinline__ uint4 lds128(uint32_t a) {
    uint4 v; asm volatile("ld.shared.v4.u32 {%0,%1,%2,%3}, [%4];" : "=r"(v.x), "=r"(v.y), "=r"(v.z), "=r"(v.w) : "r"(a) : "memory"); return v;
}
__device__ __forceinline__ void sts16(uint32_t a, uint32_t v) { asm volatile("st.shared.u16 [%0], %1;" ::"r"(a), "h"((unsigned short)v) : "memory"); }
__device__ __forceinline__ void sts32(uint32_t a, uint32_t v) { asm volatile("st.shared.u32 [%0], %1;" ::"r"(a), "r"(v) : "memory"); }
__device__ __forceinline__ void sts64(uint32_t a, uint32_t x, uint32_t y) { asm volatile("st.shared.v2.u32 [%0], {%1,%2};" ::"r"(a), "r"(x), "r"(y) : "memory"); }
__device__ __forceinline__ void sts128(uint32_t a, uint32_t x, uint32_t y, uint32_t z, uint32_t w) {
    asm volatile("st.shared.v4.u32 [%0], {%1,%2,%3,%4};" ::"r"(a), "r"(x), "r"(y), "r"(z), "r"(w) : "memory");
}
__device__ __forceinline__ void sts128f(uint32_t a, const float (&c)[4]) {
    asm volatile("st.shared.v4.f32 [%0], {%1,%2,%3,%4};" ::"r"(a), "f"(c[0]), "f"(c[1]), "f"(c[2]), "f"(c[3]) : "memory");
}
__device__ __forceinline__ unsigned ldg_rlx1(const unsigned* p) {
    unsigned v; asm volatile("ld.relaxed.gpu.global.u32 %0, [%1];" : "=r"(v) : "l"(p) : "memory"); return v;
}
__device__ __forceinline__ uint4 ldg_rlx4(const unsigned* p) {
    uint4 v; asm volatile("ld.relaxed.gpu.global.v4.u32 {%0,%1,%2,%3}, [%4];" : "=r"(v.x), "=r"(v.y), "=r"(v.z), "=r"(v.w) : "l"(p) : "memory"); return v;
}
__device__ __forceinline__ uint4 ldg_pkt(const unsigned* p) {
    uint4 v;
    asm volatile("{\n.reg .b128 t;\n.reg .b64 lo, hi;\nld.relaxed.gpu.global.b128 t, [%4];\nmov.b128 {lo, hi}, t;\n"
                 "mov.b64 {%0,%1}, lo;\nmov.b64 {%2,%3}, hi;\n}"
                 : "=r"(v.x), "=r"(v.y), "=r"(v.z), "=r"(v.w) : "l"(p) : "memory");
    return v;
}
__device__ __forceinline__ void ldg_pkt_if(uint4& v, const unsigned* a, unsigned p) {
    asm volatile("{\n.reg .pred q;\n.reg .b128 t;\n.reg .b64 lo, hi;\nsetp.ne.u32 q, %5, 0;\n"
                 "mov.b64 lo, {%0,%1};\nmov.b64 hi, {%2,%3};\nmov.b128 t, {lo, hi};\n"
                 "@q ld.relaxed.gpu.global.b128 t, [%4];\nmov.b128 {lo, hi}, t;\n"
                 "mov.b64 {%0,%1}, lo;\nmov.b64 {%2,%3}, hi;\n}"
                 : "+r"(v.x), "+r"(v.y), "+r"(v.z), "+r"(v.w) : "l"(a), "r"(p) : "memory");
}
__device__ __forceinline__ bool any_lane(unsigned x) { return __any_sync(0xffffffffu, x != 0); }
__device__ __forceinline__ void stg_pkt(unsigned* p, float a, float b, float c, float d, unsigned tag) {
    unsigned x = (__float_as_uint(a) & ~7u) | tag;
    asm volatile("{\n.reg .b128 t;\n.reg .b64 lo, hi;\nmov.b64 lo, {%1,%2};\nmov.b64 hi, {%3,%4};\nmov.b128 t, {lo, hi};\n"
                 "st.relaxed.gpu.global.b128 [%0], t;\n}"
                 ::"l"(p), "r"(x), "r"(__float_as_uint(b)), "r"(__float_as_uint(c)), "r"(__float_as_uint(d)) : "memory");
}
__device__ __forceinline__ void stg_rlx1(unsigned* p, unsigned x) { asm volatile("st.relaxed.gpu.global.u32 [%0], %1;" ::"l"(p), "r"(x) : "memory"); }
__device__ __forceinline__ unsigned bad4(const uint4& v, unsigned tag) {
    return ((v.x ^ tag) | (v.y ^ tag)) | ((v.z ^ tag) | (v.w ^ tag));
}
__device__ __forceinline__ float untagf(unsigned w) { return __uint_as_float(w & ~7u); }
__device__ __forceinline__ uint32_t pack2(float lo, float hi) {
    uint32_t r; asm("cvt.rn.bf16x2.f32 %0, %1, %2;" : "=r"(r) : "f"(hi), "f"(lo)); return r;
}
__device__ __forceinline__ float bflo(uint32_t w) { return __uint_as_float(w << 16); }
__device__ __forceinline__ float bfhi(uint32_t w) { return __uint_as_float(w & 0xffff0000u); }
__device__ __forceinline__ uint32_t hi2(uint32_t a, uint32_t b) { return __byte_perm(a, b, 0x7632); }
__device__ __forceinline__ uint32_t badd2(uint32_t a, uint32_t b) { uint32_t r; asm("add.rn.bf16x2 %0, %1, %2;" : "=r"(r) : "r"(a), "r"(b)); return r; }
__device__ __forceinline__ uint32_t bsub2(uint32_t a, uint32_t b) { uint32_t r; asm("sub.rn.bf16x2 %0, %1, %2;" : "=r"(r) : "r"(a), "r"(b)); return r; }
__device__ __forceinline__ uint32_t bmul2(uint32_t a, uint32_t b) { uint32_t r; asm("mul.rn.bf16x2 %0, %1, %2;" : "=r"(r) : "r"(a), "r"(b)); return r; }
__device__ __forceinline__ uint32_t bmax2(uint32_t a, uint32_t b) { uint32_t r; asm("max.bf16x2 %0, %1, %2;" : "=r"(r) : "r"(a), "r"(b)); return r; }
__device__ __forceinline__ float ex2(float x) { float r; asm("ex2.approx.ftz.f32 %0, %1;" : "=f"(r) : "f"(x)); return r; }
__device__ __forceinline__ float rcp(float x) { float r; asm("rcp.approx.ftz.f32 %0, %1;" : "=f"(r) : "f"(x)); return r; }
__device__ __forceinline__ float fsqrt(float x) { float r; asm("sqrt.approx.ftz.f32 %0, %1;" : "=f"(r) : "f"(x)); return r; }
__device__ __forceinline__ float shx(float v, int m) { return __shfl_xor_sync(0xffffffffu, v, m); }
#define TS(cond, slot) do { } while (0)

__device__ __forceinline__ uint32_t k_off(int i) { return i < 8 ? OFF_K0 + i * 16384 : (i - 8) * 16384; }
__device__ __forceinline__ uint32_t v_off(int i) { return i < 5 ? (8 + i) * 16384 : (i - 5) * 16384; }

__device__ __forceinline__ void stg_ph(unsigned* p) { stg_pkt(p, 0.f, 0.f, 0.f, 0.f, 2u); }

__device__ __forceinline__ void ln_stage1(uint32_t xw0, uint32_t xw1, uint32_t st, int vw, int lane) {
    const float piv = __shfl_sync(0xffffffffu, bflo(xw0), lane & 4);
    const float d0 = bflo(xw0) - piv, d1 = bfhi(xw0) - piv, d2 = bflo(xw1) - piv, d3 = bfhi(xw1) - piv;
    float s1 = (d0 + d1) + (d2 + d3), s2 = (d0 * d0 + d1 * d1) + (d2 * d2 + d3 * d3);
    s1 += shx(s1, 1); s2 += shx(s2, 1);
    s1 += shx(s1, 2); s2 += shx(s2, 2);
    s1 += shx(s1, 8); s2 += shx(s2, 8);
    s1 += shx(s1, 16); s2 += shx(s2, 16);
    if ((lane & 27) == 0)
        sts64(st + vw * 8, __float_as_uint(piv + s1 * (1.0f / 64.0f)), __float_as_uint(s2 - s1 * s1 * (1.0f / 64.0f)));
}
struct LnStat { uint4 a, b, c, d; uint2 e; };
__device__ __forceinline__ LnStat ln_load(uint32_t st) {
    LnStat s; s.a = lds128(st); s.b = lds128(st + 16); s.c = lds128(st + 32); s.d = lds128(st + 48); s.e = lds64(st + 64);
    return s;
}
__device__ __forceinline__ void ln_stage2(const LnStat& s, uint32_t xw0, uint32_t xw1, uint32_t& y0, uint32_t& y1) {
    const float m[9] = {__uint_as_float(s.a.x), __uint_as_float(s.a.z), __uint_as_float(s.b.x), __uint_as_float(s.b.z),
                        __uint_as_float(s.c.x), __uint_as_float(s.c.z), __uint_as_float(s.d.x), __uint_as_float(s.d.z), __uint_as_float(s.e.x)};
    const float mean = (((m[0] + m[1]) + (m[2] + m[3])) + ((m[4] + m[5]) + (m[6] + m[7])) + m[8]) * (1.0f / NCW);
    const float m2 = ((__uint_as_float(s.a.y) + __uint_as_float(s.a.w)) + (__uint_as_float(s.b.y) + __uint_as_float(s.b.w))) +
                     ((__uint_as_float(s.c.y) + __uint_as_float(s.c.w)) + (__uint_as_float(s.d.y) + __uint_as_float(s.d.w))) + __uint_as_float(s.e.y);
    float d[9];
#pragma unroll
    for (int w = 0; w < 9; w++) d[w] = m[w] - mean;
    const float acc = (d[0] * d[0] + d[1] * d[1] + d[2] * d[2]) + (d[3] * d[3] + d[4] * d[4] + d[5] * d[5]) + (d[6] * d[6] + d[7] * d[7] + d[8] * d[8]);
    const float var = (m2 + 64.0f * acc) * (1.0f / DM);
    const uint32_t mv = pack2(mean, var);
    const float ve = bflo(pack2(bfhi(mv) + 1e-5f, 0.f));
    const float rinv = rcp(bflo(pack2(fsqrt(ve), 0.f)));
    const uint32_t mm = __byte_perm(mv, mv, 0x1010);
    const uint32_t e0 = bsub2(xw0, mm), e1 = bsub2(xw1, mm);
    y0 = pack2(bflo(e0) * rinv, bfhi(e0) * rinv); y1 = pack2(bflo(e1) * rinv, bfhi(e1) * rinv);
}
__device__ __forceinline__ void make_bfrags(uint32_t (&bf)[4][2], uint32_t aw0, uint32_t aw1, int r) {
#pragma unroll
    for (int ks = 0; ks < 4; ks++) {
        bf[ks][0] = __shfl_sync(0xffffffffu, aw0, ks * 8 + r);
        bf[ks][1] = __shfl_sync(0xffffffffu, aw1, ks * 8 + r);
    }
}
__device__ __forceinline__ uint32_t gemv32(uint32_t s_w, uint32_t red, uint32_t fullbar, uint32_t emptybar,
                                           uint32_t aw0, uint32_t aw1, int tid) {
    const int vw = tid >> 5, lane = tid & 31, g = lane >> 2, t = lane & 3, mi = lane >> 3, r = lane & 7;
    uint32_t bf[4][2];
    make_bfrags(bf, aw0, aw1, r);
    if (vw <= 4) mbar_wait(fullbar);
    if (vw >= 4) mbar_wait(fullbar + 8);
    float cc[2][4] = {};
    const uint32_t abase = s_w + (vw * 64 + r + 8 * (mi >> 1)) * 64;
    const uint32_t sw = ((mi & 1) ^ (r >> 1)) << 4;
#pragma unroll
    for (int ks = 0; ks < 4; ks++) {
#pragma unroll
        for (int mt = 0; mt < 2; mt++) {
            uint32_t a[4];
            ldsm4t(a, abase + ks * 1024 + (sw ^ (mt * 32)));
            mma16816(cc[mt], a, bf[ks][0], bf[ks][1]);
        }
    }
    if (t == 0) { sts128f(red + vw * 256 + g * 16, cc[0]); sts128f(red + vw * 256 + 128 + g * 16, cc[1]); }
    __syncwarp();
    if (lane == 0) mbar_arrive(emptybar);
    bar_consumers();
    float s = 0.f;
    if (tid < 64) {
        const uint32_t ra = red + ((tid & 58) | ((tid & 1) << 2) | ((tid >> 2) & 1)) * 4;
#pragma unroll
        for (int w = 0; w < NCW; w++) s += ldsf(ra + w * 256);
    }
    return pack2(0.f, s);
}
__device__ __forceinline__ void publish_partials(unsigned* q, unsigned hm, const float (&cc)[4][4], unsigned tag) {
#pragma unroll
    for (int mt = 0; mt < 4; mt++)
        stg_pkt(q + mt * 4 * 2048 + ((hm >> (4 * mt)) & 1) * HALF, cc[mt][0], cc[mt][1], cc[mt][2], cc[mt][3], tag);
}
__device__ __forceinline__ void spin_cycles(unsigned n) {
    const unsigned c0 = clock();
    while ((unsigned)clock() - c0 < n) { }
}
__device__ __forceinline__ float reduce_unit(const unsigned* q, int lane, unsigned tag) {
    uint4 v[8];
#pragma unroll
    for (int i = 0; i < 8; i++) v[i] = ldg_pkt(q + i * 128);
    int it = 0;
    while (true) {
        unsigned bad = 0;
#pragma unroll
        for (int i = 0; i < 8; i += 2) bad |= (v[i].x ^ tag) | (v[i + 1].x ^ tag);
        if (!any_lane(bad & 7u) || ++it >= SPIN_LIMIT) break;
#pragma unroll
        for (int i = 0; i < 8; i++) ldg_pkt_if(v[i], q + i * 128, (v[i].x ^ tag) & 7u);
    }
    float s0 = 0.f, s1 = 0.f, s2 = 0.f, s3 = 0.f, u0 = 0.f, u1 = 0.f, u2 = 0.f, u3 = 0.f;
#pragma unroll
    for (int i = 0; i < 8; i += 2) {
        s0 += untagf(v[i].x); s1 += __uint_as_float(v[i].y); s2 += __uint_as_float(v[i].z); s3 += __uint_as_float(v[i].w);
        u0 += untagf(v[i + 1].x); u1 += __uint_as_float(v[i + 1].y); u2 += __uint_as_float(v[i + 1].z); u3 += __uint_as_float(v[i + 1].w);
    }
    s0 += u0; s1 += u1; s2 += u2; s3 += u3;
    __syncwarp();
    const bool h8 = lane & 2, bat = lane & 4;
    const float k0 = (h8 ? s2 : s0) + shx(h8 ? s0 : s2, 2);
    const float k1 = (h8 ? s3 : s1) + shx(h8 ? s1 : s3, 2);
    float k = (bat ? k1 : k0) + shx(bat ? k0 : k1, 4);
    k += shx(k, 8);
    k += shx(k, 16);
    return k;
}

__global__ void __launch_bounds__(NTHR, 1)
fused_block_kernel(const __grid_constant__ Maps maps, const __nv_bfloat16* __restrict__ xin,
                   const __nv_bfloat16* __restrict__ cin, const __nv_bfloat16* __restrict__ kcache,
                   __nv_bfloat16* __restrict__ out, unsigned* const scr) {
    extern __shared__ unsigned char smem_raw[];
    const int c = blockIdx.x;
    const int kvh = c >> 3, j = c & 7, bb = j & 1, sp = j >> 1;
    const int kvrow0 = (bb * 16 + kvh) * 32768 + 28672 + sp * 1024;
    if (EARLY_PF && threadIdx.x == 0)
        asm volatile("cp.async.bulk.prefetch.L2.global [%0], %1;" ::"l"((const char*)kcache + (size_t)kvrow0 * 256), "r"(EARLY_PF) : "memory");
    TS(threadIdx.x == 0, 0);
    const uint32_t sb = (smem_u32(smem_raw) + 1023u) & ~1023u;
    const int warp = threadIdx.x >> 5, lane = threadIdx.x & 31;
    const uint32_t s_full = sb + OFF_BAR, s_empty = s_full + N_IT * 8;

    if (warp == NCW) {
        uint32_t t0 = gtime32();
        const int first = (c < NMOD) ? 0 : 2;
        if (lane == 0) {
#pragma unroll
            for (int i = 0; i < 2; i++) mbar_init(s_full + (first + i) * 8, 1);
            asm volatile("fence.proxy.async.shared::cta;" ::: "memory");
#pragma unroll
            for (int i = 0; i < 2; i++) {
                const uint32_t bar = s_full + (first + i) * 8;
                mbar_expect_tx(bar, 18432);
                tma3d(sb + (first + i) * 18432, &maps.m[M_WMOD + (first >> 1)], c * 32, 0, i * 2, bar);
            }
            TS(true, 17);
        }
        __syncwarp();
        uint32_t w0[2], w1[2], w2[2];
#pragma unroll
        for (int h = 0; h < 2; h++) {
            const int i = lane + 32 * h;
            int off, map, dep = -1, x = 0, y = 0, z = 0, sz = 36, cum;
            if (i < IT_K) {
                off = i * 18432; map = M_WMOD + (i >> 1); x = c * 32; z = (i & 1) * 2; cum = 31104 + (i - 2) * 18432;
            } else if (i < IT_V) {
                const int k = i - IT_K;
                off = k_off(k); map = M_K; y = kvrow0 + k * 64; sz = 32; cum = 67968 + k * 16384;
                if (k == 8 && c < NMOD) dep = EM_WMOD;
                if (k == 10) dep = EM_WQ;
                if (k >= 12) dep = EM_K + k - 12;
            } else if (i < IT_WO) {
                const int k = i - IT_V;
                off = v_off(k); map = M_V; y = kvrow0 + k * 64; sz = 32; cum = 330112 + k * 16384;
                dep = EM_K + 3 + k + (k < 4);
            } else if (i < IT_GU) {
                const int k = i - IT_WO;
                off = k ? OFF_WO1 : OFF_WO0; map = M_WO; y = kvh * 256 + k * 128 + j * 16; dep = EM_V + 4 + 2 * k;
                cum = 592256 + k * 18432;
            } else if (i < IT_WD) {
                const int k = i - IT_GU;
                off = ((k & 1) ? OFF_U : OFF_G) + (k >> 1) * 18432; map = M_WG + (k & 1);
                x = (c * 36) & ~15; y = (k >> 1) * 192; dep = EM_V + 5 + ((off + 18431) >> 14);
                cum = 629120 + k * 13824;
            } else {
                const int k = i - IT_WD;
                off = OFF_D + k * DSTR; map = M_WD; y = c * 36; z = k * 3; sz = 27; dep = EM_V + 13 + k;
                cum = 712064 + k * 13824;
            }
            cum += EARLY_PF - min(max(cum - 67968, 0), EARLY_PF);
            const int stag = ((c * 37) & 127) * 128 - PACE_LEAD;
            int due = (int)((float)max(min(cum, 629120) + stag, 0) * (128.0f / PACE_GBS));
            if (i >= IT_GU) due += TAIL_GAP + (int)((float)(min(cum, 712064) - 629120) * (128.0f / PACE_TAIL));
            if (i >= IT_WD) due += (int)((float)(cum - 712064) * (128.0f / PACE_D));
            w0[h] = off | (map << 18) | ((dep + 1) << 22) | (z << 28);
            w1[h] = y | (sz << 24);
            w2[h] = x | (due << 13);
        }
        asm volatile("bar.sync 2, 384;" ::: "memory");
#pragma unroll 1
        for (int i = first + 2; i < N_IT; i++) {
            const bool hi = i >= 32;
            const uint32_t a = __shfl_sync(0xffffffffu, hi ? w0[1] : w0[0], i);
            const uint32_t b = __shfl_sync(0xffffffffu, hi ? w1[1] : w1[0], i);
            const uint32_t x = __shfl_sync(0xffffffffu, hi ? w2[1] : w2[0], i);
            if (lane == 0) {
                const int prev = i - ((i >= WIN_SWITCH) ? WIN_TAIL : WIN_MAIN);
                const int dep = (a >> 22) & 63;
                if (dep) mbar_wait(s_empty + (dep - 1) * 8);
                while (!((prev < first || mbar_test(s_full + prev * 8)) && gtime32() - t0 >= (x >> 13)) && !(OPEN_WIN && mbar_test(s_empty + EM_CH * 8))) { }
                if (i >= NOCATCH) { const uint32_t late = gtime32() - t0 - (x >> 13); if ((int)late > 0) t0 += late; }
                const uint32_t bar = s_full + i * 8;
                mbar_expect_tx(bar, (b >> 24) * 512);
                tma3d(sb + (a & 0x3ffff), &maps.m[(a >> 18) & 15], x & 0x1fff, b & 0xffffff, a >> 28, bar);
                TS(i == IT_WO, 1);
            }
            __syncwarp();
        }
        return;
    }

    const int g = lane >> 2, t = lane & 3, mi = lane >> 3, r = lane & 7;
    const int bat = g & 1;

    if (warp > NCW) {
        const bool first = warp == NCW + 1, active = first || c < 16;
        const int unit = first ? c : NCTA + c;
        const int rcol = (unit >> 2) * 16 + (unit & 3) * 2 + (lane & 1) + (lane & 2) * 4 + bat * DM;
        const unsigned ep = ldg_rlx1(scr + G_EPOCH);
        uint32_t xold = 0, ga = 0, gb = 0;
        if (active) xold = __ldg((const unsigned short*)xin + rcol);
        if (!first) asm volatile("bar.sync 2, 384;" ::: "memory");
        const unsigned tag = (ep + 1u) & 1u;
        unsigned side = 0;
        const int x1w = G_X1 + (unit >> 7) * 2048 + (unit & 127) * 8 + r + (lane & 8) * (HALF / 8) + (lane >> 4) * 4096;
        if (first) {
            unsigned* pr = scr + G_PROBE + c * 8;
            if (lane < 16) stg_rlx1(pr + r + (lane & 8) * (HALF / 8), 0u);
            __syncwarp();
            asm volatile("bar.arrive 2, 384;" ::: "memory");
            unsigned best0 = ~0u, best1 = ~0u, v = 0, cp = 0;
#pragma unroll 1
            for (int i = 0; i <= 2 * NPROBE; i++) {
                if (lane == 0) {
                    asm volatile("atom.relaxed.gpu.global.add.u32 %0, [%1], 1;" : "=r"(v) : "l"(pr + (i & 1) * HALF + (v >> 31)) : "memory");
                    const unsigned cn = clock(), d = cn - cp;
                    cp = cn;
                    if (i & 1) best0 = min(best0, d); else if (i) best1 = min(best1, d);
                    side = (best1 < best0) ^ (__popc(G_PROBE & 0x2C800) & 1);
                }
                if (i == 2 * NPROBE0) {
                    asm volatile("bar.sync 6, 64;" ::: "memory");
                    if (lane == 0) { sts32(sb + OFF_WMX + 116, side); mbar_arrive(s_empty + EM_SD * 8); }
                }
            }
            if (lane == 0) sts32(sb + OFF_WMX + 112, side);
            side = __shfl_sync(0xffffffffu, side, 0);
            mbar_wait(s_full + it_v(PH_V) * 8);
#pragma unroll 1
            for (int u = c; u < 144; u += NCTA) {
                unsigned* q = scr + G_PART + u * 2048 + near_half(G_PART + u * 2048, side) + lane * 4;
#pragma unroll
                for (int i = 0; i < 8; i++) stg_ph(q + i * 128);
#pragma unroll
                for (int i = 0; i < XREP; i += 2) stg_rlx1(scr + x1w + (u >> 7) * 2048 + i * 4096, 2u);
            }
            unsigned* o = scr + G_OP + kvh * 4096 + (j >> 2) * 2048 + (j & 3) * 256 + lane * 4;
            stg_ph(o); stg_ph(o + 128); stg_ph(o + HALF); stg_ph(o + HALF + 128);
            __threadfence();
            __syncwarp();
            if (lane < 8) stg_rlx1(scr + G_SIDE + c * 8 + lane, (side << 4) | tag);
            if (lane == 0) mbar_arrive(s_empty + EM_PH * 8);
        } else {
            asm volatile("bar.arrive 6, 64;" ::: "memory");
            if (TM_PF && lane < 8) asm volatile("prefetch.tensormap [%0];" ::"l"(&maps.m[lane]) : "memory");
            mbar_wait(s_empty + EM_PH * 8);
            side = __float_as_uint(ldsf(sb + OFF_WMX + 112));
        }
        if (active) {
            int it = 0;
            do {
                ga = ldg_rlx1(scr + dual_near(G_MOD, 2 * 1152 + unit * 8 + r, side));
                gb = ldg_rlx1(scr + dual_near(G_MOD, 5 * 1152 + unit * 8 + r, side));
            } while (any_lane(((ga ^ tag) | (gb ^ tag)) & 7u) && ++it < SPIN_LIMIT);
            ga >>= 16; gb >>= 16;
        }
        __syncwarp();
        if (first) {
            const int ow = G_OP + kvh * 4096 + (g >> 2) * 2048;
            const unsigned* q = scr + ow + near_half(ow, side) + (g & 3) * 256 + j * 32 + t * 8;
            mbar_wait(s_full + it_v(15) * 8);
            uint4 lo, hi;
            int it = 0;
            do { lo = ldg_pkt(q); hi = ldg_pkt(q + 4); } while (any_lane(((lo.x ^ tag) | (hi.x ^ tag)) & 7u) && ++it < SPIN_LIMIT);
            float o[8] = {untagf(lo.x), __uint_as_float(lo.y), __uint_as_float(lo.z), __uint_as_float(lo.w),
                          untagf(hi.x), __uint_as_float(hi.y), __uint_as_float(hi.z), __uint_as_float(hi.w)};
            __syncwarp();
#pragma unroll
            for (int sft = 8; sft <= 16; sft <<= 1) {
#pragma unroll
                for (int i = 0; i < 8; i++) o[i] += shx(o[i], sft);
            }
            if (lane < 8)
                sts128(sb + OFF_FR + lane * 48, pack2(o[0], o[4]), pack2(o[2], o[6]), pack2(o[1], o[5]), pack2(o[3], o[7]));
            TS(lane == 0, 10);
        }
        asm volatile("bar.sync 3, 352;" ::: "memory");
        const unsigned* q = scr + G_PART + unit * 2048 + near_half(G_PART + unit * 2048, side) + lane * 4;
        if (DELAY_B) spin_cycles(DELAY_B);
        if (active) {
            const float k = reduce_unit(q, lane, tag);
            xold = badd2(xold, bmul2(ga, pack2(k, 0.f))) & 0xffffu;
#pragma unroll
            for (int i = 0; i < XREP; i += 2) stg_rlx1(scr + x1w + i * 4096, (xold << 16) | tag);
            TS(first && lane == 0, 12);
            TS(!first && lane == 0, 18);
        }
        if (first && lane == 0) mbar_arrive(s_empty + EM_X1 * 8);
        asm volatile("bar.sync 5, 352;" ::: "memory");
        if (active) {
            if (DELAY_D) spin_cycles(DELAY_D);
            const float k = reduce_unit(q, lane, tag | 4u);
            xold = badd2(xold, bmul2(gb, pack2(k, 0.f)));
            if (lane < 8) ((unsigned short*)out)[rcol] = (unsigned short)xold;
            if (c == 0 && first && lane == 0) stg_rlx1(scr + G_EPOCH, ep + 1u);
            TS(first && lane == 0, 16);
        }
        return;
    }

    const int vw = warp, tid = threadIdx.x;
    const int vecw = tid * 4 - (lane & 7) * 4 + t * 8 + bat * 4;
    unsigned* const ppart = scr + G_PART + (vw * 16 + (g >> 1)) * 2048 + c * 8 + bat * 4;
    const unsigned* const pside = scr + G_SIDE + ((vw * 16 + (lane & 15)) & 127) * 8;
    const int qword = dual(G_Q, bat * 4096 + c * 32 + (tid >> 3) * 4 + t), mword = dual(G_MOD, c * 64 + (tid & 63));
    const uint32_t one2 = 0x3f803f80u;

    const unsigned ep = ldg_rlx1(scr + G_EPOCH);
    if (tid < 64) {
        if (c < NMOD) { stg_rlx1(scr + mword, 2u); stg_rlx1(scr + mword + HALF, 2u); }
        stg_rlx1(scr + qword, 2u); stg_rlx1(scr + qword + HALF, 2u);
    }
    uint32_t xw0, xw1, aw0, aw1;
    {
        const int col0 = bat * DM + (vw * 4 + mi) * 16 + 2 * t;
        const uint32_t cw0 = __ldg((const unsigned*)(cin + col0)), cw1 = __ldg((const unsigned*)(cin + col0 + 8));
        xw0 = __ldg((const unsigned*)(xin + col0)); xw1 = __ldg((const unsigned*)(xin + col0 + 8));
        if (tid < 8) sts64(sb + OFF_FR + tid * 48 + 16, 0u, 0u);
        if (lane == 0) {
            const int lo = (c < NMOD) ? 2 : 4;
#pragma unroll 1
            for (int i = vw; i < N_IT + N_EM; i += NCW) {
                const int e = i - N_IT;
                if (i >= lo) mbar_init(s_full + i * 8, (e < 0 || e >= EM_PH) ? 1 : (e < EM_K ? NCW : (e < EM_V ? 4 : 8)));
            }
            asm volatile("fence.proxy.async.shared::cta;" ::: "memory");
        }
        __syncwarp();
        asm volatile("bar.sync 2, 384;" ::: "memory");
        float cv[4] = {bflo(cw0), bfhi(cw0), bflo(cw1), bfhi(cw1)};
#pragma unroll
        for (int i = 0; i < 4; i++) cv[i] = cv[i] * rcp(1.0f + ex2(-1.4426950408889634f * cv[i]));
        aw0 = pack2(cv[0], cv[1]); aw1 = pack2(cv[2], cv[3]);
    }
    const unsigned tag = (ep + 1u) & 1u;
    const uint32_t st1 = sb + OFF_STAT + bat * 80, st2 = st1 + 160;
    ln_stage1(xw0, xw1, st1, vw, lane);

    if (c < NMOD) {
        const uint32_t m = gemv32(sb + OFF_WMOD, sb + OFF_RED, s_full + IT_WMOD * 8, s_empty + EM_WMOD * 8, aw0, aw1, tid);
        if (tid < 64) { stg_rlx1(scr + mword, m | tag); stg_rlx1(scr + mword + HALF, m | tag); }
    } else {
        bar_consumers();
    }
    TS(tid == 0, 4);
    mbar_wait(s_empty + EM_SD * 8);
    unsigned side = __float_as_uint(ldsf(sb + OFF_WMX + 116));
    {
        uint32_t y0, y1;
        ln_stage2(ln_load(st1), xw0, xw1, y0, y1);
        uint4 a, b;
        int it = 0;
        const unsigned *pa = scr + dual_near(G_MOD, vecw, side), *pb = scr + dual_near(G_MOD, 1152 + vecw, side);
        do { a = ldg_rlx4(pa); b = ldg_rlx4(pb); }
        while (any_lane((bad4(a, tag) | bad4(b, tag)) & 7u) && ++it < SPIN_LIMIT);
        __syncwarp();
        aw0 = badd2(bmul2(y0, badd2(one2, hi2(b.x, b.y))), hi2(a.x, a.y));
        aw1 = badd2(bmul2(y1, badd2(one2, hi2(b.z, b.w))), hi2(a.z, a.w));
        TS(tid == 0, 5);
        const uint32_t q = gemv32(sb + OFF_WQ, sb + OFF_RED + 2304, s_full + IT_WQ * 8, s_empty + EM_WQ * 8, aw0, aw1, tid);
        if (tid < 64) {
            stg_rlx1(scr + qword, q | tag); stg_rlx1(scr + qword + HALF, q | tag);
            uint4 v;
            int it = 0;
            const unsigned* pq = scr + dual_near(G_Q, bb * 4096 + kvh * 256 + tid * 4, side);
            do { v = ldg_rlx4(pq); } while (any_lane(bad4(v, tag) & 7u) && ++it < SPIN_LIMIT);
            sts64(sb + OFF_QS + (vw * 4 + t) * 80 + g * 8, hi2(v.x, v.y), hi2(v.z, v.w));
        }
        bar_consumers();
        TS(tid == 0, 6);
    }
    uint32_t sc0, sc1, sh0, sh1;
    {
        uint4 d, e;
        unsigned bad;
        int it = 0;
        do {
            d = ldg_rlx4(scr + dual_near(G_MOD, 3 * 1152 + vecw, side)); e = ldg_rlx4(scr + dual_near(G_MOD, 4 * 1152 + vecw, side));
            bad = bad4(d, tag) | bad4(e, tag);
        } while (any_lane(bad & 7u) && ++it < SPIN_LIMIT);
        __syncwarp();
        sh0 = hi2(d.x, d.y); sh1 = hi2(d.z, d.w);
        sc0 = badd2(one2, hi2(e.x, e.y)); sc1 = badd2(one2, hi2(e.z, e.w));
    }
    if (vw < 8) {
        uint4 qf[4];
#pragma unroll
        for (int i = 0; i < 4; i++) qf[i] = lds128(sb + OFF_QS + r * 80 + i * 16);
        const int mt = vw & 3;
        const uint32_t rowoff = (mt * 16 + r + 8 * (mi & 1)) * 128;
        const uint32_t sw = ((mi >> 1) ^ r) << 4;
        uint32_t mx = 0xff80ff80u;
#pragma unroll 1
        for (int i = (vw >> 2); i < 16; i += 2) {
            mbar_wait(s_full + (IT_K + i) * 8);
            const uint32_t base = sb + k_off(i) + rowoff;
            float c0[4] = {}, c1[4] = {};
            uint32_t a[4];
            ldsm4(a, base + sw);               mma16816(c0, a, qf[0].x, qf[0].y);
            ldsm4(a, base + 8192 + sw);        mma16816(c1, a, qf[2].x, qf[2].y);
            ldsm4(a, base + (sw ^ 32));        mma16816(c0, a, qf[0].z, qf[0].w);
            ldsm4(a, base + 8192 + (sw ^ 32)); mma16816(c1, a, qf[2].z, qf[2].w);
            ldsm4(a, base + (sw ^ 64));        mma16816(c0, a, qf[1].x, qf[1].y);
            ldsm4(a, base + 8192 + (sw ^ 64)); mma16816(c1, a, qf[3].x, qf[3].y);
            ldsm4(a, base + (sw ^ 96));        mma16816(c0, a, qf[1].z, qf[1].w);
            ldsm4(a, base + 8192 + (sw ^ 96)); mma16816(c1, a, qf[3].z, qf[3].w);
            __syncwarp();
            if (lane == 0) mbar_arrive(s_empty + (EM_K + i) * 8);
            const float scl = 0.08838834764831845f;
            uint32_t u0 = pack2(c0[0] + c1[0], c0[1] + c1[1]), u1 = pack2(c0[2] + c1[2], c0[3] + c1[3]);
            u0 = pack2(bflo(u0) * scl, bfhi(u0) * scl); u1 = pack2(bflo(u1) * scl, bfhi(u1) * scl);
            mx = bmax2(mx, bmax2(u0, u1));
            if (t == 0) {
                const uint32_t pa = sb + OFF_S + (i * 64 + 16 * (g >> 1) + 4 * mt + bat) * 4;
                sts32(pa, u0); sts32(pa + 8, u1);
            }
            if (i == PH_K && tid < 4) stg_ph(scr + G_ML + c * 8 + (tid & 1) * 4 + (tid & 2) * (HALF / 2));
        }
#pragma unroll
        for (int o = 4; o <= 16; o <<= 1) mx = bmax2(mx, __shfl_xor_sync(0xffffffffu, mx, o));
        if (lane == 0) sts32(sb + OFF_WMX + vw * 4, mx);
    }
    bar_consumers();
    TS(tid == 0, 7);
    {
        const float L2E = 1.4426950408889634f;
        uint4 sv = make_uint4(0, 0, 0, 0);
        float m0 = 0.f, m1 = 0.f;
        if (vw < 8) {
            uint4 ma = lds128(sb + OFF_WMX), mb = lds128(sb + OFF_WMX + 16);
            const uint32_t mx = bmax2(bmax2(bmax2(ma.x, ma.y), bmax2(ma.z, ma.w)), bmax2(bmax2(mb.x, mb.y), bmax2(mb.z, mb.w)));
            m0 = bflo(mx); m1 = bfhi(mx);
            sv = lds128(sb + OFF_S + tid * 16);
            float e0 = (ex2((bflo(sv.x) - m0) * L2E) + ex2((bflo(sv.y) - m0) * L2E)) + (ex2((bflo(sv.z) - m0) * L2E) + ex2((bflo(sv.w) - m0) * L2E));
            float e1 = (ex2((bfhi(sv.x) - m1) * L2E) + ex2((bfhi(sv.y) - m1) * L2E)) + (ex2((bfhi(sv.z) - m1) * L2E) + ex2((bfhi(sv.w) - m1) * L2E));
#pragma unroll
            for (int o = 16; o > 0; o >>= 1) { e0 += shx(e0, o); e1 += shx(e1, o); }
            if (lane == 0) sts64(sb + OFF_WMX + 32 + vw * 8, __float_as_uint(e0), __float_as_uint(e1));
        }
        bar_consumers();
        if (vw == 0) {
            float l0 = 0.f, l1 = 0.f;
#pragma unroll
            for (int w = 0; w < 4; w++) {
                uint4 s = lds128(sb + OFF_WMX + 32 + w * 16);
                l0 += __uint_as_float(s.x) + __uint_as_float(s.z); l1 += __uint_as_float(s.y) + __uint_as_float(s.w);
            }
            if (tid < 4) stg_pkt(scr + G_ML + c * 8 + (tid & 1) * 4 + (tid & 2) * (HALF / 2), m0, l0, m1, l1, tag);
            {
                const bool rd = lane < 4 && lane != sp;
                uint4 v = make_uint4(rd ? 2u : tag, 0, 0, 0);
                int it = 0;
                do { ldg_pkt_if(v, scr + G_ML + near_half(G_ML, side) + (kvh * 8 + (lane & 3) * 2 + bb) * 8, (v.x ^ tag) & 7u); }
                while (any_lane((v.x ^ tag) & 7u) && ++it < SPIN_LIMIT);
                if (rd) { m0 = untagf(v.x); l0 = __uint_as_float(v.y); m1 = __uint_as_float(v.z); l1 = __uint_as_float(v.w); }
            }
            float g0 = fmaxf(m0, shx(m0, 1)), g1 = fmaxf(m1, shx(m1, 1));
            g0 = fmaxf(g0, shx(g0, 2)); g1 = fmaxf(g1, shx(g1, 2));
            l0 *= ex2((m0 - g0) * L2E); l1 *= ex2((m1 - g1) * L2E);
            l0 += shx(l0, 1); l1 += shx(l1, 1);
            l0 += shx(l0, 2); l1 += shx(l1, 2);
            if (lane == 0)
                sts128(sb + OFF_WMX + 96, __float_as_uint(g0), __float_as_uint(g1), __float_as_uint(1.0f / l0), __float_as_uint(1.0f / l1));
        }
        bar_consumers();
        if (vw < 8) {
            const uint4 gs = lds128(sb + OFF_WMX + 96);
            const float g0 = __uint_as_float(gs.x), g1 = __uint_as_float(gs.y), i0 = __uint_as_float(gs.z), i1 = __uint_as_float(gs.w);
            const uint32_t a0 = pack2(ex2((bflo(sv.x) - g0) * L2E) * i0, ex2((bflo(sv.y) - g0) * L2E) * i0);
            const uint32_t a1 = pack2(ex2((bflo(sv.z) - g0) * L2E) * i0, ex2((bflo(sv.w) - g0) * L2E) * i0);
            const uint32_t b0 = pack2(ex2((bfhi(sv.x) - g1) * L2E) * i1, ex2((bfhi(sv.y) - g1) * L2E) * i1);
            const uint32_t b1 = pack2(ex2((bfhi(sv.z) - g1) * L2E) * i1, ex2((bfhi(sv.w) - g1) * L2E) * i1);
            sts64(sb + OFF_P + tid * 8, a0, a1); sts64(sb + OFF_P + PSTR + tid * 8, b0, b1);
        }
        bar_consumers();
        TS(tid == 0, 8);
    }
    const uint32_t rin = vw * 2048 + (r + 8 * (mi >> 1)) * 128;
    const uint32_t rsw = ((mi & 1) ^ r) << 4;
    uint32_t ra[2][4][4];
    unsigned sidew = 2u;
    if (vw < 8) {
        float c0[4] = {}, c1[4] = {};
        const uint32_t vo = (vw >> 2) * 8192 + (r + 8 * (mi >> 1)) * 128 + ((((2 * vw + (mi & 1)) & 7) ^ r) << 4);
        const uint32_t pa = sb + OFF_P + bat * PSTR + t * 32;
#pragma unroll 1
        for (int i = 0; i < 16; i++) {
            uint4 pb0 = lds128(pa + i * 128), pb1 = lds128(pa + i * 128 + 16);
            mbar_wait(s_full + it_v(i) * 8);
            const uint32_t base = sb + v_off(i) + vo;
            uint32_t a0[4], a1[4], a2[4], a3[4];
            ldsm4t(a0, base); ldsm4t(a1, base + 2048); ldsm4t(a2, base + 4096); ldsm4t(a3, base + 6144);
            mma16816(c0, a0, pb0.x, pb0.y);
            mma16816(c1, a1, pb0.z, pb0.w);
            mma16816(c0, a2, pb1.x, pb1.y);
            mma16816(c1, a3, pb1.z, pb1.w);
            __syncwarp();
            if (lane == 0) mbar_arrive(s_empty + (EM_V + i) * 8);
            if (i == SIDE_V) { mbar_wait(s_empty + EM_PH * 8); sidew = ldg_rlx1(pside); }
        }
        if (t < 2)
            stg_pkt(scr + G_OP + kvh * 4096 + (j >> 2) * 2048 + t * HALF + (j & 3) * 256 + vw * 32 + g * 4,
                    c0[0] + c1[0], c0[1] + c1[1], c0[2] + c1[2], c0[3] + c1[3], tag);
        TS(tid == 0, 9);
    } else {
        mbar_wait(s_full + it_v(SIDE_V) * 8);
        mbar_wait(s_empty + EM_PH * 8);
    }
    unsigned hm;
    {
        int it = 0;
        while (any_lane((sidew ^ tag) & 7u) && ++it < SPIN_LIMIT) sidew = ldg_rlx1(pside);
        __syncwarp();
        const int uw = G_PART + (vw * 16 + (lane & 15)) * 2048;
        hm = __ballot_sync(0xffffffffu, near_half(uw, sidew >> 4)) >> (g >> 1);
    }
    side = __float_as_uint(ldsf(sb + OFF_WMX + 112));
    {
        mbar_wait(s_full + IT_WO * 8);
#pragma unroll
        for (int mt = 0; mt < 4; mt++) ldsm4t(ra[0][mt], sb + OFF_WO0 + rin + (rsw ^ (mt * 32)));
        mbar_wait(s_full + (IT_WO + 1) * 8);
#pragma unroll
        for (int mt = 0; mt < 4; mt++) ldsm4t(ra[1][mt], sb + OFF_WO1 + rin + (rsw ^ (mt * 32)));
        asm volatile("bar.sync 3, 352;" ::: "memory");
        const uint4 fr = lds128(sb + OFF_FR + r * 48);
        float cc[4][4] = {};
#pragma unroll
        for (int mt = 0; mt < 4; mt++) mma16816(cc[mt], ra[0][mt], fr.x, fr.y);
#pragma unroll
        for (int mt = 0; mt < 4; mt++) mma16816(cc[mt], ra[1][mt], fr.z, fr.w);
        if (t == 0) publish_partials(ppart, hm, cc, tag);
        __syncwarp();
        TS(tid == 0, 11);
    }
    uint32_t ag[4][5][4];
    const uint32_t gub = s_full + (IT_GU + 2 * (vw / 3)) * 8;
    const uint32_t gbase = sb + ((mi & 1) ? OFF_U : OFF_G) + (vw * 64 + r + 8 * (mi >> 1)) * 96 + ((c * 36) & 8) * 2;
    bool gpre;
    while (true) {
        gpre = __all_sync(0xffffffffu, mbar_test(gub) && mbar_test(gub + 8));
        if (gpre || __all_sync(0xffffffffu, mbar_test(s_empty + EM_X1 * 8))) break;
    }
    if (gpre) {
#pragma unroll
        for (int ks = 0; ks < 4; ks++)
#pragma unroll
            for (int q = 0; q < 5; q++) ldsm4t(ag[ks][q], gbase + ks * 1536 + q * 16);
        mbar_wait(s_empty + EM_X1 * 8);
    }
    bool dpre;
    const uint32_t dbar = s_full + (IT_WD + vw / 3) * 8;
    const uint32_t dgrp = sb + OFF_D + (vw / 3) * DSTR + (vw % 3) * 4608;
    const uint32_t dbase = dgrp + (r + 8 * (mi >> 1)) * 128, dsw = ((mi & 1) ^ ((r + 4 * (vw % 3)) & 7)) << 4;
    {
        uint4 v;
        int it = 0;
        const int xw = G_X1 + (vw >> 3) * 2048 + (c & (XREP - 1)) * 4096;
        const unsigned* px = scr + xw + near_half(xw, side) + (vecw & 1023);
        while (true) {
            v = ldg_rlx4(px);
            const bool more = any_lane(bad4(v, tag) & 7u);
            if (!more || ++it >= SPIN_LIMIT) break;
        }
        xw0 = hi2(v.x, v.y); xw1 = hi2(v.z, v.w);
        __syncwarp();
        ln_stage1(xw0, xw1, st2, vw, lane);
        dpre = __all_sync(0xffffffffu, mbar_test(dbar));
        bar_consumers();
        if (tid == 0) mbar_arrive(s_empty + EM_CH * 8);
        TS(tid == 0, 13);
        const LnStat ls = ln_load(st2);
        if (dpre) {
#pragma unroll
            for (int mt = 0; mt < 4; mt++) ldsm4t(ra[0][mt], dbase + (dsw ^ (mt * 32)));
#pragma unroll
            for (int mt = 0; mt < 4; mt++) ldsm4t(ra[1][mt], dbase + 2048 + (dsw ^ (mt * 32)));
        }
        uint32_t y0, y1;
        ln_stage2(ls, xw0, xw1, y0, y1);
        aw0 = badd2(bmul2(y0, sc0), sh0); aw1 = badd2(bmul2(y1, sc1), sh1);
        uint32_t bf[4][2];
        make_bfrags(bf, aw0, aw1, r);
        if (!gpre) {
            mbar_wait(gub); mbar_wait(gub + 8);
#pragma unroll
            for (int ks = 0; ks < 4; ks++)
#pragma unroll
                for (int q = 0; q < 5; q++) ldsm4t(ag[ks][q], gbase + ks * 1536 + q * 16);
        }
        float cc[5][4] = {};
#pragma unroll
        for (int ks = 0; ks < 4; ks++)
#pragma unroll
            for (int q = 0; q < 5; q++) mma16816(cc[q], ag[ks][q], bf[ks][0], bf[ks][1]);
        if (t == 0) {
#pragma unroll
            for (int q = 0; q < 5; q++) sts128f(sb + OFF_RED + vw * 640 + q * 128 + g * 16, cc[q]);
        }
        bar_consumers();
        TS(tid == 0, 14);
        if (tid < 160) {
            float sv[NCW];
#pragma unroll
            for (int w = 0; w < NCW; w++) sv[w] = ldsf(sb + OFF_RED + w * 640 + tid * 4);
            const float s = ((sv[0] + sv[1]) + (sv[2] + sv[3])) + ((sv[4] + sv[5]) + (sv[6] + sv[7])) + sv[8];
            const uint32_t gu = pack2(s, __shfl_down_sync(0xffffffffu, s, 2));
            const float gt = bflo(gu);
            const uint32_t hh = pack2(((gt > 0.f) ? gt : gt * 0.0f) * bfhi(gu), 0.f);
            const int rr = (tid >> 2) - (c & 1) * 4;
            if ((tid & 2) == 0 && rr >= 0 && rr < 36)
                sts16(sb + OFF_FR + ((tid & 1) * 4 + ((rr & 7) >> 1)) * 48 + (rr >> 3) * 4 + (rr & 1) * 2, hh);
        }
    }
    {
        uint32_t a2[4][4];
        const uint32_t b2 = dgrp + (32 + (r & 3)) * 128, sw2 = ((mi & 1) ^ (((r & 3) + 4 * (vw % 3)) & 7)) << 4;
        if (dpre) {
#pragma unroll
            for (int mt = 0; mt < 4; mt++) ldsm4t(a2[mt], b2 + (sw2 ^ (mt * 32)));
        }
        bar_consumers();
        const uint4 fr = lds128(sb + OFF_FR + r * 48);
        const uint2 f2 = lds64(sb + OFF_FR + r * 48 + 16);
        if (!dpre) {
            mbar_wait(dbar);
#pragma unroll
            for (int mt = 0; mt < 4; mt++) ldsm4t(ra[0][mt], dbase + (dsw ^ (mt * 32)));
#pragma unroll
            for (int mt = 0; mt < 4; mt++) ldsm4t(ra[1][mt], dbase + 2048 + (dsw ^ (mt * 32)));
#pragma unroll
            for (int mt = 0; mt < 4; mt++) ldsm4t(a2[mt], b2 + (sw2 ^ (mt * 32)));
        }
        float cc[4][4] = {};
#pragma unroll
        for (int mt = 0; mt < 4; mt++) mma16816(cc[mt], ra[0][mt], fr.x, fr.y);
#pragma unroll
        for (int mt = 0; mt < 4; mt++) mma16816(cc[mt], ra[1][mt], fr.z, fr.w);
#pragma unroll
        for (int mt = 0; mt < 4; mt++) mma16816(cc[mt], a2[mt], f2.x, f2.y);
        if (t == 0) publish_partials(ppart, hm, cc, tag | 4u);
        __syncwarp();
        asm volatile("bar.arrive 5, 352;" ::: "memory");
        TS(tid == 256, 15);
    }
}

typedef CUresult (*EncodeFn)(CUtensorMap*, CUtensorMapDataType, cuuint32_t, void*, const cuuint64_t*, const cuuint64_t*,
                             const cuuint32_t*, const cuuint32_t*, CUtensorMapInterleave, CUtensorMapSwizzle,
                             CUtensorMapL2promotion, CUtensorMapFloatOOBfill);

void make_map(EncodeFn enc, CUtensorMap* m, const void* p, cuuint64_t d0, cuuint64_t d1, cuuint64_t d2,
              cuuint64_t s1, cuuint64_t s2, cuuint32_t b0, cuuint32_t b1, cuuint32_t b2, CUtensorMapSwizzle sw,
              CUtensorMapL2promotion pr = CU_TENSOR_MAP_L2_PROMOTION_L2_128B) {
    cuuint64_t dims[3] = {d0, d1, d2};
    cuuint64_t str[2] = {s1, s2};
    cuuint32_t box[3] = {b0, b1, b2};
    cuuint32_t es[3] = {1, 1, 1};
    enc(m, CU_TENSOR_MAP_DATA_TYPE_BFLOAT16, 3, const_cast<void*>(p), dims, str, box, es,
        CU_TENSOR_MAP_INTERLEAVE_NONE, sw, pr, CU_TENSOR_MAP_FLOAT_OOB_FILL_NONE);
}

}

extern "C" void kernel_launch(void* const* d_in, const int* in_sizes, int n_in, void* d_out, int out_size) {
    (void)in_sizes; (void)n_in; (void)out_size;
    void* fn = nullptr;
    cudaDriverEntryPointQueryResult qr;
    cudaGetDriverEntryPoint("cuTensorMapEncodeTiled", &fn, cudaEnableDefault, &qr);
    EncodeFn enc = (EncodeFn)fn;
    cudaFuncSetAttribute(fused_block_kernel, cudaFuncAttributeMaxDynamicSharedMemorySize, SMEM_BYTES);

    const void *x = d_in[0], *kc = d_in[1], *vc = d_in[2], *wq = d_in[3], *wo = d_in[4];
    const void *wg = d_in[6], *wu = d_in[7], *wd = d_in[8], *cc = d_in[9], *wmod = d_in[10];
    const CUtensorMapSwizzle S128 = CU_TENSOR_MAP_SWIZZLE_128B, S64 = CU_TENSOR_MAP_SWIZZLE_64B, S0 = CU_TENSOR_MAP_SWIZZLE_NONE;
    void* raw = nullptr;
    cudaGetSymbolAddress(&raw, g_raw);
    unsigned* scr = (unsigned*)(((uintptr_t)raw + 0x1fffff) & ~(uintptr_t)0x1fffff);
    Maps m;
    make_map(enc, &m.m[M_K], kc, 64, 32ull * 32768, 2, 256, 128, 64, 64, 2, S128, CU_TENSOR_MAP_L2_PROMOTION_L2_256B);
    make_map(enc, &m.m[M_V], vc, 64, 32ull * 32768, 2, 256, 128, 64, 64, 2, S128, CU_TENSOR_MAP_L2_PROMOTION_L2_256B);
    make_map(enc, &m.m[M_WMOD], wmod, 3456, 144, 4, 3456 * 2, 3456 * 2 * 144, 32, 144, 2, S64);
    make_map(enc, &m.m[M_WQ], wq, 4096, 144, 4, 4096 * 2, 4096 * 2 * 144, 32, 144, 2, S64);
    make_map(enc, &m.m[M_WG], wg, 4608, 576, 1, 4608 * 2, 4608 * 2 * 576, 48, 192, 1, S0);
    make_map(enc, &m.m[M_WU], wu, 4608, 576, 1, 4608 * 2, 4608 * 2 * 576, 48, 192, 1, S0);
    make_map(enc, &m.m[M_WO], wo, 64, 4096, 9, 1152, 128, 64, 16, 9, S128);
    make_map(enc, &m.m[M_WD], wd, 64, 4608, 9, 1152, 128, 64, 36, 3, S128);
    fused_block_kernel<<<NCTA, NTHR, SMEM_BYTES>>>(m, (const __nv_bfloat16*)x, (const __nv_bfloat16*)cc,
                                                   (const __nv_bfloat16*)kc, (__nv_bfloat16*)d_out, scr);
}
```

```cpp
#include <cuda_runtime.h>
#include <cuda.h>
#include <cuda_bf16.h>
#include <stdint.h>

namespace {

constexpr int DM = 576;
constexpr int NCTA = 128;
constexpr int NCW = 9;
constexpr int NTHR = (NCW + 3) * 32;
constexpr int NMOD = 108;

#define WIN_MAIN 4
#define WIN_TAIL 3
#define PACE_GBS 3100
#define PACE_LEAD 28672
#define PACE_TAIL 2700
#define PACE_D 3300
#define TAIL_GAP 250
#define DELAY_B 300
#define NOCATCH 99
#define WIN_SWITCH 38
#define OPEN_WIN 1
#define DELAY_D 300
#define EARLY_PF 8192
#define TM_PF 1
#define XREP 2
#define PH_V 7
#define SIDE_V 11
#define NPROBE 10
#define NPROBE0 3
#define PH_K 8

#define TUNE_PARAM
#define TUNE_ARG
constexpr int IT_WMOD = 0, IT_WQ = 2, IT_K = 4, IT_V = 20, IT_WO = 36, IT_GU = 38, IT_WD = 44, N_IT = 47;
__device__ __forceinline__ constexpr int it_v(int k) { return IT_V + k; }
constexpr int EM_WMOD = 0, EM_WQ = 1, EM_K = 2, EM_V = 18, EM_PH = 34, EM_X1 = 35, EM_CH = 36, EM_SD = 37, N_EM = 38;

constexpr int RING = 13 * 16384;
constexpr int OFF_WMOD = 0, OFF_WQ = 36864, OFF_K0 = 73728;
constexpr int OFF_WO0 = 180224, OFF_WO1 = 0, OFF_G = 18432, OFF_U = 73728;
constexpr int OFF_D = 129024, DSTR = 14336;
constexpr int PSTR = 2064;
constexpr int OFF_P = RING;
constexpr int OFF_S = OFF_P + 4160;
constexpr int OFF_RED = OFF_S + 4096;
constexpr int OFF_QS = OFF_RED + 5760;
constexpr int OFF_FR = OFF_QS + 640;
constexpr int OFF_STAT = OFF_FR + 384;
constexpr int OFF_WMX = OFF_STAT + 320;
constexpr int OFF_BAR = OFF_WMX + 128;
constexpr int SMEM_USED = OFF_BAR + (N_IT + N_EM) * 8;
constexpr int SMEM_BYTES = SMEM_USED + 1024;
static_assert(SMEM_BYTES <= 232448, "smem");

struct Maps { CUtensorMap m[8]; };
enum { M_K, M_V, M_WMOD, M_WQ, M_WG, M_WU, M_WO, M_WD };

constexpr int HALF = 1024;
constexpr int G_PART = 0;
constexpr int G_OP = G_PART + 144 * 2048;
constexpr int G_X1 = G_OP + 16 * 4096;
constexpr int G_PROBE = G_X1 + XREP * 4096;
constexpr int G_SIDE = G_PROBE + 2048;
constexpr int G_EPOCH = G_SIDE + 1024;
constexpr int G_MOD = G_EPOCH + 1024;
constexpr int G_Q = G_MOD + 7 * 2048;
constexpr int G_ML = G_Q + 8 * 2048;
constexpr int G_WORDS = G_ML + 2048;
static_assert(G_MOD % 2048 == 0 && G_OP % 2048 == 0 && G_X1 % 2048 == 0 && G_PROBE % 2048 == 0, "halves");
static_assert(G_WORDS * 4 <= (2 << 20), "scratch must fit one 2 MB page");
__device__ __align__(128) unsigned g_raw[(2 << 20) / 4 + G_WORDS + 8192];
__device__ __forceinline__ int near_half(int w, unsigned side) { return ((__popc(w & 0x2C800) ^ side) & 1) << 10; }
__device__ __forceinline__ int dual(int base, int i) { return base + i + (i & ~1023); }
__device__ __forceinline__ int dual_near(int base, int i, unsigned side) { const int w = dual(base, i); return w + near_half(w, side); }
#define g_ts ((unsigned long long*)(scr + G_WORDS))

constexpr int SPIN_LIMIT = 1 << 20;

__device__ __forceinline__ uint32_t smem_u32(const void* p) { return (uint32_t)__cvta_generic_to_shared(p); }
__device__ __forceinline__ void mbar_init(uint32_t bar, int cnt) {
    asm volatile("mbarrier.init.shared::cta.b64 [%0], %1;" ::"r"(bar), "r"(cnt) : "memory");
}
__device__ __forceinline__ void mbar_expect_tx(uint32_t bar, uint32_t bytes) {
    asm volatile("mbarrier.arrive.expect_tx.shared::cta.b64 _, [%0], %1;" ::"r"(bar), "r"(bytes) : "memory");
}
__device__ __forceinline__ void mbar_arrive(uint32_t bar) {
    asm volatile("mbarrier.arrive.shared::cta.b64 _, [%0];" ::"r"(bar) : "memory");
}
__device__ __forceinline__ void mbar_wait(uint32_t bar) {
    asm volatile("{\n.reg .pred p;\nW_%=:\nmbarrier.try_wait.parity.shared::cta.b64 p, [%0], 0;\n@!p bra W_%=;\n}"
                 ::"r"(bar) : "memory");
}
__device__ __forceinline__ bool mbar_test(uint32_t bar) {
    uint32_t ok;
    asm volatile("{\n.reg .pred p;\nmbarrier.test_wait.parity.shared::cta.b64 p, [%1], 0;\nselp.u32 %0, 1, 0, p;\n}"
                 : "=r"(ok) : "r"(bar) : "memory");
    return ok;
}
__device__ __forceinline__ uint32_t gtime32() { uint32_t t; asm volatile("mov.u32 %0, %%globaltimer_lo;" : "=r"(t)); return t; }
__device__ __forceinline__ void tma3d(uint32_t dst, const CUtensorMap* m, int x, int y, int z, uint32_t bar) {
    asm volatile("cp.async.bulk.tensor.3d.shared::cluster.global.mbarrier::complete_tx::bytes [%0], [%1, {%3, %4, %5}], [%2];"
                 ::"r"(dst), "l"(m), "r"(bar), "r"(x), "r"(y), "r"(z) : "memory");
}
__device__ __forceinline__ void bar_consumers() { asm volatile("bar.sync 1, 288;" ::: "memory"); }

__device__ __forceinline__ void ldsm4(uint32_t (&a)[4], uint32_t addr) {
    asm volatile("ldmatrix.sync.aligned.m8n8.x4.shared.b16 {%0,%1,%2,%3}, [%4];"
                 : "=r"(a[0]), "=r"(a[1]), "=r"(a[2]), "=r"(a[3]) : "r"(addr) : "memory");
}
__device__ __forceinline__ void ldsm4t(uint32_t (&a)[4], uint32_t addr) {
    asm volatile("ldmatrix.sync.aligned.m8n8.x4.trans.shared.b16 {%0,%1,%2,%3}, [%4];"
                 : "=r"(a[0]), "=r"(a[1]), "=r"(a[2]), "=r"(a[3]) : "r"(addr) : "memory");
}
__device__ __forceinline__ void mma16816(float (&c)[4], const uint32_t (&a)[4], uint32_t b0, uint32_t b1) {
    asm volatile("mma.sync.aligned.m16n8k16.row.col.f32.bf16.bf16.f32 {%0,%1,%2,%3}, {%4,%5,%6,%7}, {%8,%9}, {%0,%1,%2,%3};"
                 : "+f"(c[0]), "+f"(c[1]), "+f"(c[2]), "+f"(c[3])
                 : "r"(a[0]), "r"(a[1]), "r"(a[2]), "r"(a[3]), "r"(b0), "r"(b1));
}
__device__ __forceinline__ float ldsf(uint32_t a) { float v; asm volatile("ld.shared.f32 %0, [%1];" : "=f"(v) : "r"(a) : "memory"); return v; }
__device__ __forceinline__ uint2 lds64(uint32_t a) {
    uint2 v; asm volatile("ld.shared.v2.u32 {%0,%1}, [%2];" : "=r"(v.x), "=r"(v.y) : "r"(a) : "memory"); return v;
}
__device__ __forceinline__ uint4 lds128(uint32_t a) {
    uint4 v; asm volatile("ld.shared.v4.u32 {%0,%1,%2,%3}, [%4];" : "=r"(v.x), "=r"(v.y), "=r"(v.z), "=r"(v.w) : "r"(a) : "memory"); return v;
}
__device__ __forceinline__ void sts16(uint32_t a, uint32_t v) { asm volatile("st.shared.u16 [%0], %1;" ::"r"(a), "h"((unsigned short)v) : "memory"); }
__device__ __forceinline__ void sts32(uint32_t a, uint32_t v) { asm volatile("st.shared.u32 [%0], %1;" ::"r"(a), "r"(v) : "memory"); }
__device__ __forceinline__ void sts64(uint32_t a, uint32_t x, uint32_t y) { asm volatile("st.shared.v2.u32 [%0], {%1,%2};" ::"r"(a), "r"(x), "r"(y) : "memory"); }
__device__ __forceinline__ void sts128(uint32_t a, uint32_t x, uint32_t y, uint32_t z, uint32_t w) {
    asm volatile("st.shared.v4.u32 [%0], {%1,%2,%3,%4};" ::"r"(a), "r"(x), "r"(y), "r"(z), "r"(w) : "memory");
}
__device__ __forceinline__ void sts128f(uint32_t a, const float (&c)[4]) {
    asm volatile("st.shared.v4.f32 [%0], {%1,%2,%3,%4};" ::"r"(a), "f"(c[0]), "f"(c[1]), "f"(c[2]), "f"(c[3]) : "memory");
}
__device__ __forceinline__ unsigned ldg_rlx1(const unsigned* p) {
    unsigned v; asm volatile("ld.relaxed.gpu.global.u32 %0, [%1];" : "=r"(v) : "l"(p) : "memory"); return v;
}
__device__ __forceinline__ uint4 ldg_rlx4(const unsigned* p) {
    uint4 v; asm volatile("ld.relaxed.gpu.global.v4.u32 {%0,%1,%2,%3}, [%4];" : "=r"(v.x), "=r"(v.y), "=r"(v.z), "=r"(v.w) : "l"(p) : "memory"); return v;
}
__device__ __forceinline__ uint4 ldg_pkt(const unsigned* p) {
    uint4 v;
    asm volatile("{\n.reg .b128 t;\n.reg .b64 lo, hi;\nld.relaxed.gpu.global.b128 t, [%4];\nmov.b128 {lo, hi}, t;\n"
                 "mov.b64 {%0,%1}, lo;\nmov.b64 {%2,%3}, hi;\n}"
                 : "=r"(v.x), "=r"(v.y), "=r"(v.z), "=r"(v.w) : "l"(p) : "memory");
    return v;
}
__device__ __forceinline__ void ldg_pkt_if(uint4& v, const unsigned* a, unsigned p) {
    asm volatile("{\n.reg .pred q;\n.reg .b128 t;\n.reg .b64 lo, hi;\nsetp.ne.u32 q, %5, 0;\n"
                 "mov.b64 lo, {%0,%1};\nmov.b64 hi, {%2,%3};\nmov.b128 t, {lo, hi};\n"
                 "@q ld.relaxed.gpu.global.b128 t, [%4];\nmov.b128 {lo, hi}, t;\n"
                 "mov.b64 {%0,%1}, lo;\nmov.b64 {%2,%3}, hi;\n}"
                 : "+r"(v.x), "+r"(v.y), "+r"(v.z), "+r"(v.w) : "l"(a), "r"(p) : "memory");
}
__device__ __forceinline__ bool any_lane(unsigned x) { return __any_sync(0xffffffffu, x != 0); }
__device__ __forceinline__ void stg_pkt(unsigned* p, float a, float b, float c, float d, unsigned tag) {
    unsigned x = (__float_as_uint(a) & ~7u) | tag;
    asm volatile("{\n.reg .b128 t;\n.reg .b64 lo, hi;\nmov.b64 lo, {%1,%2};\nmov.b64 hi, {%3,%4};\nmov.b128 t, {lo, hi};\n"
                 "st.relaxed.gpu.global.b128 [%0], t;\n}"
                 ::"l"(p), "r"(x), "r"(__float_as_uint(b)), "r"(__float_as_uint(c)), "r"(__float_as_uint(d)) : "memory");
}
__device__ __forceinline__ void stg_rlx1(unsigned* p, unsigned x) { asm volatile("st.relaxed.gpu.global.u32 [%0], %1;" ::"l"(p), "r"(x) : "memory"); }
__device__ __forceinline__ unsigned bad4(const uint4& v, unsigned tag) {
    return ((v.x ^ tag) | (v.y ^ tag)) | ((v.z ^ tag) | (v.w ^ tag));
}
__device__ __forceinline__ float untagf(unsigned w) { return __uint_as_float(w & ~7u); }
__device__ __forceinline__ uint32_t pack2(float lo, float hi) {
    uint32_t r; asm("cvt.rn.bf16x2.f32 %0, %1, %2;" : "=r"(r) : "f"(hi), "f"(lo)); return r;
}
__device__ __forceinline__ float bflo(uint32_t w) { return __uint_as_float(w << 16); }
__device__ __forceinline__ float bfhi(uint32_t w) { return __uint_as_float(w & 0xffff0000u); }
__device__ __forceinline__ uint32_t hi2(uint32_t a, uint32_t b) { return __byte_perm(a, b, 0x7632); }
__device__ __forceinline__ uint32_t badd2(uint32_t a, uint32_t b) { uint32_t r; asm("add.rn.bf16x2 %0, %1, %2;" : "=r"(r) : "r"(a), "r"(b)); return r; }
__device__ __forceinline__ uint32_t bsub2(uint32_t a, uint32_t b) { uint32_t r; asm("sub.rn.bf16x2 %0, %1, %2;" : "=r"(r) : "r"(a), "r"(b)); return r; }
__device__ __forceinline__ uint32_t bmul2(uint32_t a, uint32_t b) { uint32_t r; asm("mul.rn.bf16x2 %0, %1, %2;" : "=r"(r) : "r"(a), "r"(b)); return r; }
__device__ __forceinline__ uint32_t bmax2(uint32_t a, uint32_t b) { uint32_t r; asm("max.bf16x2 %0, %1, %2;" : "=r"(r) : "r"(a), "r"(b)); return r; }
__device__ __forceinline__ float ex2(float x) { float r; asm("ex2.approx.ftz.f32 %0, %1;" : "=f"(r) : "f"(x)); return r; }
__device__ __forceinline__ float rcp(float x) { float r; asm("rcp.approx.ftz.f32 %0, %1;" : "=f"(r) : "f"(x)); return r; }
__device__ __forceinline__ float fsqrt(float x) { float r; asm("sqrt.approx.ftz.f32 %0, %1;" : "=f"(r) : "f"(x)); return r; }
__device__ __forceinline__ float shx(float v, int m) { return __shfl_xor_sync(0xffffffffu, v, m); }
#define TS(cond, slot) do { } while (0)

__device__ __forceinline__ uint32_t k_off(int i) { return i < 8 ? OFF_K0 + i * 16384 : (i - 8) * 16384; }
__device__ __forceinline__ uint32_t v_off(int i) { return i < 5 ? (8 + i) * 16384 : (i - 5) * 16384; }

__device__ __forceinline__ void stg_ph(unsigned* p) { stg_pkt(p, 0.f, 0.f, 0.f, 0.f, 2u); }

__device__ __forceinline__ void ln_stage1(uint32_t xw0, uint32_t xw1, uint32_t st, int vw, int lane) {
    const float piv = __shfl_sync(0xffffffffu, bflo(xw0), lane & 4);
    const float d0 = bflo(xw0) - piv, d1 = bfhi(xw0) - piv, d2 = bflo(xw1) - piv, d3 = bfhi(xw1) - piv;
    float s1 = (d0 + d1) + (d2 + d3), s2 = (d0 * d0 + d1 * d1) + (d2 * d2 + d3 * d3);
    s1 += shx(s1, 1); s2 += shx(s2, 1);
    s1 += shx(s1, 2); s2 += shx(s2, 2);
    s1 += shx(s1, 8); s2 += shx(s2, 8);
    s1 += shx(s1, 16); s2 += shx(s2, 16);
    if ((lane & 27) == 0)
        sts64(st + vw * 8, __float_as_uint(piv + s1 * (1.0f / 64.0f)), __float_as_uint(s2 - s1 * s1 * (1.0f / 64.0f)));
}
struct LnStat { uint4 a, b, c, d; uint2 e; };
__device__ __forceinline__ LnStat ln_load(uint32_t st) {
    LnStat s; s.a = lds128(st); s.b = lds128(st + 16); s.c = lds128(st + 32); s.d = lds128(st + 48); s.e = lds64(st + 64);
    return s;
}
__device__ __forceinline__ void ln_stage2(const LnStat& s, uint32_t xw0, uint32_t xw1, uint32_t& y0, uint32_t& y1) {
    const float m[9] = {__uint_as_float(s.a.x), __uint_as_float(s.a.z), __uint_as_float(s.b.x), __uint_as_float(s.b.z),
                        __uint_as_float(s.c.x), __uint_as_float(s.c.z), __uint_as_float(s.d.x), __uint_as_float(s.d.z), __uint_as_float(s.e.x)};
    const float mean = (((m[0] + m[1]) + (m[2] + m[3])) + ((m[4] + m[5]) + (m[6] + m[7])) + m[8]) * (1.0f / NCW);
    const float m2 = ((__uint_as_float(s.a.y) + __uint_as_float(s.a.w)) + (__uint_as_float(s.b.y) + __uint_as_float(s.b.w))) +
                     ((__uint_as_float(s.c.y) + __uint_as_float(s.c.w)) + (__uint_as_float(s.d.y) + __uint_as_float(s.d.w))) + __uint_as_float(s.e.y);
    float d[9];
#pragma unroll
    for (int w = 0; w < 9; w++) d[w] = m[w] - mean;
    const float acc = (d[0] * d[0] + d[1] * d[1] + d[2] * d[2]) + (d[3] * d[3] + d[4] * d[4] + d[5] * d[5]) + (d[6] * d[6] + d[7] * d[7] + d[8] * d[8]);
    const float var = (m2 + 64.0f * acc) * (1.0f / DM);
    const uint32_t mv = pack2(mean, var);
    const float ve = bflo(pack2(bfhi(mv) + 1e-5f, 0.f));
    const float rinv = rcp(bflo(pack2(fsqrt(ve), 0.f)));
    const uint32_t mm = __byte_perm(mv, mv, 0x1010);
    const uint32_t e0 = bsub2(xw0, mm), e1 = bsub2(xw1, mm);
    y0 = pack2(bflo(e0) * rinv, bfhi(e0) * rinv); y1 = pack2(bflo(e1) * rinv, bfhi(e1) * rinv);
}
__device__ __forceinline__ void make_bfrags(uint32_t (&bf)[4][2], uint32_t aw0, uint32_t aw1, int r) {
#pragma unroll
    for (int ks = 0; ks < 4; ks++) {
        bf[ks][0] = __shfl_sync(0xffffffffu, aw0, ks * 8 + r);
        bf[ks][1] = __shfl_sync(0xffffffffu, aw1, ks * 8 + r);
    }
}
__device__ __forceinline__ uint32_t gemv32(uint32_t s_w, uint32_t red, uint32_t fullbar, uint32_t emptybar,
                                           uint32_t aw0, uint32_t aw1, int tid) {
    const int vw = tid >> 5, lane = tid & 31, g = lane >> 2, t = lane & 3, mi = lane >> 3, r = lane & 7;
    uint32_t bf[4][2];
    make_bfrags(bf, aw0, aw1, r);
    if (vw <= 4) mbar_wait(fullbar);
    if (vw >= 4) mbar_wait(fullbar + 8);
    float cc[2][4] = {};
    const uint32_t abase = s_w + (vw * 64 + r + 8 * (mi >> 1)) * 64;
    const uint32_t sw = ((mi & 1) ^ (r >> 1)) << 4;
#pragma unroll
    for (int ks = 0; ks < 4; ks++) {
#pragma unroll
        for (int mt = 0; mt < 2; mt++) {
            uint32_t a[4];
            ldsm4t(a, abase + ks * 1024 + (sw ^ (mt * 32)));
            mma16816(cc[mt], a, bf[ks][0], bf[ks][1]);
        }
    }
    if (t == 0) { sts128f(red + vw * 256 + g * 16, cc[0]); sts128f(red + vw * 256 + 128 + g * 16, cc[1]); }
    __syncwarp();
    if (lane == 0) mbar_arrive(emptybar);
    bar_consumers();
    float s = 0.f;
    if (tid < 64) {
        const uint32_t ra = red + ((tid & 58) | ((tid & 1) << 2) | ((tid >> 2) & 1)) * 4;
#pragma unroll
        for (int w = 0; w < NCW; w++) s += ldsf(ra + w * 256);
    }
    return pack2(0.f, s);
}
__device__ __forceinline__ void publish_partials(unsigned* q, unsigned hm, const float (&cc)[4][4], unsigned tag) {
#pragma unroll
    for (int mt = 0; mt < 4; mt++)
        stg_pkt(q + mt * 4 * 2048 + ((hm >> (4 * mt)) & 1) * HALF, cc[mt][0], cc[mt][1], cc[mt][2], cc[mt][3], tag);
}
__device__ __forceinline__ void spin_cycles(unsigned n) {
    const unsigned c0 = clock();
    while ((unsigned)clock() - c0 < n) { }
}
__device__ __forceinline__ float reduce_unit(const unsigned* q, int lane, unsigned tag) {
    uint4 v[8];
#pragma unroll
    for (int i = 0; i < 8; i++) v[i] = ldg_pkt(q + i * 128);
    int it = 0;
    while (true) {
        unsigned bad = 0;
#pragma unroll
        for (int i = 0; i < 8; i += 2) bad |= (v[i].x ^ tag) | (v[i + 1].x ^ tag);
        if (!any_lane(bad & 7u) || ++it >= SPIN_LIMIT) break;
#pragma unroll
        for (int i = 0; i < 8; i++) ldg_pkt_if(v[i], q + i * 128, (v[i].x ^ tag) & 7u);
    }
    float s0 = 0.f, s1 = 0.f, s2 = 0.f, s3 = 0.f, u0 = 0.f, u1 = 0.f, u2 = 0.f, u3 = 0.f;
#pragma unroll
    for (int i = 0; i < 8; i += 2) {
        s0 += untagf(v[i].x); s1 += __uint_as_float(v[i].y); s2 += __uint_as_float(v[i].z); s3 += __uint_as_float(v[i].w);
        u0 += untagf(v[i + 1].x); u1 += __uint_as_float(v[i + 1].y); u2 += __uint_as_float(v[i + 1].z); u3 += __uint_as_float(v[i + 1].w);
    }
    s0 += u0; s1 += u1; s2 += u2; s3 += u3;
    __syncwarp();
    const bool h8 = lane & 2, bat = lane & 4;
    const float k0 = (h8 ? s2 : s0) + shx(h8 ? s0 : s2, 2);
    const float k1 = (h8 ? s3 : s1) + shx(h8 ? s1 : s3, 2);
    float k = (bat ? k1 : k0) + shx(bat ? k0 : k1, 4);
    k += shx(k, 8);
    k += shx(k, 16);
    return k;
}

__global__ void __launch_bounds__(NTHR, 1)
fused_block_kernel(const __grid_constant__ Maps maps, const __nv_bfloat16* __restrict__ xin,
                   const __nv_bfloat16* __restrict__ cin, const __nv_bfloat16* __restrict__ kcache,
                   __nv_bfloat16* __restrict__ out, unsigned* const scr TUNE_PARAM) {
    extern __shared__ unsigned char smem_raw[];
    const int c = blockIdx.x;
    const int kvh = c >> 3, j = c & 7, bb = j & 1, sp = j >> 1;
    const int kvrow0 = (bb * 16 + kvh) * 32768 + 28672 + sp * 1024;
    if (EARLY_PF && threadIdx.x == 0)
        asm volatile("cp.async.bulk.prefetch.L2.global [%0], %1;" ::"l"((const char*)kcache + (size_t)kvrow0 * 256), "r"(EARLY_PF) : "memory");
    TS(threadIdx.x == 0, 0);
    const uint32_t sb = (smem_u32(smem_raw) + 1023u) & ~1023u;
    const int warp = threadIdx.x >> 5, lane = threadIdx.x & 31;
    const uint32_t s_full = sb + OFF_BAR, s_empty = s_full + N_IT * 8;

    if (warp == NCW) {
        uint32_t t0 = gtime32();
        const int first = (c < NMOD) ? 0 : 2;
        if (lane == 0) {
#pragma unroll
            for (int i = 0; i < 2; i++) mbar_init(s_full + (first + i) * 8, 1);
            asm volatile("fence.proxy.async.shared::cta;" ::: "memory");
#pragma unroll
            for (int i = 0; i < 2; i++) {
                const uint32_t bar = s_full + (first + i) * 8;
                mbar_expect_tx(bar, 18432);
                tma3d(sb + (first + i) * 18432, &maps.m[M_WMOD + (first >> 1)], c * 32, 0, i * 2, bar);
            }
            TS(true, 17);
        }
        __syncwarp();
        uint32_t w0[2], w1[2], w2[2];
#pragma unroll
        for (int h = 0; h < 2; h++) {
            const int i = lane + 32 * h;
            int off, map, dep = -1, x = 0, y = 0, z = 0, sz = 36, cum;
            if (i < IT_K) {
                off = i * 18432; map = M_WMOD + (i >> 1); x = c * 32; z = (i & 1) * 2; cum = 31104 + (i - 2) * 18432;
            } else if (i < IT_V) {
                const int k = i - IT_K;
                off = k_off(k); map = M_K; y = kvrow0 + k * 64; sz = 32; cum = 67968 + k * 16384;
                if (k == 8 && c < NMOD) dep = EM_WMOD;
                if (k == 10) dep = EM_WQ;
                if (k >= 12) dep = EM_K + k - 12;
            } else if (i < IT_WO) {
                const int k = i - IT_V;
                off = v_off(k); map = M_V; y = kvrow0 + k * 64; sz = 32; cum = 330112 + k * 16384;
                dep = EM_K + 3 + k + (k < 4);
            } else if (i < IT_GU) {
                const int k = i - IT_WO;
                off = k ? OFF_WO1 : OFF_WO0; map = M_WO; y = kvh * 256 + k * 128 + j * 16; dep = EM_V + 4 + 2 * k;
                cum = 592256 + k * 18432;
            } else if (i < IT_WD) {
                const int k = i - IT_GU;
                off = ((k & 1) ? OFF_U : OFF_G) + (k >> 1) * 18432; map = M_WG + (k & 1);
                x = (c * 36) & ~15; y = (k >> 1) * 192; dep = EM_V + 5 + ((off + 18431) >> 14);
                cum = 629120 + k * 13824;
            } else {
                const int k = i - IT_WD;
                off = OFF_D + k * DSTR; map = M_WD; y = c * 36; z = k * 3; sz = 27; dep = EM_V + 13 + k;
                cum = 712064 + k * 13824;
            }
            cum += EARLY_PF - min(max(cum - 67968, 0), EARLY_PF);
            const int stag = ((c * 37) & 127) * 128 - PACE_LEAD;
            int due = (int)((float)max(min(cum, 629120) + stag, 0) * (128.0f / PACE_GBS));
            if (i >= IT_GU) due += TAIL_GAP + (int)((float)(min(cum, 712064) - 629120) * (128.0f / PACE_TAIL));
            if (i >= IT_WD) due += (int)((float)(cum - 712064) * (128.0f / PACE_D));
            w0[h] = off | (map << 18) | ((dep + 1) << 22) | (z << 28);
            w1[h] = y | (sz << 24);
            w2[h] = x | (due << 13);
        }
        asm volatile("bar.sync 2, 384;" ::: "memory");
#pragma unroll 1
        for (int i = first + 2; i < N_IT; i++) {
            const bool hi = i >= 32;
            const uint32_t a = __shfl_sync(0xffffffffu, hi ? w0[1] : w0[0], i);
            const uint32_t b = __shfl_sync(0xffffffffu, hi ? w1[1] : w1[0], i);
            const uint32_t x = __shfl_sync(0xffffffffu, hi ? w2[1] : w2[0], i);
            if (lane == 0) {
                const int prev = i - ((i >= WIN_SWITCH) ? WIN_TAIL : WIN_MAIN);
                const int dep = (a >> 22) & 63;
                if (dep) mbar_wait(s_empty + (dep - 1) * 8);
                while (!((prev < first || mbar_test(s_full + prev * 8)) && gtime32() - t0 >= (x >> 13)) && !(OPEN_WIN && mbar_test(s_empty + EM_CH * 8))) { }
                if (i >= NOCATCH) { const uint32_t late = gtime32() - t0 - (x >> 13); if ((int)late > 0) t0 += late; }
                const uint32_t bar = s_full + i * 8;
                mbar_expect_tx(bar, (b >> 24) * 512);
                tma3d(sb + (a & 0x3ffff), &maps.m[(a >> 18) & 15], x & 0x1fff, b & 0xffffff, a >> 28, bar);
                TS(i == IT_WO, 1);
            }
            __syncwarp();
        }
        return;
    }

    const int g = lane >> 2, t = lane & 3, mi = lane >> 3, r = lane & 7;
    const int bat = g & 1;

    if (warp > NCW) {
        const bool first = warp == NCW + 1, active = first || c < 16;
        const int unit = first ? c : NCTA + c;
        const int rcol = (unit >> 2) * 16 + (unit & 3) * 2 + (lane & 1) + (lane & 2) * 4 + bat * DM;
        const unsigned ep = ldg_rlx1(scr + G_EPOCH);
        uint32_t xold = 0, ga = 0, gb = 0;
        if (active) xold = __ldg((const unsigned short*)xin + rcol);
        if (!first) asm volatile("bar.sync 2, 384;" ::: "memory");
        const unsigned tag = (ep + 1u) & 1u;
        unsigned side = 0;
        const int x1w = G_X1 + (unit >> 7) * 2048 + (unit & 127) * 8 + r + (lane & 8) * (HALF / 8) + (lane >> 4) * 4096;
        if (first) {
            unsigned* pr = scr + G_PROBE + c * 8;
            if (lane < 16) stg_rlx1(pr + r + (lane & 8) * (HALF / 8), 0u);
            __syncwarp();
            asm volatile("bar.arrive 2, 384;" ::: "memory");
            unsigned best0 = ~0u, best1 = ~0u, v = 0, cp = 0;
#pragma unroll 1
            for (int i = 0; i <= 2 * NPROBE; i++) {
                if (lane == 0) {
                    asm volatile("atom.relaxed.gpu.global.add.u32 %0, [%1], 1;" : "=r"(v) : "l"(pr + (i & 1) * HALF + (v >> 31)) : "memory");
                    const unsigned cn = clock(), d = cn - cp;
                    cp = cn;
                    if (i & 1) best0 = min(best0, d); else if (i) best1 = min(best1, d);
                    side = (best1 < best0) ^ (__popc(G_PROBE & 0x2C800) & 1);
                }
                if (i == 2 * NPROBE0) {
                    asm volatile("bar.sync 6, 64;" ::: "memory");
                    if (lane == 0) { sts32(sb + OFF_WMX + 116, side); mbar_arrive(s_empty + EM_SD * 8); }
                }
            }
            if (lane == 0) sts32(sb + OFF_WMX + 112, side);
            side = __shfl_sync(0xffffffffu, side, 0);
            mbar_wait(s_full + it_v(PH_V) * 8);
#pragma unroll 1
            for (int u = c; u < 144; u += NCTA) {
                unsigned* q = scr + G_PART + u * 2048 + near_half(G_PART + u * 2048, side) + lane * 4;
#pragma unroll
                for (int i = 0; i < 8; i++) stg_ph(q + i * 128);
#pragma unroll
                for (int i = 0; i < XREP; i += 2) stg_rlx1(scr + x1w + (u >> 7) * 2048 + i * 4096, 2u);
            }
            unsigned* o = scr + G_OP + kvh * 4096 + (j >> 2) * 2048 + (j & 3) * 256 + lane * 4;
            stg_ph(o); stg_ph(o + 128); stg_ph(o + HALF); stg_ph(o + HALF + 128);
            __threadfence();
            __syncwarp();
            if (lane < 8) stg_rlx1(scr + G_SIDE + c * 8 + lane, (side << 4) | tag);
            if (lane == 0) mbar_arrive(s_empty + EM_PH * 8);
        } else {
            asm volatile("bar.arrive 6, 64;" ::: "memory");
            if (TM_PF && lane < 8) asm volatile("prefetch.tensormap [%0];" ::"l"(&maps.m[lane]) : "memory");
            mbar_wait(s_empty + EM_PH * 8);
            side = __float_as_uint(ldsf(sb + OFF_WMX + 112));
        }
        if (active) {
            int it = 0;
            do {
                ga = ldg_rlx1(scr + dual_near(G_MOD, 2 * 1152 + unit * 8 + r, side));
                gb = ldg_rlx1(scr + dual_near(G_MOD, 5 * 1152 + unit * 8 + r, side));
            } while (any_lane(((ga ^ tag) | (gb ^ tag)) & 7u) && ++it < SPIN_LIMIT);
            ga >>= 16; gb >>= 16;
        }
        __syncwarp();
        if (first) {
            const int ow = G_OP + kvh * 4096 + (g >> 2) * 2048;
            const unsigned* q = scr + ow + near_half(ow, side) + (g & 3) * 256 + j * 32 + t * 8;
            mbar_wait(s_full + it_v(15) * 8);
            uint4 lo, hi;
            int it = 0;
            do { lo = ldg_pkt(q); hi = ldg_pkt(q + 4); } while (any_lane(((lo.x ^ tag) | (hi.x ^ tag)) & 7u) && ++it < SPIN_LIMIT);
            float o[8] = {untagf(lo.x), __uint_as_float(lo.y), __uint_as_float(lo.z), __uint_as_float(lo.w),
                          untagf(hi.x), __uint_as_float(hi.y), __uint_as_float(hi.z), __uint_as_float(hi.w)};
            __syncwarp();
#pragma unroll
            for (int sft = 8; sft <= 16; sft <<= 1) {
#pragma unroll
                for (int i = 0; i < 8; i++) o[i] += shx(o[i], sft);
            }
            if (lane < 8)
                sts128(sb + OFF_FR + lane * 48, pack2(o[0], o[4]), pack2(o[2], o[6]), pack2(o[1], o[5]), pack2(o[3], o[7]));
            TS(lane == 0, 10);
        }
        asm volatile("bar.sync 3, 352;" ::: "memory");
        const unsigned* q = scr + G_PART + unit * 2048 + near_half(G_PART + unit * 2048, side) + lane * 4;
        if (DELAY_B) spin_cycles(DELAY_B);
        if (active) {
            const float k = reduce_unit(q, lane, tag);
            xold = badd2(xold, bmul2(ga, pack2(k, 0.f))) & 0xffffu;
#pragma unroll
            for (int i = 0; i < XREP; i += 2) stg_rlx1(scr + x1w + i * 4096, (xold << 16) | tag);
            TS(first && lane == 0, 12);
            TS(!first && lane == 0, 18);
        }
        if (first && lane == 0) mbar_arrive(s_empty + EM_X1 * 8);
        asm volatile("bar.sync 5, 352;" ::: "memory");
        if (active) {
            if (DELAY_D) spin_cycles(DELAY_D);
            const float k = reduce_unit(q, lane, tag | 4u);
            xold = badd2(xold, bmul2(gb, pack2(k, 0.f)));
            if (lane < 8) ((unsigned short*)out)[rcol] = (unsigned short)xold;
            if (c == 0 && first && lane == 0) stg_rlx1(scr + G_EPOCH, ep + 1u);
            TS(first && lane == 0, 16);
        }
        return;
    }

    const int vw = warp, tid = threadIdx.x;
    const int vecw = tid * 4 - (lane & 7) * 4 + t * 8 + bat * 4;
    unsigned* const ppart = scr + G_PART + (vw * 16 + (g >> 1)) * 2048 + c * 8 + bat * 4;
    const unsigned* const pside = scr + G_SIDE + ((vw * 16 + (lane & 15)) & 127) * 8;
    const int qword = dual(G_Q, bat * 4096 + c * 32 + (tid >> 3) * 4 + t), mword = dual(G_MOD, c * 64 + (tid & 63));
    const uint32_t one2 = 0x3f803f80u;

    const unsigned ep = ldg_rlx1(scr + G_EPOCH);
    if (tid < 64) {
        if (c < NMOD) { stg_rlx1(scr + mword, 2u); stg_rlx1(scr + mword + HALF, 2u); }
        stg_rlx1(scr + qword, 2u); stg_rlx1(scr + qword + HALF, 2u);
    }
    uint32_t xw0, xw1, aw0, aw1;
    {
        const int col0 = bat * DM + (vw * 4 + mi) * 16 + 2 * t;
        const uint32_t cw0 = __ldg((const unsigned*)(cin + col0)), cw1 = __ldg((const unsigned*)(cin + col0 + 8));
        xw0 = __ldg((const unsigned*)(xin + col0)); xw1 = __ldg((const unsigned*)(xin + col0 + 8));
        if (tid < 8) sts64(sb + OFF_FR + tid * 48 + 16, 0u, 0u);
        if (lane == 0) {
            const int lo = (c < NMOD) ? 2 : 4;
#pragma unroll 1
            for (int i = vw; i < N_IT + N_EM; i += NCW) {
                const int e = i - N_IT;
                if (i >= lo) mbar_init(s_full + i * 8, (e < 0 || e >= EM_PH) ? 1 : (e < EM_K ? NCW : (e < EM_V ? 4 : 8)));
            }
            asm volatile("fence.proxy.async.shared::cta;" ::: "memory");
        }
        __syncwarp();
        asm volatile("bar.sync 2, 384;" ::: "memory");
        float cv[4] = {bflo(cw0), bfhi(cw0), bflo(cw1), bfhi(cw1)};
#pragma unroll
        for (int i = 0; i < 4; i++) cv[i] = cv[i] * rcp(1.0f + ex2(-1.4426950408889634f * cv[i]));
        aw0 = pack2(cv[0], cv[1]); aw1 = pack2(cv[2], cv[3]);
    }
    const unsigned tag = (ep + 1u) & 1u;
    const uint32_t st1 = sb + OFF_STAT + bat * 80, st2 = st1 + 160;
    ln_stage1(xw0, xw1, st1, vw, lane);

    if (c < NMOD) {
        const uint32_t m = gemv32(sb + OFF_WMOD, sb + OFF_RED, s_full + IT_WMOD * 8, s_empty + EM_WMOD * 8, aw0, aw1, tid);
        if (tid < 64) { stg_rlx1(scr + mword, m | tag); stg_rlx1(scr + mword + HALF, m | tag); }
    } else {
        bar_consumers();
    }
    TS(tid == 0, 4);
    mbar_wait(s_empty + EM_SD * 8);
    unsigned side = __float_as_uint(ldsf(sb + OFF_WMX + 116));
    {
        uint32_t y0, y1;
        ln_stage2(ln_load(st1), xw0, xw1, y0, y1);
        uint4 a, b;
        int it = 0;
        const unsigned *pa = scr + dual_near(G_MOD, vecw, side), *pb = scr + dual_near(G_MOD, 1152 + vecw, side);
        do { a = ldg_rlx4(pa); b = ldg_rlx4(pb); }
        while (any_lane((bad4(a, tag) | bad4(b, tag)) & 7u) && ++it < SPIN_LIMIT);
        __syncwarp();
        aw0 = badd2(bmul2(y0, badd2(one2, hi2(b.x, b.y))), hi2(a.x, a.y));
        aw1 = badd2(bmul2(y1, badd2(one2, hi2(b.z, b.w))), hi2(a.z, a.w));
        TS(tid == 0, 5);
        const uint32_t q = gemv32(sb + OFF_WQ, sb + OFF_RED + 2304, s_full + IT_WQ * 8, s_empty + EM_WQ * 8, aw0, aw1, tid);
        if (tid < 64) {
            stg_rlx1(scr + qword, q | tag); stg_rlx1(scr + qword + HALF, q | tag);
            uint4 v;
            int it = 0;
            const unsigned* pq = scr + dual_near(G_Q, bb * 4096 + kvh * 256 + tid * 4, side);
            do { v = ldg_rlx4(pq); } while (any_lane(bad4(v, tag) & 7u) && ++it < SPIN_LIMIT);
            sts64(sb + OFF_QS + (vw * 4 + t) * 80 + g * 8, hi2(v.x, v.y), hi2(v.z, v.w));
        }
        bar_consumers();
        TS(tid == 0, 6);
    }
    uint32_t sc0, sc1, sh0, sh1;
    {
        uint4 d, e;
        unsigned bad;
        int it = 0;
        do {
            d = ldg_rlx4(scr + dual_near(G_MOD, 3 * 1152 + vecw, side)); e = ldg_rlx4(scr + dual_near(G_MOD, 4 * 1152 + vecw, side));
            bad = bad4(d, tag) | bad4(e, tag);
        } while (any_lane(bad & 7u) && ++it < SPIN_LIMIT);
        __syncwarp();
        sh0 = hi2(d.x, d.y); sh1 = hi2(d.z, d.w);
        sc0 = badd2(one2, hi2(e.x, e.y)); sc1 = badd2(one2, hi2(e.z, e.w));
    }
    if (vw < 8) {
        uint4 qf[4];
#pragma unroll
        for (int i = 0; i < 4; i++) qf[i] = lds128(sb + OFF_QS + r * 80 + i * 16);
        const int mt = vw & 3;
        const uint32_t rowoff = (mt * 16 + r + 8 * (mi & 1)) * 128;
        const uint32_t sw = ((mi >> 1) ^ r) << 4;
        uint32_t mx = 0xff80ff80u;
#pragma unroll 1
        for (int i = (vw >> 2); i < 16; i += 2) {
            mbar_wait(s_full + (IT_K + i) * 8);
            const uint32_t base = sb + k_off(i) + rowoff;
            float c0[4] = {}, c1[4] = {};
            uint32_t a[4];
            ldsm4(a, base + sw);               mma16816(c0, a, qf[0].x, qf[0].y);
            ldsm4(a, base + 8192 + sw);        mma16816(c1, a, qf[2].x, qf[2].y);
            ldsm4(a, base + (sw ^ 32));        mma16816(c0, a, qf[0].z, qf[0].w);
            ldsm4(a, base + 8192 + (sw ^ 32)); mma16816(c1, a, qf[2].z, qf[2].w);
            ldsm4(a, base + (sw ^ 64));        mma16816(c0, a, qf[1].x, qf[1].y);
            ldsm4(a, base + 8192 + (sw ^ 64)); mma16816(c1, a, qf[3].x, qf[3].y);
            ldsm4(a, base + (sw ^ 96));        mma16816(c0, a, qf[1].z, qf[1].w);
            ldsm4(a, base + 8192 + (sw ^ 96)); mma16816(c1, a, qf[3].z, qf[3].w);
            __syncwarp();
            if (lane == 0) mbar_arrive(s_empty + (EM_K + i) * 8);
            const float scl = 0.08838834764831845f;
            uint32_t u0 = pack2(c0[0] + c1[0], c0[1] + c1[1]), u1 = pack2(c0[2] + c1[2], c0[3] + c1[3]);
            u0 = pack2(bflo(u0) * scl, bfhi(u0) * scl); u1 = pack2(bflo(u1) * scl, bfhi(u1) * scl);
            mx = bmax2(mx, bmax2(u0, u1));
            if (t == 0) {
                const uint32_t pa = sb + OFF_S + (i * 64 + 16 * (g >> 1) + 4 * mt + bat) * 4;
                sts32(pa, u0); sts32(pa + 8, u1);
            }
            if (i == PH_K && tid < 4) stg_ph(scr + G_ML + c * 8 + (tid & 1) * 4 + (tid & 2) * (HALF / 2));
        }
#pragma unroll
        for (int o = 4; o <= 16; o <<= 1) mx = bmax2(mx, __shfl_xor_sync(0xffffffffu, mx, o));
        if (lane == 0) sts32(sb + OFF_WMX + vw * 4, mx);
    }
    bar_consumers();
    TS(tid == 0, 7);
    {
        const float L2E = 1.4426950408889634f;
        uint4 sv = make_uint4(0, 0, 0, 0);
        float m0 = 0.f, m1 = 0.f;
        if (vw < 8) {
            uint4 ma = lds128(sb + OFF_WMX), mb = lds128(sb + OFF_WMX + 16);
            const uint32_t mx = bmax2(bmax2(bmax2(ma.x, ma.y), bmax2(ma.z, ma.w)), bmax2(bmax2(mb.x, mb.y), bmax2(mb.z, mb.w)));
            m0 = bflo(mx); m1 = bfhi(mx);
            sv = lds128(sb + OFF_S + tid * 16);
            float e0 = (ex2((bflo(sv.x) - m0) * L2E) + ex2((bflo(sv.y) - m0) * L2E)) + (ex2((bflo(sv.z) - m0) * L2E) + ex2((bflo(sv.w) - m0) * L2E));
            float e1 = (ex2((bfhi(sv.x) - m1) * L2E) + ex2((bfhi(sv.y) - m1) * L2E)) + (ex2((bfhi(sv.z) - m1) * L2E) + ex2((bfhi(sv.w) - m1) * L2E));
#pragma unroll
            for (int o = 16; o > 0; o >>= 1) { e0 += shx(e0, o); e1 += shx(e1, o); }
            if (lane == 0) sts64(sb + OFF_WMX + 32 + vw * 8, __float_as_uint(e0), __float_as_uint(e1));
        }
        bar_consumers();
        if (vw == 0) {
            float l0 = 0.f, l1 = 0.f;
#pragma unroll
            for (int w = 0; w < 4; w++) {
                uint4 s = lds128(sb + OFF_WMX + 32 + w * 16);
                l0 += __uint_as_float(s.x) + __uint_as_float(s.z); l1 += __uint_as_float(s.y) + __uint_as_float(s.w);
            }
            if (tid < 4) stg_pkt(scr + G_ML + c * 8 + (tid & 1) * 4 + (tid & 2) * (HALF / 2), m0, l0, m1, l1, tag);
            {
                const bool rd = lane < 4 && lane != sp;
                uint4 v = make_uint4(rd ? 2u : tag, 0, 0, 0);
                int it = 0;
                do { ldg_pkt_if(v, scr + G_ML + near_half(G_ML, side) + (kvh * 8 + (lane & 3) * 2 + bb) * 8, (v.x ^ tag) & 7u); }
                while (any_lane((v.x ^ tag) & 7u) && ++it < SPIN_LIMIT);
                if (rd) { m0 = untagf(v.x); l0 = __uint_as_float(v.y); m1 = __uint_as_float(v.z); l1 = __uint_as_float(v.w); }
            }
            float g0 = fmaxf(m0, shx(m0, 1)), g1 = fmaxf(m1, shx(m1, 1));
            g0 = fmaxf(g0, shx(g0, 2)); g1 = fmaxf(g1, shx(g1, 2));
            l0 *= ex2((m0 - g0) * L2E); l1 *= ex2((m1 - g1) * L2E);
            l0 += shx(l0, 1); l1 += shx(l1, 1);
            l0 += shx(l0, 2); l1 += shx(l1, 2);
            if (lane == 0)
                sts128(sb + OFF_WMX + 96, __float_as_uint(g0), __float_as_uint(g1), __float_as_uint(1.0f / l0), __float_as_uint(1.0f / l1));
        }
        bar_consumers();
        if (vw < 8) {
            const uint4 gs = lds128(sb + OFF_WMX + 96);
            const float g0 = __uint_as_float(gs.x), g1 = __uint_as_float(gs.y), i0 = __uint_as_float(gs.z), i1 = __uint_as_float(gs.w);
            const uint32_t a0 = pack2(ex2((bflo(sv.x) - g0) * L2E) * i0, ex2((bflo(sv.y) - g0) * L2E) * i0);
            const uint32_t a1 = pack2(ex2((bflo(sv.z) - g0) * L2E) * i0, ex2((bflo(sv.w) - g0) * L2E) * i0);
            const uint32_t b0 = pack2(ex2((bfhi(sv.x) - g1) * L2E) * i1, ex2((bfhi(sv.y) - g1) * L2E) * i1);
            const uint32_t b1 = pack2(ex2((bfhi(sv.z) - g1) * L2E) * i1, ex2((bfhi(sv.w) - g1) * L2E) * i1);
            sts64(sb + OFF_P + tid * 8, a0, a1); sts64(sb + OFF_P + PSTR + tid * 8, b0, b1);
        }
        bar_consumers();
        TS(tid == 0, 8);
    }
    const uint32_t rin = vw * 2048 + (r + 8 * (mi >> 1)) * 128;
    const uint32_t rsw = ((mi & 1) ^ r) << 4;
    uint32_t ra[2][4][4];
    unsigned sidew = 2u;
    if (vw < 8) {
        float c0[4] = {}, c1[4] = {};
        const uint32_t vo = (vw >> 2) * 8192 + (r + 8 * (mi >> 1)) * 128 + ((((2 * vw + (mi & 1)) & 7) ^ r) << 4);
        const uint32_t pa = sb + OFF_P + bat * PSTR + t * 32;
#pragma unroll 1
        for (int i = 0; i < 16; i++) {
            uint4 pb0 = lds128(pa + i * 128), pb1 = lds128(pa + i * 128 + 16);
            mbar_wait(s_full + it_v(i) * 8);
            const uint32_t base = sb + v_off(i) + vo;
            uint32_t a0[4], a1[4], a2[4], a3[4];
            ldsm4t(a0, base); ldsm4t(a1, base + 2048); ldsm4t(a2, base + 4096); ldsm4t(a3, base + 6144);
            mma16816(c0, a0, pb0.x, pb0.y);
            mma16816(c1, a1, pb0.z, pb0.w);
            mma16816(c0, a2, pb1.x, pb1.y);
            mma16816(c1, a3, pb1.z, pb1.w);
            __syncwarp();
            if (lane == 0) mbar_arrive(s_empty + (EM_V + i) * 8);
            if (i == SIDE_V) { mbar_wait(s_empty + EM_PH * 8); sidew = ldg_rlx1(pside); }
        }
        if (t < 2)
            stg_pkt(scr + G_OP + kvh * 4096 + (j >> 2) * 2048 + t * HALF + (j & 3) * 256 + vw * 32 + g * 4,
                    c0[0] + c1[0], c0[1] + c1[1], c0[2] + c1[2], c0[3] + c1[3], tag);
        TS(tid == 0, 9);
    } else {
        mbar_wait(s_full + it_v(SIDE_V) * 8);
        mbar_wait(s_empty + EM_PH * 8);
    }
    unsigned hm;
    {
        int it = 0;
        while (any_lane((sidew ^ tag) & 7u) && ++it < SPIN_LIMIT) sidew = ldg_rlx1(pside);
        __syncwarp();
        const int uw = G_PART + (vw * 16 + (lane & 15)) * 2048;
        hm = __ballot_sync(0xffffffffu, near_half(uw, sidew >> 4)) >> (g >> 1);
    }
    side = __float_as_uint(ldsf(sb + OFF_WMX + 112));
    {
        mbar_wait(s_full + IT_WO * 8);
#pragma unroll
        for (int mt = 0; mt < 4; mt++) ldsm4t(ra[0][mt], sb + OFF_WO0 + rin + (rsw ^ (mt * 32)));
        mbar_wait(s_full + (IT_WO + 1) * 8);
#pragma unroll
        for (int mt = 0; mt < 4; mt++) ldsm4t(ra[1][mt], sb + OFF_WO1 + rin + (rsw ^ (mt * 32)));
        asm volatile("bar.sync 3, 352;" ::: "memory");
        const uint4 fr = lds128(sb + OFF_FR + r * 48);
        float cc[4][4] = {};
#pragma unroll
        for (int mt = 0; mt < 4; mt++) mma16816(cc[mt], ra[0][mt], fr.x, fr.y);
#pragma unroll
        for (int mt = 0; mt < 4; mt++) mma16816(cc[mt], ra[1][mt], fr.z, fr.w);
        if (t == 0) publish_partials(ppart, hm, cc, tag);
        __syncwarp();
        TS(tid == 0, 11);
    }
    uint32_t ag[4][5][4];
    const uint32_t gub = s_full + (IT_GU + 2 * (vw / 3)) * 8;
    const uint32_t gbase = sb + ((mi & 1) ? OFF_U : OFF_G) + (vw * 64 + r + 8 * (mi >> 1)) * 96 + ((c * 36) & 8) * 2;
    bool gpre;
    while (true) {
        gpre = __all_sync(0xffffffffu, mbar_test(gub) && mbar_test(gub + 8));
        if (gpre || __all_sync(0xffffffffu, mbar_test(s_empty + EM_X1 * 8))) break;
    }
    if (gpre) {
#pragma unroll
        for (int ks = 0; ks < 4; ks++)
#pragma unroll
            for (int q = 0; q < 5; q++) ldsm4t(ag[ks][q], gbase + ks * 1536 + q * 16);
        mbar_wait(s_empty + EM_X1 * 8);
    }
    bool dpre;
    const uint32_t dbar = s_full + (IT_WD + vw / 3) * 8;
    const uint32_t dgrp = sb + OFF_D + (vw / 3) * DSTR + (vw % 3) * 4608;
    const uint32_t dbase = dgrp + (r + 8 * (mi >> 1)) * 128, dsw = ((mi & 1) ^ ((r + 4 * (vw % 3)) & 7)) << 4;
    {
        uint4 v;
        int it = 0;
        const int xw = G_X1 + (vw >> 3) * 2048 + (c & (XREP - 1)) * 4096;
        const unsigned* px = scr + xw + near_half(xw, side) + (vecw & 1023);
        while (true) {
            v = ldg_rlx4(px);
            const bool more = any_lane(bad4(v, tag) & 7u);
            if (!more || ++it >= SPIN_LIMIT) break;
        }
        xw0 = hi2(v.x, v.y); xw1 = hi2(v.z, v.w);
        __syncwarp();
        ln_stage1(xw0, xw1, st2, vw, lane);
        dpre = __all_sync(0xffffffffu, mbar_test(dbar));
        bar_consumers();
        if (tid == 0) mbar_arrive(s_empty + EM_CH * 8);
        TS(tid == 0, 13);
        const LnStat ls = ln_load(st2);
        if (dpre) {
#pragma unroll
            for (int mt = 0; mt < 4; mt++) ldsm4t(ra[0][mt], dbase + (dsw ^ (mt * 32)));
#pragma unroll
            for (int mt = 0; mt < 4; mt++) ldsm4t(ra[1][mt], dbase + 2048 + (dsw ^ (mt * 32)));
        }
        uint32_t y0, y1;
        ln_stage2(ls, xw0, xw1, y0, y1);
        aw0 = badd2(bmul2(y0, sc0), sh0); aw1 = badd2(bmul2(y1, sc1), sh1);
        uint32_t bf[4][2];
        make_bfrags(bf, aw0, aw1, r);
        if (!gpre) {
            mbar_wait(gub); mbar_wait(gub + 8);
#pragma unroll
            for (int ks = 0; ks < 4; ks++)
#pragma unroll
                for (int q = 0; q < 5; q++) ldsm4t(ag[ks][q], gbase + ks * 1536 + q * 16);
        }
        float cc[5][4] = {};
#pragma unroll
        for (int ks = 0; ks < 4; ks++)
#pragma unroll
            for (int q = 0; q < 5; q++) mma16816(cc[q], ag[ks][q], bf[ks][0], bf[ks][1]);
        if (t == 0) {
#pragma unroll
            for (int q = 0; q < 5; q++) sts128f(sb + OFF_RED + vw * 640 + q * 128 + g * 16, cc[q]);
        }
        bar_consumers();
        TS(tid == 0, 14);
        if (tid < 160) {
            float sv[NCW];
#pragma unroll
            for (int w = 0; w < NCW; w++) sv[w] = ldsf(sb + OFF_RED + w * 640 + tid * 4);
            const float s = ((sv[0] + sv[1]) + (sv[2] + sv[3])) + ((sv[4] + sv[5]) + (sv[6] + sv[7])) + sv[8];
            const uint32_t gu = pack2(s, __shfl_down_sync(0xffffffffu, s, 2));
            const float gt = bflo(gu);
            const uint32_t hh = pack2(((gt > 0.f) ? gt : gt * 0.0f) * bfhi(gu), 0.f);
            const int rr = (tid >> 2) - (c & 1) * 4;
            if ((tid & 2) == 0 && rr >= 0 && rr < 36)
                sts16(sb + OFF_FR + ((tid & 1) * 4 + ((rr & 7) >> 1)) * 48 + (rr >> 3) * 4 + (rr & 1) * 2, hh);
        }
    }
    {
        uint32_t a2[4][4];
        const uint32_t b2 = dgrp + (32 + (r & 3)) * 128, sw2 = ((mi & 1) ^ (((r & 3) + 4 * (vw % 3)) & 7)) << 4;
        if (dpre) {
#pragma unroll
            for (int mt = 0; mt < 4; mt++) ldsm4t(a2[mt], b2 + (sw2 ^ (mt * 32)));
        }
        bar_consumers();
        const uint4 fr = lds128(sb + OFF_FR + r * 48);
        const uint2 f2 = lds64(sb + OFF_FR + r * 48 + 16);
        if (!dpre) {
            mbar_wait(dbar);
#pragma unroll
            for (int mt = 0; mt < 4; mt++) ldsm4t(ra[0][mt], dbase + (dsw ^ (mt * 32)));
#pragma unroll
            for (int mt = 0; mt < 4; mt++) ldsm4t(ra[1][mt], dbase + 2048 + (dsw ^ (mt * 32)));
#pragma unroll
            for (int mt = 0; mt < 4; mt++) ldsm4t(a2[mt], b2 + (sw2 ^ (mt * 32)));
        }
        float cc[4][4] = {};
#pragma unroll
        for (int mt = 0; mt < 4; mt++) mma16816(cc[mt], ra[0][mt], fr.x, fr.y);
#pragma unroll
        for (int mt = 0; mt < 4; mt++) mma16816(cc[mt], ra[1][mt], fr.z, fr.w);
#pragma unroll
        for (int mt = 0; mt < 4; mt++) mma16816(cc[mt], a2[mt], f2.x, f2.y);
        if (t == 0) publish_partials(ppart, hm, cc, tag | 4u);
        __syncwarp();
        asm volatile("bar.arrive 5, 352;" ::: "memory");
        TS(tid == 256, 15);
    }
}

typedef CUresult (*EncodeFn)(CUtensorMap*, CUtensorMapDataType, cuuint32_t, void*, const cuuint64_t*, const cuuint64_t*,
                             const cuuint32_t*, const cuuint32_t*, CUtensorMapInterleave, CUtensorMapSwizzle,
                             CUtensorMapL2promotion, CUtensorMapFloatOOBfill);

void make_map(EncodeFn enc, CUtensorMap* m, const void* p, cuuint64_t d0, cuuint64_t d1, cuuint64_t d2,
              cuuint64_t s1, cuuint64_t s2, cuuint32_t b0, cuuint32_t b1, cuuint32_t b2, CUtensorMapSwizzle sw,
              CUtensorMapL2promotion pr = CU_TENSOR_MAP_L2_PROMOTION_L2_128B) {
    cuuint64_t dims[3] = {d0, d1, d2};
    cuuint64_t str[2] = {s1, s2};
    cuuint32_t box[3] = {b0, b1, b2};
    cuuint32_t es[3] = {1, 1, 1};
    enc(m, CU_TENSOR_MAP_DATA_TYPE_BFLOAT16, 3, const_cast<void*>(p), dims, str, box, es,
        CU_TENSOR_MAP_INTERLEAVE_NONE, sw, pr, CU_TENSOR_MAP_FLOAT_OOB_FILL_NONE);
}

}

extern "C" void kernel_launch(void* const* d_in, const int* in_sizes, int n_in, void* d_out, int out_size) {
    (void)in_sizes; (void)n_in; (void)out_size;
    void* fn = nullptr;
    cudaDriverEntryPointQueryResult qr;
    cudaGetDriverEntryPoint("cuTensorMapEncodeTiled", &fn, cudaEnableDefault, &qr);
    EncodeFn enc = (EncodeFn)fn;
    cudaFuncSetAttribute(fused_block_kernel, cudaFuncAttributeMaxDynamicSharedMemorySize, SMEM_BYTES);

    const void *x = d_in[0], *kc = d_in[1], *vc = d_in[2], *wq = d_in[3], *wo = d_in[4];
    const void *wg = d_in[6], *wu = d_in[7], *wd = d_in[8], *cc = d_in[9], *wmod = d_in[10];
    const CUtensorMapSwizzle S128 = CU_TENSOR_MAP_SWIZZLE_128B, S64 = CU_TENSOR_MAP_SWIZZLE_64B, S0 = CU_TENSOR_MAP_SWIZZLE_NONE;
    void* raw = nullptr;
    cudaGetSymbolAddress(&raw, g_raw);
    unsigned* scr = (unsigned*)(((uintptr_t)raw + 0x1fffff) & ~(uintptr_t)0x1fffff);
    Maps m;
    make_map(enc, &m.m[M_K], kc, 64, 32ull * 32768, 2, 256, 128, 64, 64, 2, S128, CU_TENSOR_MAP_L2_PROMOTION_L2_256B);
    make_map(enc, &m.m[M_V], vc, 64, 32ull * 32768, 2, 256, 128, 64, 64, 2, S128, CU_TENSOR_MAP_L2_PROMOTION_L2_256B);
    make_map(enc, &m.m[M_WMOD], wmod, 3456, 144, 4, 3456 * 2, 3456 * 2 * 144, 32, 144, 2, S64);
    make_map(enc, &m.m[M_WQ], wq, 4096, 144, 4, 4096 * 2, 4096 * 2 * 144, 32, 144, 2, S64);
    make_map(enc, &m.m[M_WG], wg, 4608, 576, 1, 4608 * 2, 4608 * 2 * 576, 48, 192, 1, S0);
    make_map(enc, &m.m[M_WU], wu, 4608, 576, 1, 4608 * 2, 4608 * 2 * 576, 48, 192, 1, S0);
    make_map(enc, &m.m[M_WO], wo, 64, 4096, 9, 1152, 128, 64, 16, 9, S128);
    make_map(enc, &m.m[M_WD], wd, 64, 4608, 9, 1152, 128, 64, 36, 3, S128);
    fused_block_kernel<<<NCTA, NTHR, SMEM_BYTES>>>(m, (const __nv_bfloat16*)x, (const __nv_bfloat16*)cc,
                                                   (const __nv_bfloat16*)kc, (__nv_bfloat16*)d_out, scr TUNE_ARG);
}
```

```cpp
#include <cuda_runtime.h>
#include <cuda.h>
#include <cuda_bf16.h>
#include <stdint.h>

namespace {

constexpr int DM = 576;
constexpr int NCTA = 128;
constexpr int NCW = 9;
constexpr int NTHR = (NCW + 3) * 32;
constexpr int NMOD = 108;

#define WIN_MAIN 4
#define WIN_TAIL 3
#define WIN_SWITCH 38
#define PACE_GBS 3100
#define PACE_LEAD 28672
#define PACE_TAIL 2700
#define TAIL_GAP 250
#define PACE_D 3300
#define OPEN_WIN 1
#define DELAY_B 300
#define DELAY_D 300
#define CTL_GAIN 0
#define CTL_MAIN 57344
#define CTL_TAIL 40960
#define CTL_SWITCH 30
#define CTL_SUB 1
#define EARLY_PF 8192
#define TM_PF 1
#define XREP 2
#define PH_V 7
#define SIDE_V 11
#define NPROBE 10
#define NPROBE0 3
#define PH_K 8

#define TUNE_PARAM
#define TUNE_ARG

constexpr int IT_WMOD = 0, IT_WQ = 2, IT_K = 4, IT_V = 20, IT_WO = 36, IT_GU = 38, IT_WD = 44, N_IT = 47;
__device__ __forceinline__ constexpr int it_v(int k) { return IT_V + k; }
constexpr int EM_WMOD = 0, EM_WQ = 1, EM_K = 2, EM_V = 18, EM_PH = 34, EM_X1 = 35, EM_CH = 36, EM_SD = 37, N_EM = 38;

constexpr int RING = 13 * 16384;
constexpr int OFF_WMOD = 0, OFF_WQ = 36864, OFF_K0 = 73728;
constexpr int OFF_WO0 = 194560, OFF_WO1 = 0, OFF_G = 18432, OFF_U = 73728;
constexpr int OFF_D = 129024, DSTR = 18432;
constexpr int PSTR = 2064;
constexpr int OFF_P = RING;
constexpr int OFF_S = OFF_P + 4160;
constexpr int OFF_RED = OFF_S + 4096;
constexpr int OFF_QS = OFF_RED + 6912;
constexpr int OFF_FR = OFF_QS + 640;
constexpr int OFF_STAT = OFF_FR + 384;
constexpr int OFF_WMX = OFF_STAT + 320;
constexpr int OFF_BAR = OFF_WMX + 128;
constexpr int SMEM_USED = OFF_BAR + (N_IT + N_EM) * 8;
constexpr int SMEM_BYTES = SMEM_USED + 1024;
static_assert(SMEM_BYTES <= 232448, "smem");

struct Maps { CUtensorMap m[11]; };
enum { M_K, M_V, M_WMOD, M_WQ, M_WO, M_WG, M_WU, M_WD, M_WG48, M_WU48, M_WD48 };

constexpr int HALF = 1024;
constexpr int G_PART = 0;
constexpr int G_OP = G_PART + 144 * 2048;
constexpr int G_X1 = G_OP + 16 * 4096;
constexpr int G_PROBE = G_X1 + XREP * 4096;
constexpr int G_SIDE = G_PROBE + 2048;
constexpr int G_EPOCH = G_SIDE + 1024;
constexpr int G_MOD = G_EPOCH + 1024;
constexpr int G_Q = G_MOD + 7 * 2048;
constexpr int G_ML = G_Q + 8 * 2048;
constexpr int G_CNT = G_ML + 2048;
constexpr unsigned CNT_PER_LAUNCH = 148064;
constexpr int G_WORDS = G_CNT + 2048;
static_assert(G_MOD % 2048 == 0 && G_OP % 2048 == 0 && G_X1 % 2048 == 0 && G_PROBE % 2048 == 0, "halves");
static_assert(G_WORDS * 4 <= (2 << 20), "scratch must fit one 2 MB page");
__device__ __align__(128) unsigned g_raw[(2 << 20) / 4 + G_WORDS + 8192];
__device__ __forceinline__ int near_half(int w, unsigned side) { return ((__popc(w & 0x2C800) ^ side) & 1) << 10; }
__device__ __forceinline__ int dual(int base, int i) { return base + i + (i & ~1023); }
__device__ __forceinline__ int dual_near(int base, int i, unsigned side) { const int w = dual(base, i); return w + near_half(w, side); }
#define g_ts ((unsigned long long*)(scr + G_WORDS))

constexpr int SPIN_LIMIT = 1 << 20;

__device__ __forceinline__ uint32_t smem_u32(const void* p) { return (uint32_t)__cvta_generic_to_shared(p); }
__device__ __forceinline__ void mbar_init(uint32_t bar, int cnt) {
    asm volatile("mbarrier.init.shared::cta.b64 [%0], %1;" ::"r"(bar), "r"(cnt) : "memory");
}
__device__ __forceinline__ void mbar_expect_tx(uint32_t bar, uint32_t bytes) {
    asm volatile("mbarrier.arrive.expect_tx.shared::cta.b64 _, [%0], %1;" ::"r"(bar), "r"(bytes) : "memory");
}
__device__ __forceinline__ void mbar_arrive(uint32_t bar) {
    asm volatile("mbarrier.arrive.shared::cta.b64 _, [%0];" ::"r"(bar) : "memory");
}
__device__ __forceinline__ void mbar_wait(uint32_t bar) {
    asm volatile("{\n.reg .pred p;\nW_%=:\nmbarrier.try_wait.parity.shared::cta.b64 p, [%0], 0;\n@!p bra W_%=;\n}"
                 ::"r"(bar) : "memory");
}
__device__ __forceinline__ bool mbar_test(uint32_t bar) {
    uint32_t ok;
    asm volatile("{\n.reg .pred p;\nmbarrier.test_wait.parity.shared::cta.b64 p, [%1], 0;\nselp.u32 %0, 1, 0, p;\n}"
                 : "=r"(ok) : "r"(bar) : "memory");
    return ok;
}
__device__ __forceinline__ uint32_t gtime32() { uint32_t t; asm volatile("mov.u32 %0, %%globaltimer_lo;" : "=r"(t)); return t; }
__device__ __forceinline__ void tma3d(uint32_t dst, const CUtensorMap* m, int x, int y, int z, uint32_t bar) {
    asm volatile("cp.async.bulk.tensor.3d.shared::cluster.global.mbarrier::complete_tx::bytes [%0], [%1, {%3, %4, %5}], [%2];"
                 ::"r"(dst), "l"(m), "r"(bar), "r"(x), "r"(y), "r"(z) : "memory");
}
__device__ __forceinline__ void bar_consumers() { asm volatile("bar.sync 1, 288;" ::: "memory"); }

__device__ __forceinline__ void ldsm4(uint32_t (&a)[4], uint32_t addr) {
    asm volatile("ldmatrix.sync.aligned.m8n8.x4.shared.b16 {%0,%1,%2,%3}, [%4];"
                 : "=r"(a[0]), "=r"(a[1]), "=r"(a[2]), "=r"(a[3]) : "r"(addr) : "memory");
}
__device__ __forceinline__ void ldsm4t(uint32_t (&a)[4], uint32_t addr) {
    asm volatile("ldmatrix.sync.aligned.m8n8.x4.trans.shared.b16 {%0,%1,%2,%3}, [%4];"
                 : "=r"(a[0]), "=r"(a[1]), "=r"(a[2]), "=r"(a[3]) : "r"(addr) : "memory");
}
__device__ __forceinline__ void mma16816(float (&c)[4], const uint32_t (&a)[4], uint32_t b0, uint32_t b1) {
    asm volatile("mma.sync.aligned.m16n8k16.row.col.f32.bf16.bf16.f32 {%0,%1,%2,%3}, {%4,%5,%6,%7}, {%8,%9}, {%0,%1,%2,%3};"
                 : "+f"(c[0]), "+f"(c[1]), "+f"(c[2]), "+f"(c[3])
                 : "r"(a[0]), "r"(a[1]), "r"(a[2]), "r"(a[3]), "r"(b0), "r"(b1));
}
__device__ __forceinline__ float ldsf(uint32_t a) { float v; asm volatile("ld.shared.f32 %0, [%1];" : "=f"(v) : "r"(a) : "memory"); return v; }
__device__ __forceinline__ uint2 lds64(uint32_t a) {
    uint2 v; asm volatile("ld.shared.v2.u32 {%0,%1}, [%2];" : "=r"(v.x), "=r"(v.y) : "r"(a) : "memory"); return v;
}
__device__ __forceinline__ uint4 lds128(uint32_t a) {
    uint4 v; asm volatile("ld.shared.v4.u32 {%0,%1,%2,%3}, [%4];" : "=r"(v.x), "=r"(v.y), "=r"(v.z), "=r"(v.w) : "r"(a) : "memory"); return v;
}
__device__ __forceinline__ void sts16(uint32_t a, uint32_t v) { asm volatile("st.shared.u16 [%0], %1;" ::"r"(a), "h"((unsigned short)v) : "memory"); }
__device__ __forceinline__ void sts32(uint32_t a, uint32_t v) { asm volatile("st.shared.u32 [%0], %1;" ::"r"(a), "r"(v) : "memory"); }
__device__ __forceinline__ void sts64(uint32_t a, uint32_t x, uint32_t y) { asm volatile("st.shared.v2.u32 [%0], {%1,%2};" ::"r"(a), "r"(x), "r"(y) : "memory"); }
__device__ __forceinline__ void sts128(uint32_t a, uint32_t x, uint32_t y, uint32_t z, uint32_t w) {
    asm volatile("st.shared.v4.u32 [%0], {%1,%2,%3,%4};" ::"r"(a), "r"(x), "r"(y), "r"(z), "r"(w) : "memory");
}
__device__ __forceinline__ void sts128f(uint32_t a, const float (&c)[4]) {
    asm volatile("st.shared.v4.f32 [%0], {%1,%2,%3,%4};" ::"r"(a), "f"(c[0]), "f"(c[1]), "f"(c[2]), "f"(c[3]) : "memory");
}
__device__ __forceinline__ unsigned ldg_rlx1(const unsigned* p) {
    unsigned v; asm volatile("ld.relaxed.gpu.global.u32 %0, [%1];" : "=r"(v) : "l"(p) : "memory"); return v;
}
__device__ __forceinline__ uint4 ldg_rlx4(const unsigned* p) {
    uint4 v; asm volatile("ld.relaxed.gpu.global.v4.u32 {%0,%1,%2,%3}, [%4];" : "=r"(v.x), "=r"(v.y), "=r"(v.z), "=r"(v.w) : "l"(p) : "memory"); return v;
}
__device__ __forceinline__ uint4 ldg_pkt(const unsigned* p) {
    uint4 v;
    asm volatile("{\n.reg .b128 t;\n.reg .b64 lo, hi;\nld.relaxed.gpu.global.b128 t, [%4];\nmov.b128 {lo, hi}, t;\n"
                 "mov.b64 {%0,%1}, lo;\nmov.b64 {%2,%3}, hi;\n}"
                 : "=r"(v.x), "=r"(v.y), "=r"(v.z), "=r"(v.w) : "l"(p) : "memory");
    return v;
}
__device__ __forceinline__ void ldg_pkt_if(uint4& v, const unsigned* a, unsigned p) {
    asm volatile("{\n.reg .pred q;\n.reg .b128 t;\n.reg .b64 lo, hi;\nsetp.ne.u32 q, %5, 0;\n"
                 "mov.b64 lo, {%0,%1};\nmov.b64 hi, {%2,%3};\nmov.b128 t, {lo, hi};\n"
                 "@q ld.relaxed.gpu.global.b128 t, [%4];\nmov.b128 {lo, hi}, t;\n"
                 "mov.b64 {%0,%1}, lo;\nmov.b64 {%2,%3}, hi;\n}"
                 : "+r"(v.x), "+r"(v.y), "+r"(v.z), "+r"(v.w) : "l"(a), "r"(p) : "memory");
}
__device__ __forceinline__ bool any_lane(unsigned x) { return __any_sync(0xffffffffu, x != 0); }
__device__ __forceinline__ void stg_pkt(unsigned* p, float a, float b, float c, float d, unsigned tag) {
    unsigned x = (__float_as_uint(a) & ~7u) | tag;
    asm volatile("{\n.reg .b128 t;\n.reg .b64 lo, hi;\nmov.b64 lo, {%1,%2};\nmov.b64 hi, {%3,%4};\nmov.b128 t, {lo, hi};\n"
                 "st.relaxed.gpu.global.b128 [%0], t;\n}"
                 ::"l"(p), "r"(x), "r"(__float_as_uint(b)), "r"(__float_as_uint(c)), "r"(__float_as_uint(d)) : "memory");
}
__device__ __forceinline__ void stg_rlx1(unsigned* p, unsigned x) { asm volatile("st.relaxed.gpu.global.u32 [%0], %1;" ::"l"(p), "r"(x) : "memory"); }
__device__ __forceinline__ unsigned bad4(const uint4& v, unsigned tag) {
    return ((v.x ^ tag) | (v.y ^ tag)) | ((v.z ^ tag) | (v.w ^ tag));
}
__device__ __forceinline__ float untagf(unsigned w) { return __uint_as_float(w & ~7u); }
__device__ __forceinline__ uint32_t pack2(float lo, float hi) {
    uint32_t r; asm("cvt.rn.bf16x2.f32 %0, %1, %2;" : "=r"(r) : "f"(hi), "f"(lo)); return r;
}
__device__ __forceinline__ float bflo(uint32_t w) { return __uint_as_float(w << 16); }
__device__ __forceinline__ float bfhi(uint32_t w) { return __uint_as_float(w & 0xffff0000u); }
__device__ __forceinline__ uint32_t hi2(uint32_t a, uint32_t b) { return __byte_perm(a, b, 0x7632); }
__device__ __forceinline__ uint32_t badd2(uint32_t a, uint32_t b) { uint32_t r; asm("add.rn.bf16x2 %0, %1, %2;" : "=r"(r) : "r"(a), "r"(b)); return r; }
__device__ __forceinline__ uint32_t bsub2(uint32_t a, uint32_t b) { uint32_t r; asm("sub.rn.bf16x2 %0, %1, %2;" : "=r"(r) : "r"(a), "r"(b)); return r; }
__device__ __forceinline__ uint32_t bmul2(uint32_t a, uint32_t b) { uint32_t r; asm("mul.rn.bf16x2 %0, %1, %2;" : "=r"(r) : "r"(a), "r"(b)); return r; }
__device__ __forceinline__ uint32_t bmax2(uint32_t a, uint32_t b) { uint32_t r; asm("max.bf16x2 %0, %1, %2;" : "=r"(r) : "r"(a), "r"(b)); return r; }
__device__ __forceinline__ float ex2(float x) { float r; asm("ex2.approx.ftz.f32 %0, %1;" : "=f"(r) : "f"(x)); return r; }
__device__ __forceinline__ float rcp(float x) { float r; asm("rcp.approx.ftz.f32 %0, %1;" : "=f"(r) : "f"(x)); return r; }
__device__ __forceinline__ float fsqrt(float x) { float r; asm("sqrt.approx.ftz.f32 %0, %1;" : "=f"(r) : "f"(x)); return r; }
__device__ __forceinline__ float shx(float v, int m) { return __shfl_xor_sync(0xffffffffu, v, m); }
#define TS(cond, slot) do { } while (0)

__device__ __forceinline__ uint32_t k_off(int i) { return i < 8 ? OFF_K0 + i * 16384 : (i - 8) * 16384; }
__device__ __forceinline__ uint32_t v_off(int i) { return i < 5 ? (8 + i) * 16384 : (i - 5) * 16384; }

__device__ __forceinline__ void stg_ph(unsigned* p) { stg_pkt(p, 0.f, 0.f, 0.f, 0.f, 2u); }

__device__ __forceinline__ void ln_stage1(uint32_t xw0, uint32_t xw1, uint32_t st, int vw, int lane) {
    const float piv = __shfl_sync(0xffffffffu, bflo(xw0), lane & 4);
    const float d0 = bflo(xw0) - piv, d1 = bfhi(xw0) - piv, d2 = bflo(xw1) - piv, d3 = bfhi(xw1) - piv;
    float s1 = (d0 + d1) + (d2 + d3), s2 = (d0 * d0 + d1 * d1) + (d2 * d2 + d3 * d3);
    s1 += shx(s1, 1); s2 += shx(s2, 1);
    s1 += shx(s1, 2); s2 += shx(s2, 2);
    s1 += shx(s1, 8); s2 += shx(s2, 8);
    s1 += shx(s1, 16); s2 += shx(s2, 16);
    if ((lane & 27) == 0)
        sts64(st + vw * 8, __float_as_uint(piv + s1 * (1.0f / 64.0f)), __float_as_uint(s2 - s1 * s1 * (1.0f / 64.0f)));
}
struct LnStat { uint4 a, b, c, d; uint2 e; };
__device__ __forceinline__ LnStat ln_load(uint32_t st) {
    LnStat s; s.a = lds128(st); s.b = lds128(st + 16); s.c = lds128(st + 32); s.d = lds128(st + 48); s.e = lds64(st + 64);
    return s;
}
__device__ __forceinline__ void ln_stage2(const LnStat& s, uint32_t xw0, uint32_t xw1, uint32_t& y0, uint32_t& y1) {
    const float m[9] = {__uint_as_float(s.a.x), __uint_as_float(s.a.z), __uint_as_float(s.b.x), __uint_as_float(s.b.z),
                        __uint_as_float(s.c.x), __uint_as_float(s.c.z), __uint_as_float(s.d.x), __uint_as_float(s.d.z), __uint_as_float(s.e.x)};
    const float mean = (((m[0] + m[1]) + (m[2] + m[3])) + ((m[4] + m[5]) + (m[6] + m[7])) + m[8]) * (1.0f / NCW);
    const float m2 = ((__uint_as_float(s.a.y) + __uint_as_float(s.a.w)) + (__uint_as_float(s.b.y) + __uint_as_float(s.b.w))) +
                     ((__uint_as_float(s.c.y) + __uint_as_float(s.c.w)) + (__uint_as_float(s.d.y) + __uint_as_float(s.d.w))) + __uint_as_float(s.e.y);
    float d[9];
#pragma unroll
    for (int w = 0; w < 9; w++) d[w] = m[w] - mean;
    const float acc = (d[0] * d[0] + d[1] * d[1] + d[2] * d[2]) + (d[3] * d[3] + d[4] * d[4] + d[5] * d[5]) + (d[6] * d[6] + d[7] * d[7] + d[8] * d[8]);
    const float var = (m2 + 64.0f * acc) * (1.0f / DM);
    const uint32_t mv = pack2(mean, var);
    const float ve = bflo(pack2(bfhi(mv) + 1e-5f, 0.f));
    const float rinv = rcp(bflo(pack2(fsqrt(ve), 0.f)));
    const uint32_t mm = __byte_perm(mv, mv, 0x1010);
    const uint32_t e0 = bsub2(xw0, mm), e1 = bsub2(xw1, mm);
    y0 = pack2(bflo(e0) * rinv, bfhi(e0) * rinv); y1 = pack2(bflo(e1) * rinv, bfhi(e1) * rinv);
}
__device__ __forceinline__ void make_bfrags(uint32_t (&bf)[4][2], uint32_t aw0, uint32_t aw1, int r) {
#pragma unroll
    for (int ks = 0; ks < 4; ks++) {
        bf[ks][0] = __shfl_sync(0xffffffffu, aw0, ks * 8 + r);
        bf[ks][1] = __shfl_sync(0xffffffffu, aw1, ks * 8 + r);
    }
}
__device__ __forceinline__ uint32_t gemv32(uint32_t s_w, uint32_t red, uint32_t fullbar, uint32_t emptybar,
                                           uint32_t aw0, uint32_t aw1, int tid) {
    const int vw = tid >> 5, lane = tid & 31, g = lane >> 2, t = lane & 3, mi = lane >> 3, r = lane & 7;
    uint32_t bf[4][2];
    make_bfrags(bf, aw0, aw1, r);
    if (vw <= 4) mbar_wait(fullbar);
    if (vw >= 4) mbar_wait(fullbar + 8);
    float cc[2][4] = {};
    const uint32_t abase = s_w + (vw * 64 + r + 8 * (mi >> 1)) * 64;
    const uint32_t sw = ((mi & 1) ^ (r >> 1)) << 4;
#pragma unroll
    for (int ks = 0; ks < 4; ks++) {
#pragma unroll
        for (int mt = 0; mt < 2; mt++) {
            uint32_t a[4];
            ldsm4t(a, abase + ks * 1024 + (sw ^ (mt * 32)));
            mma16816(cc[mt], a, bf[ks][0], bf[ks][1]);
        }
    }
    if (t == 0) { sts128f(red + vw * 256 + g * 16, cc[0]); sts128f(red + vw * 256 + 128 + g * 16, cc[1]); }
    __syncwarp();
    if (lane == 0) mbar_arrive(emptybar);
    bar_consumers();
    float s = 0.f;
    if (tid < 64) {
        const uint32_t ra = red + ((tid & 58) | ((tid & 1) << 2) | ((tid >> 2) & 1)) * 4;
#pragma unroll
        for (int w = 0; w < NCW; w++) s += ldsf(ra + w * 256);
    }
    return pack2(0.f, s);
}
__device__ __forceinline__ void publish_partials(unsigned* q, unsigned hm, const float (&cc)[4][4], unsigned tag) {
#pragma unroll
    for (int mt = 0; mt < 4; mt++)
        stg_pkt(q + mt * 4 * 2048 + ((hm >> (4 * mt)) & 1) * HALF, cc[mt][0], cc[mt][1], cc[mt][2], cc[mt][3], tag);
}
__device__ __forceinline__ void spin_cycles(unsigned n) {
    const unsigned c0 = clock();
    while ((unsigned)clock() - c0 < n) { }
}
__device__ __forceinline__ float reduce_unit(const unsigned* q, int lane, unsigned tag) {
    uint4 v[8];
#pragma unroll
    for (int i = 0; i < 8; i++) v[i] = ldg_pkt(q + i * 128);
    int it = 0;
    while (true) {
        unsigned bad = 0;
#pragma unroll
        for (int i = 0; i < 8; i += 2) bad |= (v[i].x ^ tag) | (v[i + 1].x ^ tag);
        if (!any_lane(bad & 7u) || ++it >= SPIN_LIMIT) break;
#pragma unroll
        for (int i = 0; i < 8; i++) ldg_pkt_if(v[i], q + i * 128, (v[i].x ^ tag) & 7u);
    }
    float s0 = 0.f, s1 = 0.f, s2 = 0.f, s3 = 0.f, u0 = 0.f, u1 = 0.f, u2 = 0.f, u3 = 0.f;
#pragma unroll
    for (int i = 0; i < 8; i += 2) {
        s0 += untagf(v[i].x); s1 += __uint_as_float(v[i].y); s2 += __uint_as_float(v[i].z); s3 += __uint_as_float(v[i].w);
        u0 += untagf(v[i + 1].x); u1 += __uint_as_float(v[i + 1].y); u2 += __uint_as_float(v[i + 1].z); u3 += __uint_as_float(v[i + 1].w);
    }
    s0 += u0; s1 += u1; s2 += u2; s3 += u3;
    __syncwarp();
    const bool h8 = lane & 2, bat = lane & 4;
    const float k0 = (h8 ? s2 : s0) + shx(h8 ? s0 : s2, 2);
    const float k1 = (h8 ? s3 : s1) + shx(h8 ? s1 : s3, 2);
    float k = (bat ? k1 : k0) + shx(bat ? k0 : k1, 4);
    k += shx(k, 8);
    k += shx(k, 16);
    return k;
}

__global__ void __launch_bounds__(NTHR, 1)
fused_block_kernel(const __grid_constant__ Maps maps, const __nv_bfloat16* __restrict__ xin,
                   const __nv_bfloat16* __restrict__ cin, const __nv_bfloat16* __restrict__ kcache,
                   __nv_bfloat16* __restrict__ out, unsigned* const scr TUNE_PARAM) {
    extern __shared__ unsigned char smem_raw[];
    const int c = blockIdx.x;
    const int kvh = c >> 3, j = c & 7, bb = j & 1, sp = j >> 1;
    const bool wide = j >= 6;
    const int f0 = kvh * 288 + (wide ? 48 * j - 96 : 32 * j);
    const int kvrow0 = (bb * 16 + kvh) * 32768 + 28672 + sp * 1024;
    if (EARLY_PF && threadIdx.x == 0)
        asm volatile("cp.async.bulk.prefetch.L2.global [%0], %1;" ::"l"((const char*)kcache + (size_t)kvrow0 * 256), "r"(EARLY_PF) : "memory");
    TS(threadIdx.x == 0, 0);
    const uint32_t sb = (smem_u32(smem_raw) + 1023u) & ~1023u;
    const int warp = threadIdx.x >> 5, lane = threadIdx.x & 31;
    const uint32_t s_full = sb + OFF_BAR, s_empty = s_full + N_IT * 8;

    if (warp == NCW) {
        uint32_t t0 = gtime32();
        const int first = (c < NMOD) ? 0 : 2;
        if (lane == 0) {
#pragma unroll
            for (int i = 0; i < 2; i++) mbar_init(s_full + (first + i) * 8, 1);
            asm volatile("fence.proxy.async.shared::cta;" ::: "memory");
#pragma unroll
            for (int i = 0; i < 2; i++) {
                const uint32_t bar = s_full + (first + i) * 8;
                mbar_expect_tx(bar, 18432);
                tma3d(sb + (first + i) * 18432, &maps.m[M_WMOD + (first >> 1)], c * 32, 0, i * 2, bar);
            }
            TS(true, 17);
        }
        __syncwarp();
        const unsigned cbase = ldg_rlx1(scr + G_EPOCH) * CNT_PER_LAUNCH;
        uint32_t w0[2], w1[2], w2[2];
#pragma unroll
        for (int h = 0; h < 2; h++) {
            const int i = lane + 32 * h;
            int off, map, dep = -1, x = 0, y = 0, z = 0, sz = 36, cum;
            if (i < IT_K) {
                off = i * 18432; map = M_WMOD + (i >> 1); x = c * 32; z = (i & 1) * 2; cum = 31104 + (i - 2) * 18432;
            } else if (i < IT_V) {
                const int k = i - IT_K;
                off = k_off(k); map = M_K; y = kvrow0 + k * 64; sz = 32; cum = 67968 + k * 16384;
                if (k == 8 && c < NMOD) dep = EM_WMOD;
                if (k == 10) dep = EM_WQ;
                if (k >= 12) dep = EM_K + k - 12;
            } else if (i < IT_WO) {
                const int k = i - IT_V;
                off = v_off(k); map = M_V; y = kvrow0 + k * 64; sz = 32; cum = 330112 + k * 16384;
                dep = EM_K + 3 + k + (k < 4);
            } else if (i < IT_GU) {
                const int k = i - IT_WO;
                off = k ? OFF_WO1 : OFF_WO0; map = M_WO; y = kvh * 256 + k * 128 + j * 16; dep = EM_V + 4 + 2 * k;
                cum = 592256 + k * 18432;
            } else if (i < IT_WD) {
                const int k = i - IT_GU;
                sz = wide ? 36 : 24;
                off = ((k & 1) ? OFF_U : OFF_G) + (k >> 1) * sz * 512; map = M_WG + (k & 1) + (wide ? 3 : 0);
                x = f0; y = (k >> 1) * 192; dep = EM_V + 5 + ((off + sz * 512 - 1) >> 14);
                cum = 629120 + k * 13824;
            } else {
                const int k = i - IT_WD;
                off = OFF_D + k * DSTR; map = wide ? M_WD48 : M_WD; y = f0; z = k * 3; sz = wide ? 36 : 24; dep = EM_V + (k ? 15 : 13);
                cum = 712064 + k * 13824;
            }
            const int stag = ((c * 37) & 127) * 128;
            cum += EARLY_PF - min(max(cum - 67968, 0), EARLY_PF);
            int due = (int)((float)max(min(cum, 629120) + stag - PACE_LEAD, 0) * (128.0f / PACE_GBS));
            if (i >= IT_GU) due += TAIL_GAP + (int)((float)(min(cum, 712064) - 629120) * (128.0f / PACE_TAIL));
            if (i >= IT_WD) due += (int)((float)(cum - 712064) * (128.0f / PACE_D));
            w0[h] = off | (map << 18) | ((dep + 1) << 22) | (z << 28);
            w1[h] = y | (sz << 24);
            w2[h] = x | (due << 13);
        }
        asm volatile("bar.sync 2, 384;" ::: "memory");
        int obs = first;
        const unsigned* pcnt = scr + G_CNT;
        bool have_side = false;
        unsigned cv = cbase;
        uint32_t ts = t0;
#pragma unroll 1
        for (int i = first + 2; i < N_IT; i++) {
            const bool hi = i >= 32;
            const uint32_t a = __shfl_sync(0xffffffffu, hi ? w0[1] : w0[0], i);
            const uint32_t b = __shfl_sync(0xffffffffu, hi ? w1[1] : w1[0], i);
            const uint32_t x = __shfl_sync(0xffffffffu, hi ? w2[1] : w2[0], i);
            if (lane == 0) {
                const int prev = i - ((i >= WIN_SWITCH) ? WIN_TAIL : WIN_MAIN);
                const int dep = (a >> 22) & 63;
                if (have_side) {
                    const float backlog_ns = (float)(int)(ts - t0) - (float)(cv - cbase) * (512.0f / PACE_GBS);
                    const float target_ns = (float)((i >= CTL_SWITCH ? CTL_TAIL : CTL_MAIN) - PACE_LEAD) * (128.0f / PACE_GBS);
                    t0 += max((int)((backlog_ns - target_ns) * (CTL_GAIN * 0.01f)), 0);
                    if (i >= IT_GU) have_side = false;
                } else if (CTL_GAIN && i >= 8 && i < 20 && mbar_test(s_empty + EM_SD * 8)) {
                    have_side = true;
                    pcnt += near_half(G_CNT, __float_as_uint(ldsf(sb + OFF_WMX + 116)));
                }
                if (have_side) { cv = ldg_rlx1(pcnt); ts = gtime32(); }
                while (true) {
                    if (obs < i && mbar_test(s_full + obs * 8)) {
                        if (CTL_GAIN && obs < IT_WO && (c % CTL_SUB) == 0) {
                            const unsigned u = (obs < IT_K ? 36 : 32) * CTL_SUB;
                            asm volatile("red.relaxed.gpu.global.add.u32 [%0], %1;" ::"l"(scr + G_CNT), "r"(u) : "memory");
                            asm volatile("red.relaxed.gpu.global.add.u32 [%0], %1;" ::"l"(scr + G_CNT + HALF), "r"(u) : "memory");
                        }
                        obs++;
                    }
                    if (dep && !mbar_test(s_empty + (dep - 1) * 8)) continue;
                    if (OPEN_WIN && mbar_test(s_empty + EM_CH * 8)) break;
                    if (obs > prev && (int)(gtime32() - t0) >= (int)(x >> 13)) break;
                }
                if (i < N_IT) {
                    const uint32_t bar = s_full + i * 8;
                    mbar_expect_tx(bar, (b >> 24) * 512);
                    tma3d(sb + (a & 0x3ffff), &maps.m[(a >> 18) & 15], x & 0x1fff, b & 0xffffff, a >> 28, bar);
                }
                TS(i == IT_WO, 1);
                TS(i == N_IT - 1, 2);
            }
            __syncwarp();
        }
        return;
    }

    const int g = lane >> 2, t = lane & 3, mi = lane >> 3, r = lane & 7;
    const int bat = g & 1;

    if (warp > NCW) {
        const bool first = warp == NCW + 1, active = first || c < 16;
        const int unit = first ? c : NCTA + c;
        const int rcol = (unit >> 2) * 16 + (unit & 3) * 2 + (lane & 1) + (lane & 2) * 4 + bat * DM;
        const unsigned ep = ldg_rlx1(scr + G_EPOCH);
        uint32_t xold = 0, ga = 0, gb = 0;
        if (active) xold = __ldg((const unsigned short*)xin + rcol);
        if (!first) asm volatile("bar.sync 2, 384;" ::: "memory");
        const unsigned tag = (ep + 1u) & 1u;
        unsigned side = 0;
        const int x1w = G_X1 + (unit >> 7) * 2048 + (unit & 127) * 8 + r + (lane & 8) * (HALF / 8) + (lane >> 4) * 4096;
        if (first) {
            unsigned* pr = scr + G_PROBE + c * 8;
            if (lane < 16) stg_rlx1(pr + r + (lane & 8) * (HALF / 8), 0u);
            __syncwarp();
            asm volatile("bar.arrive 2, 384;" ::: "memory");
            unsigned best0 = ~0u, best1 = ~0u, v = 0, cp = 0;
#pragma unroll 1
            for (int i = 0; i <= 2 * NPROBE; i++) {
                if (lane == 0) {
                    asm volatile("atom.relaxed.gpu.global.add.u32 %0, [%1], 1;" : "=r"(v) : "l"(pr + (i & 1) * HALF + (v >> 31)) : "memory");
                    const unsigned cn = clock(), d = cn - cp;
                    cp = cn;
                    if (i & 1) best0 = min(best0, d); else if (i) best1 = min(best1, d);
                    side = (best1 < best0) ^ (__popc(G_PROBE & 0x2C800) & 1);
                }
                if (i == 2 * NPROBE0) {
                    asm volatile("bar.sync 6, 64;" ::: "memory");
                    if (lane == 0) { sts32(sb + OFF_WMX + 116, side); mbar_arrive(s_empty + EM_SD * 8); }
                }
            }
            if (lane == 0) sts32(sb + OFF_WMX + 112, side);
            side = __shfl_sync(0xffffffffu, side, 0);
            mbar_wait(s_full + it_v(PH_V) * 8);
#pragma unroll 1
            for (int u = c; u < 144; u += NCTA) {
                unsigned* q = scr + G_PART + u * 2048 + near_half(G_PART + u * 2048, side) + lane * 4;
#pragma unroll
                for (int i = 0; i < 8; i++) stg_ph(q + i * 128);
#pragma unroll
                for (int i = 0; i < XREP; i += 2) stg_rlx1(scr + x1w + (u >> 7) * 2048 + i * 4096, 2u);
            }
            unsigned* o = scr + G_OP + kvh * 4096 + (j >> 2) * 2048 + (j & 3) * 256 + lane * 4;
            stg_ph(o); stg_ph(o + 128); stg_ph(o + HALF); stg_ph(o + HALF + 128);
            __threadfence();
            __syncwarp();
            if (lane < 8) stg_rlx1(scr + G_SIDE + c * 8 + lane, (side << 4) | tag);
            if (lane == 0) mbar_arrive(s_empty + EM_PH * 8);
        } else {
            asm volatile("bar.arrive 6, 64;" ::: "memory");
            if (TM_PF && lane < 8) asm volatile("prefetch.tensormap [%0];" ::"l"(&maps.m[lane + ((wide && lane >= M_WG) ? 3 : 0)]) : "memory");
            mbar_wait(s_empty + EM_PH * 8);
            side = __float_as_uint(ldsf(sb + OFF_WMX + 112));
        }
        if (active) {
            int it = 0;
            do {
                ga = ldg_rlx1(scr + dual_near(G_MOD, 2 * 1152 + unit * 8 + r, side));
                gb = ldg_rlx1(scr + dual_near(G_MOD, 5 * 1152 + unit * 8 + r, side));
            } while (any_lane(((ga ^ tag) | (gb ^ tag)) & 7u) && ++it < SPIN_LIMIT);
            ga >>= 16; gb >>= 16;
        }
        __syncwarp();
        if (first) {
            const int ow = G_OP + kvh * 4096 + (g >> 2) * 2048;
            const unsigned* q = scr + ow + near_half(ow, side) + (g & 3) * 256 + j * 32 + t * 8;
            mbar_wait(s_full + it_v(15) * 8);
            uint4 lo, hi;
            int it = 0;
            do { lo = ldg_pkt(q); hi = ldg_pkt(q + 4); } while (any_lane(((lo.x ^ tag) | (hi.x ^ tag)) & 7u) && ++it < SPIN_LIMIT);
            float o[8] = {untagf(lo.x), __uint_as_float(lo.y), __uint_as_float(lo.z), __uint_as_float(lo.w),
                          untagf(hi.x), __uint_as_float(hi.y), __uint_as_float(hi.z), __uint_as_float(hi.w)};
            __syncwarp();
#pragma unroll
            for (int sft = 8; sft <= 16; sft <<= 1) {
#pragma unroll
                for (int i = 0; i < 8; i++) o[i] += shx(o[i], sft);
            }
            if (lane < 8)
                sts128(sb + OFF_FR + lane * 48, pack2(o[0], o[4]), pack2(o[2], o[6]), pack2(o[1], o[5]), pack2(o[3], o[7]));
            TS(lane == 0, 10);
        }
        asm volatile("bar.sync 3, 352;" ::: "memory");
        const unsigned* q = scr + G_PART + unit * 2048 + near_half(G_PART + unit * 2048, side) + lane * 4;
        if (DELAY_B) spin_cycles(DELAY_B);
        if (active) {
            const float k = reduce_unit(q, lane, tag);
            xold = badd2(xold, bmul2(ga, pack2(k, 0.f))) & 0xffffu;
#pragma unroll
            for (int i = 0; i < XREP; i += 2) stg_rlx1(scr + x1w + i * 4096, (xold << 16) | tag);
            TS(first && lane == 0, 12);
            TS(!first && lane == 0, 18);
        }
        if (first && lane == 0) mbar_arrive(s_empty + EM_X1 * 8);
        asm volatile("bar.sync 5, 352;" ::: "memory");
        if (active) {
            if (DELAY_D) spin_cycles(DELAY_D);
            const float k = reduce_unit(q, lane, tag | 4u);
            xold = badd2(xold, bmul2(gb, pack2(k, 0.f)));
            if (lane < 8) ((unsigned short*)out)[rcol] = (unsigned short)xold;
            if (c == 0 && first && lane == 0) stg_rlx1(scr + G_EPOCH, ep + 1u);
            TS(first && lane == 0, 16);
        }
        return;
    }

    const int vw = warp, tid = threadIdx.x;
    const int vecw = tid * 4 - (lane & 7) * 4 + t * 8 + bat * 4;
    unsigned* const ppart = scr + G_PART + (vw * 16 + (g >> 1)) * 2048 + c * 8 + bat * 4;
    const unsigned* const pside = scr + G_SIDE + ((vw * 16 + (lane & 15)) & 127) * 8;
    const int qword = dual(G_Q, bat * 4096 + c * 32 + (tid >> 3) * 4 + t), mword = dual(G_MOD, c * 64 + (tid & 63));
    const uint32_t one2 = 0x3f803f80u;

    const unsigned ep = ldg_rlx1(scr + G_EPOCH);
    if (tid < 64) {
        if (c < NMOD) { stg_rlx1(scr + mword, 2u); stg_rlx1(scr + mword + HALF, 2u); }
        stg_rlx1(scr + qword, 2u); stg_rlx1(scr + qword + HALF, 2u);
    }
    uint32_t xw0, xw1, aw0, aw1;
    {
        const int col0 = bat * DM + (vw * 4 + mi) * 16 + 2 * t;
        const uint32_t cw0 = __ldg((const unsigned*)(cin + col0)), cw1 = __ldg((const unsigned*)(cin + col0 + 8));
        xw0 = __ldg((const unsigned*)(xin + col0)); xw1 = __ldg((const unsigned*)(xin + col0 + 8));
        if (lane == 0) {
            const int lo = (c < NMOD) ? 2 : 4;
#pragma unroll 1
            for (int i = vw; i < N_IT + N_EM; i += NCW) {
                const int e = i - N_IT;
                if (i >= lo) mbar_init(s_full + i * 8, (e < 0 || e >= EM_PH) ? 1 : (e < EM_K ? NCW : (e < EM_V ? 4 : 8)));
            }
            asm volatile("fence.proxy.async.shared::cta;" ::: "memory");
        }
        __syncwarp();
        asm volatile("bar.sync 2, 384;" ::: "memory");
        float cv[4] = {bflo(cw0), bfhi(cw0), bflo(cw1), bfhi(cw1)};
#pragma unroll
        for (int i = 0; i < 4; i++) cv[i] = cv[i] * rcp(1.0f + ex2(-1.4426950408889634f * cv[i]));
        aw0 = pack2(cv[0], cv[1]); aw1 = pack2(cv[2], cv[3]);
    }
    const unsigned tag = (ep + 1u) & 1u;
    const uint32_t st1 = sb + OFF_STAT + bat * 80, st2 = st1 + 160;
    ln_stage1(xw0, xw1, st1, vw, lane);

    if (c < NMOD) {
        const uint32_t m = gemv32(sb + OFF_WMOD, sb + OFF_RED, s_full + IT_WMOD * 8, s_empty + EM_WMOD * 8, aw0, aw1, tid);
        if (tid < 64) { stg_rlx1(scr + mword, m | tag); stg_rlx1(scr + mword + HALF, m | tag); }
    } else {
        bar_consumers();
    }
    TS(tid == 0, 4);
    mbar_wait(s_empty + EM_SD * 8);
    unsigned side = __float_as_uint(ldsf(sb + OFF_WMX + 116));
    {
        uint32_t y0, y1;
        ln_stage2(ln_load(st1), xw0, xw1, y0, y1);
        uint4 a, b;
        int it = 0;
        const unsigned *pa = scr + dual_near(G_MOD, vecw, side), *pb = scr + dual_near(G_MOD, 1152 + vecw, side);
        do { a = ldg_rlx4(pa); b = ldg_rlx4(pb); }
        while (any_lane((bad4(a, tag) | bad4(b, tag)) & 7u) && ++it < SPIN_LIMIT);
        __syncwarp();
        aw0 = badd2(bmul2(y0, badd2(one2, hi2(b.x, b.y))), hi2(a.x, a.y));
        aw1 = badd2(bmul2(y1, badd2(one2, hi2(b.z, b.w))), hi2(a.z, a.w));
        TS(tid == 0, 5);
        const uint32_t q = gemv32(sb + OFF_WQ, sb + OFF_RED + 2304, s_full + IT_WQ * 8, s_empty + EM_WQ * 8, aw0, aw1, tid);
        if (tid < 64) {
            stg_rlx1(scr + qword, q | tag); stg_rlx1(scr + qword + HALF, q | tag);
            uint4 v;
            int it = 0;
            const unsigned* pq = scr + dual_near(G_Q, bb * 4096 + kvh * 256 + tid * 4, side);
            do { v = ldg_rlx4(pq); } while (any_lane(bad4(v, tag) & 7u) && ++it < SPIN_LIMIT);
            sts64(sb + OFF_QS + (vw * 4 + t) * 80 + g * 8, hi2(v.x, v.y), hi2(v.z, v.w));
        }
        bar_consumers();
        TS(tid == 0, 6);
    }
    uint32_t sc0, sc1, sh0, sh1;
    {
        uint4 d, e;
        unsigned bad;
        int it = 0;
        do {
            d = ldg_rlx4(scr + dual_near(G_MOD, 3 * 1152 + vecw, side)); e = ldg_rlx4(scr + dual_near(G_MOD, 4 * 1152 + vecw, side));
            bad = bad4(d, tag) | bad4(e, tag);
        } while (any_lane(bad & 7u) && ++it < SPIN_LIMIT);
        __syncwarp();
        sh0 = hi2(d.x, d.y); sh1 = hi2(d.z, d.w);
        sc0 = badd2(one2, hi2(e.x, e.y)); sc1 = badd2(one2, hi2(e.z, e.w));
    }
    if (vw < 8) {
        uint4 qf[4];
#pragma unroll
        for (int i = 0; i < 4; i++) qf[i] = lds128(sb + OFF_QS + r * 80 + i * 16);
        const int mt = vw & 3;
        const uint32_t rowoff = (mt * 16 + r + 8 * (mi & 1)) * 128;
        const uint32_t sw = ((mi >> 1) ^ r) << 4;
        uint32_t mx = 0xff80ff80u;
#pragma unroll 1
        for (int i = (vw >> 2); i < 16; i += 2) {
            mbar_wait(s_full + (IT_K + i) * 8);
            const uint32_t base = sb + k_off(i) + rowoff;
            float c0[4] = {}, c1[4] = {};
            uint32_t a[4];
            ldsm4(a, base + sw);               mma16816(c0, a, qf[0].x, qf[0].y);
            ldsm4(a, base + 8192 + sw);        mma16816(c1, a, qf[2].x, qf[2].y);
            ldsm4(a, base + (sw ^ 32));        mma16816(c0, a, qf[0].z, qf[0].w);
            ldsm4(a, base + 8192 + (sw ^ 32)); mma16816(c1, a, qf[2].z, qf[2].w);
            ldsm4(a, base + (sw ^ 64));        mma16816(c0, a, qf[1].x, qf[1].y);
            ldsm4(a, base + 8192 + (sw ^ 64)); mma16816(c1, a, qf[3].x, qf[3].y);
            ldsm4(a, base + (sw ^ 96));        mma16816(c0, a, qf[1].z, qf[1].w);
            ldsm4(a, base + 8192 + (sw ^ 96)); mma16816(c1, a, qf[3].z, qf[3].w);
            __syncwarp();
            if (lane == 0) mbar_arrive(s_empty + (EM_K + i) * 8);
            const float scl = 0.08838834764831845f;
            uint32_t u0 = pack2(c0[0] + c1[0], c0[1] + c1[1]), u1 = pack2(c0[2] + c1[2], c0[3] + c1[3]);
            u0 = pack2(bflo(u0) * scl, bfhi(u0) * scl); u1 = pack2(bflo(u1) * scl, bfhi(u1) * scl);
            mx = bmax2(mx, bmax2(u0, u1));
            if (t == 0) {
                const uint32_t pa = sb + OFF_S + (i * 64 + 16 * (g >> 1) + 4 * mt + bat) * 4;
                sts32(pa, u0); sts32(pa + 8, u1);
            }
            if (i == PH_K && tid < 4) stg_ph(scr + G_ML + c * 8 + (tid & 1) * 4 + (tid & 2) * (HALF / 2));
        }
#pragma unroll
        for (int o = 4; o <= 16; o <<= 1) mx = bmax2(mx, __shfl_xor_sync(0xffffffffu, mx, o));
        if (lane == 0) sts32(sb + OFF_WMX + vw * 4, mx);
    }
    bar_consumers();
    TS(tid == 0, 7);
    {
        const float L2E = 1.4426950408889634f;
        uint4 sv = make_uint4(0, 0, 0, 0);
        float m0 = 0.f, m1 = 0.f;
        if (vw < 8) {
            uint4 ma = lds128(sb + OFF_WMX), mb = lds128(sb + OFF_WMX + 16);
            const uint32_t mx = bmax2(bmax2(bmax2(ma.x, ma.y), bmax2(ma.z, ma.w)), bmax2(bmax2(mb.x, mb.y), bmax2(mb.z, mb.w)));
            m0 = bflo(mx); m1 = bfhi(mx);
            sv = lds128(sb + OFF_S + tid * 16);
            float e0 = (ex2((bflo(sv.x) - m0) * L2E) + ex2((bflo(sv.y) - m0) * L2E)) + (ex2((bflo(sv.z) - m0) * L2E) + ex2((bflo(sv.w) - m0) * L2E));
            float e1 = (ex2((bfhi(sv.x) - m1) * L2E) + ex2((bfhi(sv.y) - m1) * L2E)) + (ex2((bfhi(sv.z) - m1) * L2E) + ex2((bfhi(sv.w) - m1) * L2E));
#pragma unroll
            for (int o = 16; o > 0; o >>= 1) { e0 += shx(e0, o); e1 += shx(e1, o); }
            if (lane == 0) sts64(sb + OFF_WMX + 32 + vw * 8, __float_as_uint(e0), __float_as_uint(e1));
        }
        bar_consumers();
        if (vw == 0) {
            float l0 = 0.f, l1 = 0.f;
#pragma unroll
            for (int w = 0; w < 4; w++) {
                uint4 s = lds128(sb + OFF_WMX + 32 + w * 16);
                l0 += __uint_as_float(s.x) + __uint_as_float(s.z); l1 += __uint_as_float(s.y) + __uint_as_float(s.w);
            }
            if (tid < 4) stg_pkt(scr + G_ML + c * 8 + (tid & 1) * 4 + (tid & 2) * (HALF / 2), m0, l0, m1, l1, tag);
            {
                const bool rd = lane < 4 && lane != sp;
                uint4 v = make_uint4(rd ? 2u : tag, 0, 0, 0);
                int it = 0;
                do { ldg_pkt_if(v, scr + G_ML + near_half(G_ML, side) + (kvh * 8 + (lane & 3) * 2 + bb) * 8, (v.x ^ tag) & 7u); }
                while (any_lane((v.x ^ tag) & 7u) && ++it < SPIN_LIMIT);
                if (rd) { m0 = untagf(v.x); l0 = __uint_as_float(v.y); m1 = __uint_as_float(v.z); l1 = __uint_as_float(v.w); }
            }
            float g0 = fmaxf(m0, shx(m0, 1)), g1 = fmaxf(m1, shx(m1, 1));
            g0 = fmaxf(g0, shx(g0, 2)); g1 = fmaxf(g1, shx(g1, 2));
            l0 *= ex2((m0 - g0) * L2E); l1 *= ex2((m1 - g1) * L2E);
            l0 += shx(l0, 1); l1 += shx(l1, 1);
            l0 += shx(l0, 2); l1 += shx(l1, 2);
            if (lane == 0)
                sts128(sb + OFF_WMX + 96, __float_as_uint(g0), __float_as_uint(g1), __float_as_uint(1.0f / l0), __float_as_uint(1.0f / l1));
        }
        bar_consumers();
        if (vw < 8) {
            const uint4 gs = lds128(sb + OFF_WMX + 96);
            const float g0 = __uint_as_float(gs.x), g1 = __uint_as_float(gs.y), i0 = __uint_as_float(gs.z), i1 = __uint_as_float(gs.w);
            const uint32_t a0 = pack2(ex2((bflo(sv.x) - g0) * L2E) * i0, ex2((bflo(sv.y) - g0) * L2E) * i0);
            const uint32_t a1 = pack2(ex2((bflo(sv.z) - g0) * L2E) * i0, ex2((bflo(sv.w) - g0) * L2E) * i0);
            const uint32_t b0 = pack2(ex2((bfhi(sv.x) - g1) * L2E) * i1, ex2((bfhi(sv.y) - g1) * L2E) * i1);
            const uint32_t b1 = pack2(ex2((bfhi(sv.z) - g1) * L2E) * i1, ex2((bfhi(sv.w) - g1) * L2E) * i1);
            sts64(sb + OFF_P + tid * 8, a0, a1); sts64(sb + OFF_P + PSTR + tid * 8, b0, b1);
        }
        bar_consumers();
        TS(tid == 0, 8);
    }
    const uint32_t rin = vw * 2048 + (r + 8 * (mi >> 1)) * 128;
    const uint32_t rsw = ((mi & 1) ^ r) << 4;
    uint32_t ra[2][4][4];
    unsigned sidew = 2u;
    if (vw < 8) {
        float c0[4] = {}, c1[4] = {};
        const uint32_t vo = (vw >> 2) * 8192 + (r + 8 * (mi >> 1)) * 128 + ((((2 * vw + (mi & 1)) & 7) ^ r) << 4);
        const uint32_t pa = sb + OFF_P + bat * PSTR + t * 32;
#pragma unroll 1
        for (int i = 0; i < 16; i++) {
            uint4 pb0 = lds128(pa + i * 128), pb1 = lds128(pa + i * 128 + 16);
            mbar_wait(s_full + it_v(i) * 8);
            const uint32_t base = sb + v_off(i) + vo;
            uint32_t a0[4], a1[4], a2[4], a3[4];
            ldsm4t(a0, base); ldsm4t(a1, base + 2048); ldsm4t(a2, base + 4096); ldsm4t(a3, base + 6144);
            mma16816(c0, a0, pb0.x, pb0.y);
            mma16816(c1, a1, pb0.z, pb0.w);
            mma16816(c0, a2, pb1.x, pb1.y);
            mma16816(c1, a3, pb1.z, pb1.w);
            __syncwarp();
            if (lane == 0) mbar_arrive(s_empty + (EM_V + i) * 8);
            if (i == SIDE_V) { mbar_wait(s_empty + EM_PH * 8); sidew = ldg_rlx1(pside); }
        }
        if (t < 2)
            stg_pkt(scr + G_OP + kvh * 4096 + (j >> 2) * 2048 + t * HALF + (j & 3) * 256 + vw * 32 + g * 4,
                    c0[0] + c1[0], c0[1] + c1[1], c0[2] + c1[2], c0[3] + c1[3], tag);
        TS(tid == 0, 9);
    } else {
        mbar_wait(s_full + it_v(SIDE_V) * 8);
        mbar_wait(s_empty + EM_PH * 8);
    }
    unsigned hm;
    {
        int it = 0;
        while (any_lane((sidew ^ tag) & 7u) && ++it < SPIN_LIMIT) sidew = ldg_rlx1(pside);
        __syncwarp();
        const int uw = G_PART + (vw * 16 + (lane & 15)) * 2048;
        hm = __ballot_sync(0xffffffffu, near_half(uw, sidew >> 4)) >> (g >> 1);
    }
    side = __float_as_uint(ldsf(sb + OFF_WMX + 112));
    {
        mbar_wait(s_full + IT_WO * 8);
#pragma unroll
        for (int mt = 0; mt < 4; mt++) ldsm4t(ra[0][mt], sb + OFF_WO0 + rin + (rsw ^ (mt * 32)));
        mbar_wait(s_full + (IT_WO + 1) * 8);
#pragma unroll
        for (int mt = 0; mt < 4; mt++) ldsm4t(ra[1][mt], sb + OFF_WO1 + rin + (rsw ^ (mt * 32)));
        asm volatile("bar.sync 3, 352;" ::: "memory");
        const uint4 fr = lds128(sb + OFF_FR + r * 48);
        float cc[4][4] = {};
#pragma unroll
        for (int mt = 0; mt < 4; mt++) mma16816(cc[mt], ra[0][mt], fr.x, fr.y);
#pragma unroll
        for (int mt = 0; mt < 4; mt++) mma16816(cc[mt], ra[1][mt], fr.z, fr.w);
        if (t == 0) publish_partials(ppart, hm, cc, tag);
        __syncwarp();
        TS(tid == 0, 11);
    }
    uint32_t ag[4][6][4];
    const uint32_t gub = s_full + (IT_GU + 2 * (vw / 3)) * 8;
    const uint32_t gpitch = wide ? 96 : 64, gsw = wide ? 0 : (r >> 1) << 4;
    const uint32_t gbase = sb + ((mi & 1) ? OFF_U : OFF_G) + (vw * 64 + r + 8 * (mi >> 1)) * gpitch;
    auto load_gu = [&]() {
#pragma unroll
        for (int ks = 0; ks < 4; ks++)
#pragma unroll
            for (int q = 0; q < 4; q++) ldsm4t(ag[ks][q], gbase + ks * 16 * gpitch + ((q << 4) ^ gsw));
        if (wide) {
#pragma unroll
            for (int ks = 0; ks < 4; ks++)
#pragma unroll
                for (int q = 4; q < 6; q++) ldsm4t(ag[ks][q], gbase + ks * 1536 + q * 16);
        }
    };
    bool gpre;
    while (true) {
        gpre = __all_sync(0xffffffffu, mbar_test(gub) && mbar_test(gub + 8));
        if (gpre || __all_sync(0xffffffffu, mbar_test(s_empty + EM_X1 * 8))) break;
    }
    if (gpre) {
        load_gu();
        mbar_wait(s_empty + EM_X1 * 8);
    }
    const uint32_t dbar = s_full + (IT_WD + vw / 3) * 8;
    const uint32_t dbase = sb + OFF_D + (vw / 3) * DSTR + (vw % 3) * (wide ? 6144 : 4096) + (r + 8 * (mi >> 1)) * 128;
    uint32_t ad[3][4][4];
    auto load_d = [&]() {
#pragma unroll
        for (int ks = 0; ks < 2; ks++)
#pragma unroll
            for (int mt = 0; mt < 4; mt++) ldsm4t(ad[ks][mt], dbase + ks * 2048 + (rsw ^ (mt * 32)));
        if (wide) {
#pragma unroll
            for (int mt = 0; mt < 4; mt++) ldsm4t(ad[2][mt], dbase + 4096 + (rsw ^ (mt * 32)));
        }
    };
    bool dpre;
    {
        uint4 v;
        int it = 0;
        const int xw = G_X1 + (vw >> 3) * 2048 + (c & (XREP - 1)) * 4096;
        const unsigned* px = scr + xw + near_half(xw, side) + (vecw & 1023);
        do { v = ldg_rlx4(px); } while (any_lane(bad4(v, tag) & 7u) && ++it < SPIN_LIMIT);
        xw0 = hi2(v.x, v.y); xw1 = hi2(v.z, v.w);
        ln_stage1(xw0, xw1, st2, vw, lane);
        bar_consumers();
        if (tid == 0) mbar_arrive(s_empty + EM_CH * 8);
        TS(tid == 0, 13);
        uint32_t y0, y1;
        ln_stage2(ln_load(st2), xw0, xw1, y0, y1);
        aw0 = badd2(bmul2(y0, sc0), sh0); aw1 = badd2(bmul2(y1, sc1), sh1);
        uint32_t bf[4][2];
        make_bfrags(bf, aw0, aw1, r);
        if (!gpre) { mbar_wait(gub); mbar_wait(gub + 8); load_gu(); }
        float cc[6][4] = {};
#pragma unroll
        for (int ks = 0; ks < 4; ks++)
#pragma unroll
            for (int q = 0; q < 4; q++) mma16816(cc[q], ag[ks][q], bf[ks][0], bf[ks][1]);
        if (wide) {
#pragma unroll
            for (int ks = 0; ks < 4; ks++)
#pragma unroll
                for (int q = 4; q < 6; q++) mma16816(cc[q], ag[ks][q], bf[ks][0], bf[ks][1]);
        }
        if (t == 0) {
#pragma unroll
            for (int q = 0; q < 6; q++) sts128f(sb + OFF_RED + vw * 768 + q * 128 + g * 16, cc[q]);
        }
        dpre = __all_sync(0xffffffffu, mbar_test(dbar));
        bar_consumers();
        TS(tid == 0, 14);
        if (tid < 192) {
            float sv[NCW];
#pragma unroll
            for (int w = 0; w < NCW; w++) sv[w] = ldsf(sb + OFF_RED + w * 768 + tid * 4);
            if (dpre) load_d();
            const float s = ((sv[0] + sv[1]) + (sv[2] + sv[3])) + ((sv[4] + sv[5]) + (sv[6] + sv[7])) + sv[8];
            const uint32_t gu = pack2(s, __shfl_down_sync(0xffffffffu, s, 2));
            const float gt = bflo(gu);
            const uint32_t hh = pack2(((gt > 0.f) ? gt : gt * 0.0f) * bfhi(gu), 0.f);
            const int rr = tid >> 2;
            if ((tid & 2) == 0)
                sts16(sb + OFF_FR + ((tid & 1) * 4 + ((rr & 7) >> 1)) * 48 + (rr >> 3) * 4 + (rr & 1) * 2, hh);
        } else if (dpre) {
            load_d();
        }
    }
    {
        bar_consumers();
        const uint4 fr = lds128(sb + OFF_FR + r * 48);
        const uint2 f2 = lds64(sb + OFF_FR + r * 48 + 16);
        if (!dpre) { mbar_wait(dbar); load_d(); }
        float cc[4][4] = {};
#pragma unroll
        for (int mt = 0; mt < 4; mt++) mma16816(cc[mt], ad[0][mt], fr.x, fr.y);
#pragma unroll
        for (int mt = 0; mt < 4; mt++) mma16816(cc[mt], ad[1][mt], fr.z, fr.w);
        if (wide) {
#pragma unroll
            for (int mt = 0; mt < 4; mt++) mma16816(cc[mt], ad[2][mt], f2.x, f2.y);
        }
        if (t == 0) publish_partials(ppart, hm, cc, tag | 4u);
        __syncwarp();
        asm volatile("bar.arrive 5, 352;" ::: "memory");
        TS(tid == 256, 15);
    }
}

typedef CUresult (*EncodeFn)(CUtensorMap*, CUtensorMapDataType, cuuint32_t, void*, const cuuint64_t*, const cuuint64_t*,
                             const cuuint32_t*, const cuuint32_t*, CUtensorMapInterleave, CUtensorMapSwizzle,
                             CUtensorMapL2promotion, CUtensorMapFloatOOBfill);

void make_map(EncodeFn enc, CUtensorMap* m, const void* p, cuuint64_t d0, cuuint64_t d1, cuuint64_t d2,
              cuuint64_t s1, cuuint64_t s2, cuuint32_t b0, cuuint32_t b1, cuuint32_t b2, CUtensorMapSwizzle sw,
              CUtensorMapL2promotion pr = CU_TENSOR_MAP_L2_PROMOTION_L2_128B) {
    cuuint64_t dims[3] = {d0, d1, d2};
    cuuint64_t str[2] = {s1, s2};
    cuuint32_t box[3] = {b0, b1, b2};
    cuuint32_t es[3] = {1, 1, 1};
    enc(m, CU_TENSOR_MAP_DATA_TYPE_BFLOAT16, 3, const_cast<void*>(p), dims, str, box, es,
        CU_TENSOR_MAP_INTERLEAVE_NONE, sw, pr, CU_TENSOR_MAP_FLOAT_OOB_FILL_NONE);
}

}

extern "C" void kernel_launch(void* const* d_in, const int* in_sizes, int n_in, void* d_out, int out_size) {
    (void)in_sizes; (void)n_in; (void)out_size;
    void* fn = nullptr;
    cudaDriverEntryPointQueryResult qr;
    cudaGetDriverEntryPoint("cuTensorMapEncodeTiled", &fn, cudaEnableDefault, &qr);
    EncodeFn enc = (EncodeFn)fn;
    cudaFuncSetAttribute(fused_block_kernel, cudaFuncAttributeMaxDynamicSharedMemorySize, SMEM_BYTES);

    const void *x = d_in[0], *kc = d_in[1], *vc = d_in[2], *wq = d_in[3], *wo = d_in[4];
    const void *wg = d_in[6], *wu = d_in[7], *wd = d_in[8], *cc = d_in[9], *wmod = d_in[10];
    const CUtensorMapSwizzle S128 = CU_TENSOR_MAP_SWIZZLE_128B, S64 = CU_TENSOR_MAP_SWIZZLE_64B, S0 = CU_TENSOR_MAP_SWIZZLE_NONE;
    void* raw = nullptr;
    cudaGetSymbolAddress(&raw, g_raw);
    unsigned* scr = (unsigned*)(((uintptr_t)raw + 0x1fffff) & ~(uintptr_t)0x1fffff);
    Maps m;
    make_map(enc, &m.m[M_K], kc, 64, 32ull * 32768, 2, 256, 128, 64, 64, 2, S128, CU_TENSOR_MAP_L2_PROMOTION_L2_256B);
    make_map(enc, &m.m[M_V], vc, 64, 32ull * 32768, 2, 256, 128, 64, 64, 2, S128, CU_TENSOR_MAP_L2_PROMOTION_L2_256B);
    make_map(enc, &m.m[M_WMOD], wmod, 3456, 144, 4, 3456 * 2, 3456 * 2 * 144, 32, 144, 2, S64);
    make_map(enc, &m.m[M_WQ], wq, 4096, 144, 4, 4096 * 2, 4096 * 2 * 144, 32, 144, 2, S64);
    make_map(enc, &m.m[M_WG], wg, 4608, 576, 1, 4608 * 2, 4608 * 2 * 576, 32, 192, 1, S64);
    make_map(enc, &m.m[M_WU], wu, 4608, 576, 1, 4608 * 2, 4608 * 2 * 576, 32, 192, 1, S64);
    make_map(enc, &m.m[M_WG48], wg, 4608, 576, 1, 4608 * 2, 4608 * 2 * 576, 48, 192, 1, S0);
    make_map(enc, &m.m[M_WU48], wu, 4608, 576, 1, 4608 * 2, 4608 * 2 * 576, 48, 192, 1, S0);
    make_map(enc, &m.m[M_WO], wo, 64, 4096, 9, 1152, 128, 64, 16, 9, S128);
    make_map(enc, &m.m[M_WD], wd, 64, 4608, 9, 1152, 128, 64, 32, 3, S128);
    make_map(enc, &m.m[M_WD48], wd, 64, 4608, 9, 1152, 128, 64, 48, 3, S128);
    fused_block_kernel<<<NCTA, NTHR, SMEM_BYTES>>>(m, (const __nv_bfloat16*)x, (const __nv_bfloat16*)cc,
                                                   (const __nv_bfloat16*)kc, (__nv_bfloat16*)d_out, scr TUNE_ARG);
}
```

```cpp
#include <cuda_runtime.h>
#include <cuda.h>
#include <cuda_bf16.h>
#include <stdint.h>

namespace {

constexpr int DM = 576;
constexpr int NCTA = 128;
constexpr int NCW = 9;
constexpr int NTHR = (NCW + 3) * 32;
constexpr int NMOD = 108;

#define WIN_MAIN 4
#define WIN_TAIL 3
#define WIN_SWITCH 38
#define PACE_GBS 3100
#define PACE_LEAD 28672
#define PACE_TAIL 2900
#define TAIL_GAP 250
#define PACE_D 3300
#define OPEN_WIN 1
#define DELAY_B 300
#define DELAY_D 150
#define CTL_GAIN 0
#define CTL_MAIN 57344
#define CTL_TAIL 40960
#define CTL_SWITCH 30
#define CTL_SUB 1
#define KVPAT 1
#define KVROT 1
#define EARLY_PF 8192
#define TM_PF 1
#define XREP 2
#define PH_V 7
#define SIDE_V 11
#define NPROBE 10
#define NPROBE0 3
#define PH_K 8

#define TUNE_PARAM
#define TUNE_ARG

constexpr int IT_WMOD = 0, IT_WQ = 2, IT_K = 4, IT_V = 20, IT_WO = 36, IT_GU = 38, IT_WD = 44, N_IT = 47;
__device__ __forceinline__ constexpr int it_v(int k) { return IT_V + k; }
constexpr int EM_WMOD = 0, EM_WQ = 1, EM_K = 2, EM_V = 18, EM_PH = 34, EM_X1 = 35, EM_CH = 36, EM_SD = 37, N_EM = 38;

constexpr int RING = 13 * 16384;
constexpr int OFF_WMOD = 0, OFF_WQ = 36864, OFF_K0 = 73728;
constexpr int OFF_WO0 = 194560, OFF_WO1 = 0, OFF_G = 18432, OFF_U = 73728;
constexpr int OFF_D = 129024, DSTR = 18432;
constexpr int PSTR = 2064;
constexpr int OFF_P = RING;
constexpr int OFF_S = OFF_P + 4160;
constexpr int OFF_RED = OFF_S + 4096;
constexpr int OFF_QS = OFF_RED + 6912;
constexpr int OFF_FR = OFF_QS + 640;
constexpr int OFF_STAT = OFF_FR + 384;
constexpr int OFF_WMX = OFF_STAT + 320;
constexpr int OFF_BAR = OFF_WMX + 128;
constexpr int SMEM_USED = OFF_BAR + (N_IT + N_EM) * 8;
constexpr int SMEM_BYTES = SMEM_USED + 1024;
static_assert(SMEM_BYTES <= 232448, "smem");

struct Maps { CUtensorMap m[11]; };
enum { M_K, M_V, M_WMOD, M_WQ, M_WO, M_WG, M_WU, M_WD, M_WG48, M_WU48, M_WD48 };

constexpr int HALF = 1024;
constexpr int G_PART = 0;
constexpr int G_OP = G_PART + 144 * 2048;
constexpr int G_X1 = G_OP + 16 * 4096;
constexpr int G_PROBE = G_X1 + XREP * 4096;
constexpr int G_SIDE = G_PROBE + 2048;
constexpr int G_EPOCH = G_SIDE + 1024;
constexpr int G_MOD = G_EPOCH + 1024;
constexpr int G_Q = G_MOD + 7 * 2048;
constexpr int G_ML = G_Q + 8 * 2048;
constexpr int G_WORDS = G_ML + 2048;
static_assert(G_MOD % 2048 == 0 && G_OP % 2048 == 0 && G_X1 % 2048 == 0 && G_PROBE % 2048 == 0, "halves");
static_assert(G_WORDS * 4 <= (2 << 20), "scratch must fit one 2 MB page");
__device__ __align__(128) unsigned g_raw[(2 << 20) / 4 + G_WORDS + 8192];
__device__ __forceinline__ int near_half(int w, unsigned side) { return ((__popc(w & 0x2C800) ^ side) & 1) << 10; }
__device__ __forceinline__ int dual(int base, int i) { return base + i + (i & ~1023); }
__device__ __forceinline__ int dual_near(int base, int i, unsigned side) { const int w = dual(base, i); return w + near_half(w, side); }
#define g_ts ((unsigned long long*)(scr + G_WORDS))

constexpr int SPIN_LIMIT = 1 << 20;

__device__ __forceinline__ uint32_t smem_u32(const void* p) { return (uint32_t)__cvta_generic_to_shared(p); }
__device__ __forceinline__ void mbar_init(uint32_t bar, int cnt) {
    asm volatile("mbarrier.init.shared::cta.b64 [%0], %1;" ::"r"(bar), "r"(cnt) : "memory");
}
__device__ __forceinline__ void mbar_expect_tx(uint32_t bar, uint32_t bytes) {
    asm volatile("mbarrier.arrive.expect_tx.shared::cta.b64 _, [%0], %1;" ::"r"(bar), "r"(bytes) : "memory");
}
__device__ __forceinline__ void mbar_arrive(uint32_t bar) {
    asm volatile("mbarrier.arrive.shared::cta.b64 _, [%0];" ::"r"(bar) : "memory");
}
__device__ __forceinline__ void mbar_wait(uint32_t bar) {
    asm volatile("{\n.reg .pred p;\nW_%=:\nmbarrier.try_wait.parity.shared::cta.b64 p, [%0], 0;\n@!p bra W_%=;\n}"
                 ::"r"(bar) : "memory");
}
__device__ __forceinline__ bool mbar_test(uint32_t bar) {
    uint32_t ok;
    asm volatile("{\n.reg .pred p;\nmbarrier.test_wait.parity.shared::cta.b64 p, [%1], 0;\nselp.u32 %0, 1, 0, p;\n}"
                 : "=r"(ok) : "r"(bar) : "memory");
    return ok;
}
__device__ __forceinline__ uint32_t gtime32() { uint32_t t; asm volatile("mov.u32 %0, %%globaltimer_lo;" : "=r"(t)); return t; }
__device__ __forceinline__ void tma3d(uint32_t dst, const CUtensorMap* m, int x, int y, int z, uint32_t bar) {
    asm volatile("cp.async.bulk.tensor.3d.shared::cluster.global.mbarrier::complete_tx::bytes [%0], [%1, {%3, %4, %5}], [%2];"
                 ::"r"(dst), "l"(m), "r"(bar), "r"(x), "r"(y), "r"(z) : "memory");
}
__device__ __forceinline__ void bar_consumers() { asm volatile("bar.sync 1, 288;" ::: "memory"); }

__device__ __forceinline__ void ldsm4(uint32_t (&a)[4], uint32_t addr) {
    asm volatile("ldmatrix.sync.aligned.m8n8.x4.shared.b16 {%0,%1,%2,%3}, [%4];"
                 : "=r"(a[0]), "=r"(a[1]), "=r"(a[2]), "=r"(a[3]) : "r"(addr) : "memory");
}
__device__ __forceinline__ void ldsm4t(uint32_t (&a)[4], uint32_t addr) {
    asm volatile("ldmatrix.sync.aligned.m8n8.x4.trans.shared.b16 {%0,%1,%2,%3}, [%4];"
                 : "=r"(a[0]), "=r"(a[1]), "=r"(a[2]), "=r"(a[3]) : "r"(addr) : "memory");
}
__device__ __forceinline__ void mma16816(float (&c)[4], const uint32_t (&a)[4], uint32_t b0, uint32_t b1) {
    asm volatile("mma.sync.aligned.m16n8k16.row.col.f32.bf16.bf16.f32 {%0,%1,%2,%3}, {%4,%5,%6,%7}, {%8,%9}, {%0,%1,%2,%3};"
                 : "+f"(c[0]), "+f"(c[1]), "+f"(c[2]), "+f"(c[3])
                 : "r"(a[0]), "r"(a[1]), "r"(a[2]), "r"(a[3]), "r"(b0), "r"(b1));
}
__device__ __forceinline__ float ldsf(uint32_t a) { float v; asm volatile("ld.shared.f32 %0, [%1];" : "=f"(v) : "r"(a) : "memory"); return v; }
__device__ __forceinline__ uint2 lds64(uint32_t a) {
    uint2 v; asm volatile("ld.shared.v2.u32 {%0,%1}, [%2];" : "=r"(v.x), "=r"(v.y) : "r"(a) : "memory"); return v;
}
__device__ __forceinline__ uint4 lds128(uint32_t a) {
    uint4 v; asm volatile("ld.shared.v4.u32 {%0,%1,%2,%3}, [%4];" : "=r"(v.x), "=r"(v.y), "=r"(v.z), "=r"(v.w) : "r"(a) : "memory"); return v;
}
__device__ __forceinline__ void sts16(uint32_t a, uint32_t v) { asm volatile("st.shared.u16 [%0], %1;" ::"r"(a), "h"((unsigned short)v) : "memory"); }
__device__ __forceinline__ void sts32(uint32_t a, uint32_t v) { asm volatile("st.shared.u32 [%0], %1;" ::"r"(a), "r"(v) : "memory"); }
__device__ __forceinline__ void sts64(uint32_t a, uint32_t x, uint32_t y) { asm volatile("st.shared.v2.u32 [%0], {%1,%2};" ::"r"(a), "r"(x), "r"(y) : "memory"); }
__device__ __forceinline__ void sts128(uint32_t a, uint32_t x, uint32_t y, uint32_t z, uint32_t w) {
    asm volatile("st.shared.v4.u32 [%0], {%1,%2,%3,%4};" ::"r"(a), "r"(x), "r"(y), "r"(z), "r"(w) : "memory");
}
__device__ __forceinline__ void sts128f(uint32_t a, const float (&c)[4]) {
    asm volatile("st.shared.v4.f32 [%0], {%1,%2,%3,%4};" ::"r"(a), "f"(c[0]), "f"(c[1]), "f"(c[2]), "f"(c[3]) : "memory");
}
__device__ __forceinline__ unsigned ldg_rlx1(const unsigned* p) {
    unsigned v; asm volatile("ld.relaxed.gpu.global.u32 %0, [%1];" : "=r"(v) : "l"(p) : "memory"); return v;
}
__device__ __forceinline__ uint4 ldg_rlx4(const unsigned* p) {
    uint4 v; asm volatile("ld.relaxed.gpu.global.v4.u32 {%0,%1,%2,%3}, [%4];" : "=r"(v.x), "=r"(v.y), "=r"(v.z), "=r"(v.w) : "l"(p) : "memory"); return v;
}
__device__ __forceinline__ uint4 ldg_pkt(const unsigned* p) {
    uint4 v;
    asm volatile("{\n.reg .b128 t;\n.reg .b64 lo, hi;\nld.relaxed.gpu.global.b128 t, [%4];\nmov.b128 {lo, hi}, t;\n"
                 "mov.b64 {%0,%1}, lo;\nmov.b64 {%2,%3}, hi;\n}"
                 : "=r"(v.x), "=r"(v.y), "=r"(v.z), "=r"(v.w) : "l"(p) : "memory");
    return v;
}
__device__ __forceinline__ void ldg_pkt_if(uint4& v, const unsigned* a, unsigned p) {
    asm volatile("{\n.reg .pred q;\n.reg .b128 t;\n.reg .b64 lo, hi;\nsetp.ne.u32 q, %5, 0;\n"
                 "mov.b64 lo, {%0,%1};\nmov.b64 hi, {%2,%3};\nmov.b128 t, {lo, hi};\n"
                 "@q ld.relaxed.gpu.global.b128 t, [%4];\nmov.b128 {lo, hi}, t;\n"
                 "mov.b64 {%0,%1}, lo;\nmov.b64 {%2,%3}, hi;\n}"
                 : "+r"(v.x), "+r"(v.y), "+r"(v.z), "+r"(v.w) : "l"(a), "r"(p) : "memory");
}
__device__ __forceinline__ bool any_lane(unsigned x) { return __any_sync(0xffffffffu, x != 0); }
__device__ __forceinline__ void stg_pkt(unsigned* p, float a, float b, float c, float d, unsigned tag) {
    unsigned x = (__float_as_uint(a) & ~7u) | tag;
    asm volatile("{\n.reg .b128 t;\n.reg .b64 lo, hi;\nmov.b64 lo, {%1,%2};\nmov.b64 hi, {%3,%4};\nmov.b128 t, {lo, hi};\n"
                 "st.relaxed.gpu.global.b128 [%0], t;\n}"
                 ::"l"(p), "r"(x), "r"(__float_as_uint(b)), "r"(__float_as_uint(c)), "r"(__float_as_uint(d)) : "memory");
}
__device__ __forceinline__ void stg_rlx1(unsigned* p, unsigned x) { asm volatile("st.relaxed.gpu.global.u32 [%0], %1;" ::"l"(p), "r"(x) : "memory"); }
__device__ __forceinline__ unsigned bad4(const uint4& v, unsigned tag) {
    return ((v.x ^ tag) | (v.y ^ tag)) | ((v.z ^ tag) | (v.w ^ tag));
}
__device__ __forceinline__ float untagf(unsigned w) { return __uint_as_float(w & ~7u); }
__device__ __forceinline__ uint32_t pack2(float lo, float hi) {
    uint32_t r; asm("cvt.rn.bf16x2.f32 %0, %1, %2;" : "=r"(r) : "f"(hi), "f"(lo)); return r;
}
__device__ __forceinline__ float bflo(uint32_t w) { return __uint_as_float(w << 16); }
__device__ __forceinline__ float bfhi(uint32_t w) { return __uint_as_float(w & 0xffff0000u); }
__device__ __forceinline__ uint32_t hi2(uint32_t a, uint32_t b) { return __byte_perm(a, b, 0x7632); }
__device__ __forceinline__ uint32_t badd2(uint32_t a, uint32_t b) { uint32_t r; asm("add.rn.bf16x2 %0, %1, %2;" : "=r"(r) : "r"(a), "r"(b)); return r; }
__device__ __forceinline__ uint32_t bsub2(uint32_t a, uint32_t b) { uint32_t r; asm("sub.rn.bf16x2 %0, %1, %2;" : "=r"(r) : "r"(a), "r"(b)); return r; }
__device__ __forceinline__ uint32_t bmul2(uint32_t a, uint32_t b) { uint32_t r; asm("mul.rn.bf16x2 %0, %1, %2;" : "=r"(r) : "r"(a), "r"(b)); return r; }
__device__ __forceinline__ uint32_t bmax2(uint32_t a, uint32_t b) { uint32_t r; asm("max.bf16x2 %0, %1, %2;" : "=r"(r) : "r"(a), "r"(b)); return r; }
__device__ __forceinline__ float ex2(float x) { float r; asm("ex2.approx.ftz.f32 %0, %1;" : "=f"(r) : "f"(x)); return r; }
__device__ __forceinline__ float rcp(float x) { float r; asm("rcp.approx.ftz.f32 %0, %1;" : "=f"(r) : "f"(x)); return r; }
__device__ __forceinline__ float fsqrt(float x) { float r; asm("sqrt.approx.ftz.f32 %0, %1;" : "=f"(r) : "f"(x)); return r; }
__device__ __forceinline__ float shx(float v, int m) { return __shfl_xor_sync(0xffffffffu, v, m); }
#define TS(cond, slot) do { } while (0)

__device__ __forceinline__ uint32_t k_off(int i) { return i < 8 ? OFF_K0 + i * 16384 : (i - 8) * 16384; }
__device__ __forceinline__ uint32_t v_off(int i) { return i < 5 ? (8 + i) * 16384 : (i - 5) * 16384; }

__device__ __forceinline__ void stg_ph(unsigned* p) { stg_pkt(p, 0.f, 0.f, 0.f, 0.f, 2u); }

__device__ __forceinline__ void ln_stage1(uint32_t xw0, uint32_t xw1, uint32_t st, int vw, int lane) {
    const float piv = __shfl_sync(0xffffffffu, bflo(xw0), lane & 4);
    const float d0 = bflo(xw0) - piv, d1 = bfhi(xw0) - piv, d2 = bflo(xw1) - piv, d3 = bfhi(xw1) - piv;
    float s1 = (d0 + d1) + (d2 + d3), s2 = (d0 * d0 + d1 * d1) + (d2 * d2 + d3 * d3);
    s1 += shx(s1, 1); s2 += shx(s2, 1);
    s1 += shx(s1, 2); s2 += shx(s2, 2);
    s1 += shx(s1, 8); s2 += shx(s2, 8);
    s1 += shx(s1, 16); s2 += shx(s2, 16);
    if ((lane & 27) == 0)
        sts64(st + vw * 8, __float_as_uint(piv + s1 * (1.0f / 64.0f)), __float_as_uint(s2 - s1 * s1 * (1.0f / 64.0f)));
}
struct LnStat { uint4 a, b, c, d; uint2 e; };
__device__ __forceinline__ LnStat ln_load(uint32_t st) {
    LnStat s; s.a = lds128(st); s.b = lds128(st + 16); s.c = lds128(st + 32); s.d = lds128(st + 48); s.e = lds64(st + 64);
    return s;
}
__device__ __forceinline__ void ln_stage2(const LnStat& s, uint32_t xw0, uint32_t xw1, uint32_t& y0, uint32_t& y1) {
    const float m[9] = {__uint_as_float(s.a.x), __uint_as_float(s.a.z), __uint_as_float(s.b.x), __uint_as_float(s.b.z),
                        __uint_as_float(s.c.x), __uint_as_float(s.c.z), __uint_as_float(s.d.x), __uint_as_float(s.d.z), __uint_as_float(s.e.x)};
    const float mean = (((m[0] + m[1]) + (m[2] + m[3])) + ((m[4] + m[5]) + (m[6] + m[7])) + m[8]) * (1.0f / NCW);
    const float m2 = ((__uint_as_float(s.a.y) + __uint_as_float(s.a.w)) + (__uint_as_float(s.b.y) + __uint_as_float(s.b.w))) +
                     ((__uint_as_float(s.c.y) + __uint_as_float(s.c.w)) + (__uint_as_float(s.d.y) + __uint_as_float(s.d.w))) + __uint_as_float(s.e.y);
    float d[9];
#pragma unroll
    for (int w = 0; w < 9; w++) d[w] = m[w] - mean;
    const float acc = (d[0] * d[0] + d[1] * d[1] + d[2] * d[2]) + (d[3] * d[3] + d[4] * d[4] + d[5] * d[5]) + (d[6] * d[6] + d[7] * d[7] + d[8] * d[8]);
    const float var = (m2 + 64.0f * acc) * (1.0f / DM);
    const uint32_t mv = pack2(mean, var);
    const float ve = bflo(pack2(bfhi(mv) + 1e-5f, 0.f));
    const float rinv = rcp(bflo(pack2(fsqrt(ve), 0.f)));
    const uint32_t mm = __byte_perm(mv, mv, 0x1010);
    const uint32_t e0 = bsub2(xw0, mm), e1 = bsub2(xw1, mm);
    y0 = pack2(bflo(e0) * rinv, bfhi(e0) * rinv); y1 = pack2(bflo(e1) * rinv, bfhi(e1) * rinv);
}
__device__ __forceinline__ void make_bfrags(uint32_t (&bf)[4][2], uint32_t aw0, uint32_t aw1, int r) {
#pragma unroll
    for (int ks = 0; ks < 4; ks++) {
        bf[ks][0] = __shfl_sync(0xffffffffu, aw0, ks * 8 + r);
        bf[ks][1] = __shfl_sync(0xffffffffu, aw1, ks * 8 + r);
    }
}
__device__ __forceinline__ uint32_t gemv32(uint32_t s_w, uint32_t red, uint32_t fullbar, uint32_t emptybar,
                                           uint32_t aw0, uint32_t aw1, int tid) {
    const int vw = tid >> 5, lane = tid & 31, g = lane >> 2, t = lane & 3, mi = lane >> 3, r = lane & 7;
    uint32_t bf[4][2];
    make_bfrags(bf, aw0, aw1, r);
    if (vw <= 4) mbar_wait(fullbar);
    if (vw >= 4) mbar_wait(fullbar + 8);
    float cc[2][4] = {};
    const uint32_t abase = s_w + (vw * 64 + r + 8 * (mi >> 1)) * 64;
    const uint32_t sw = ((mi & 1) ^ (r >> 1)) << 4;
#pragma unroll
    for (int ks = 0; ks < 4; ks++) {
#pragma unroll
        for (int mt = 0; mt < 2; mt++) {
            uint32_t a[4];
            ldsm4t(a, abase + ks * 1024 + (sw ^ (mt * 32)));
            mma16816(cc[mt], a, bf[ks][0], bf[ks][1]);
        }
    }
    if (t == 0) { sts128f(red + vw * 256 + g * 16, cc[0]); sts128f(red + vw * 256 + 128 + g * 16, cc[1]); }
    __syncwarp();
    if (lane == 0) mbar_arrive(emptybar);
    bar_consumers();
    float s = 0.f;
    if (tid < 64) {
        const uint32_t ra = red + ((tid & 58) | ((tid & 1) << 2) | ((tid >> 2) & 1)) * 4;
#pragma unroll
        for (int w = 0; w < NCW; w++) s += ldsf(ra + w * 256);
    }
    return pack2(0.f, s);
}
__device__ __forceinline__ void publish_partials(unsigned* q, int t, const float (&cc)[4][4], unsigned tag) {
    float v[4];
#pragma unroll
    for (int i = 0; i < 4; i++) {
        const float lo = (t & 1) ? cc[1][i] : cc[0][i], hi = (t & 1) ? cc[3][i] : cc[2][i];
        v[i] = (t & 2) ? hi : lo;
    }
    stg_pkt(q, v[0], v[1], v[2], v[3], tag);
}
__device__ __forceinline__ void spin_cycles(unsigned n) {
    const unsigned c0 = clock();
    while ((unsigned)clock() - c0 < n) { }
}
__device__ __forceinline__ float reduce_unit(const unsigned* q, int lane, unsigned tag) {
    uint4 v[8];
#pragma unroll
    for (int i = 0; i < 8; i++) v[i] = ldg_pkt(q + i * 128);
    int it = 0;
    while (true) {
        unsigned bad = 0;
#pragma unroll
        for (int i = 0; i < 8; i += 2) bad |= (v[i].x ^ tag) | (v[i + 1].x ^ tag);
        if (!any_lane(bad & 7u) || ++it >= SPIN_LIMIT) break;
#pragma unroll
        for (int i = 0; i < 8; i++) ldg_pkt_if(v[i], q + i * 128, (v[i].x ^ tag) & 7u);
    }
    float s0 = 0.f, s1 = 0.f, s2 = 0.f, s3 = 0.f, u0 = 0.f, u1 = 0.f, u2 = 0.f, u3 = 0.f;
#pragma unroll
    for (int i = 0; i < 8; i += 2) {
        s0 += untagf(v[i].x); s1 += __uint_as_float(v[i].y); s2 += __uint_as_float(v[i].z); s3 += __uint_as_float(v[i].w);
        u0 += untagf(v[i + 1].x); u1 += __uint_as_float(v[i + 1].y); u2 += __uint_as_float(v[i + 1].z); u3 += __uint_as_float(v[i + 1].w);
    }
    s0 += u0; s1 += u1; s2 += u2; s3 += u3;
    __syncwarp();
    const bool h8 = lane & 2, bat = lane & 4;
    const float k0 = (h8 ? s2 : s0) + shx(h8 ? s0 : s2, 2);
    const float k1 = (h8 ? s3 : s1) + shx(h8 ? s1 : s3, 2);
    float k = (bat ? k1 : k0) + shx(bat ? k0 : k1, 4);
    k += shx(k, 8);
    k += shx(k, 16);
    return k;
}

__global__ void __launch_bounds__(NTHR, 1)
fused_block_kernel(const __grid_constant__ Maps maps, const __nv_bfloat16* __restrict__ xin,
                   const __nv_bfloat16* __restrict__ cin, const __nv_bfloat16* __restrict__ kcache,
                   __nv_bfloat16* __restrict__ out, unsigned* const scr TUNE_PARAM) {
    extern __shared__ unsigned char smem_raw[];
    const int c = blockIdx.x;
    const int kvh = c >> 3, j = c & 7, bb = j & 1, sp = j >> 1;
    const bool wide = j >= 6;
    const int f0 = kvh * 288 + (wide ? 48 * j - 96 : 32 * j);
    const int kvrow0 = (bb * 16 + kvh) * 32768 + 28672 + sp * (KVPAT ? 64 : 1024);
    const int kvstep = KVPAT ? 256 : 64;
    if (EARLY_PF && threadIdx.x == 0)
        asm volatile("cp.async.bulk.prefetch.L2.global [%0], %1;" ::"l"((const char*)kcache + (size_t)kvrow0 * 256), "r"(EARLY_PF) : "memory");
    TS(threadIdx.x == 0, 0);
    const uint32_t sb = (smem_u32(smem_raw) + 1023u) & ~1023u;
    const int warp = threadIdx.x >> 5, lane = threadIdx.x & 31;
    const uint32_t s_full = sb + OFF_BAR, s_empty = s_full + N_IT * 8;

    if (warp == NCW) {
        const uint32_t t0 = gtime32();
        const int first = (c < NMOD) ? 0 : 2;
        if (lane == 0) {
#pragma unroll
            for (int i = 0; i < 2; i++) mbar_init(s_full + (first + i) * 8, 1);
            asm volatile("fence.proxy.async.shared::cta;" ::: "memory");
#pragma unroll
            for (int i = 0; i < 2; i++) {
                const uint32_t bar = s_full + (first + i) * 8;
                mbar_expect_tx(bar, 18432);
                tma3d(sb + (first + i) * 18432, &maps.m[M_WMOD + (first >> 1)], c * 32, 0, i * 2, bar);
            }
            TS(true, 17);
        }
        __syncwarp();
        uint32_t w0[2], w1[2], w2[2];
#pragma unroll
        for (int h = 0; h < 2; h++) {
            const int i = lane + 32 * h;
            int off, map, dep = -1, x = 0, y = 0, z = 0, sz = 36, cum;
            if (i < IT_K) {
                off = i * 18432; map = M_WMOD + (i >> 1); x = c * 32; z = (i & 1) * 2; cum = 31104 + (i - 2) * 18432;
            } else if (i < IT_V) {
                const int k = i - IT_K;
                off = k_off(k); map = M_K; y = kvrow0 + k * kvstep; sz = 32; cum = 67968 + k * 16384;
                if (k == 8 && c < NMOD) dep = EM_WMOD;
                if (k == 10) dep = EM_WQ;
                if (k >= 12) dep = EM_K + k - 12;
            } else if (i < IT_WO) {
                const int k = i - IT_V;
                off = v_off(k); map = M_V; y = kvrow0 + k * kvstep; sz = 32; cum = 330112 + k * 16384;
                dep = EM_K + 3 + k + (k < 4);
            } else if (i < IT_GU) {
                const int k = i - IT_WO;
                off = k ? OFF_WO1 : OFF_WO0; map = M_WO; y = kvh * 256 + k * 128 + j * 16; dep = EM_V + 4 + 2 * k;
                cum = 592256 + k * 18432;
            } else if (i < IT_WD) {
                const int k = i - IT_GU;
                sz = wide ? 36 : 24;
                off = ((k & 1) ? OFF_U : OFF_G) + (k >> 1) * sz * 512; map = M_WG + (k & 1) + (wide ? 3 : 0);
                x = f0; y = (k >> 1) * 192; dep = EM_V + 5 + ((off + sz * 512 - 1) >> 14);
                cum = 629120 + k * 13824;
            } else {
                const int k = i - IT_WD;
                off = OFF_D + k * DSTR; map = wide ? M_WD48 : M_WD; y = f0; z = ((k + 2) % 3) * 3; sz = wide ? 36 : 24; dep = EM_V + (k ? 15 : 13);
                cum = 712064 + k * 13824;
            }
            const int stag = (KVROT && i >= IT_K && i < IT_WO) ? (((kvh * 2 + bb) * 13) & 31) * 512 + sp * (KVROT - 1) * 128 : ((c * 37) & 127) * 128;
            cum += EARLY_PF - min(max(cum - 67968, 0), EARLY_PF);
            int due = (int)((float)max(min(cum, 629120) + stag - PACE_LEAD, 0) * (128.0f / PACE_GBS));
            if (i >= IT_GU) due += TAIL_GAP + (int)((float)(min(cum, 712064) - 629120) * (128.0f / PACE_TAIL));
            if (i >= IT_WD) due += (int)((float)(cum - 712064) * (128.0f / PACE_D));
            w0[h] = off | (map << 18) | ((dep + 1) << 22) | (z << 28);
            w1[h] = y | (sz << 24);
            w2[h] = x | (due << 13);
        }
        asm volatile("bar.sync 2, 384;" ::: "memory");
        uint32_t fb = s_full;
        asm volatile("" : "+r"(fb));
        bool open = false;
#pragma unroll 1
        for (int i = first + 2; i < N_IT; i++) {
            const bool hi = i >= 32;
            const uint32_t a = __shfl_sync(0xffffffffu, hi ? w0[1] : w0[0], i);
            const uint32_t b = __shfl_sync(0xffffffffu, hi ? w1[1] : w1[0], i);
            const uint32_t x = __shfl_sync(0xffffffffu, hi ? w2[1] : w2[0], i);
            if (lane == 0) {
                const uint32_t bar = fb + i * 8;
                if (!open) {
                    const int win = (i >= WIN_SWITCH) ? WIN_TAIL : WIN_MAIN;
                    const int dep = (a >> 22) & 63;
                    const uint32_t due = t0 + (x >> 13);
                    if (dep) mbar_wait(fb + (N_IT - 1 + dep) * 8);
                    if (i < IT_GU || !OPEN_WIN) {
                        if (i - win >= first) mbar_wait(bar - win * 8);
                        while ((int)(gtime32() - due) < 0) { }
                    } else {
                        const uint32_t ch = fb + (N_IT + EM_CH) * 8;
                        while (!mbar_test(bar - win * 8)) { if (mbar_test(ch)) { open = true; break; } }
                        while (!open && (int)(gtime32() - due) < 0) open = mbar_test(ch);
                    }
                }
                mbar_expect_tx(bar, (b >> 24) * 512);
                tma3d(fb - OFF_BAR + (a & 0x3ffff), &maps.m[(a >> 18) & 15], x & 0x1fff, b & 0xffffff, a >> 28, bar);
                TS(i == IT_WO, 1);
                TS(i == N_IT - 1, 2);
            }
            __syncwarp();
        }
        return;
    }

    const int g = lane >> 2, t = lane & 3, mi = lane >> 3, r = lane & 7;
    const int bat = g & 1;

    if (warp > NCW) {
        const bool first = warp == NCW + 1, active = first || c < 16;
        const int unit = first ? c : NCTA + c;
        const int rcol = (unit >> 2) * 16 + (unit & 3) * 2 + (lane & 1) + (lane & 2) * 4 + bat * DM;
        const unsigned ep = ldg_rlx1(scr + G_EPOCH);
        uint32_t xold = 0, ga = 0, gb = 0;
        if (active) xold = __ldg((const unsigned short*)xin + rcol);
        if (!first) asm volatile("bar.sync 2, 384;" ::: "memory");
        const unsigned tag = (ep + 1u) & 1u;
        unsigned side = 0;
        const int x1w = G_X1 + (unit >> 7) * 2048 + (unit & 127) * 8 + r + (lane & 8) * (HALF / 8) + (lane >> 4) * 4096;
        if (first) {
            unsigned* pr = scr + G_PROBE + c * 8;
            if (lane < 16) stg_rlx1(pr + r + (lane & 8) * (HALF / 8), 0u);
            __syncwarp();
            asm volatile("bar.arrive 2, 384;" ::: "memory");
            unsigned best0 = ~0u, best1 = ~0u, v = 0, cp = 0;
#pragma unroll 1
            for (int i = 0; i <= 2 * NPROBE; i++) {
                if (lane == 0) {
                    asm volatile("atom.relaxed.gpu.global.add.u32 %0, [%1], 1;" : "=r"(v) : "l"(pr + (i & 1) * HALF + (v >> 31)) : "memory");
                    const unsigned cn = clock(), d = cn - cp;
                    cp = cn;
                    if (i & 1) best0 = min(best0, d); else if (i) best1 = min(best1, d);
                    side = (best1 < best0) ^ (__popc(G_PROBE & 0x2C800) & 1);
                }
                if (i == 2 * NPROBE0) {
                    asm volatile("bar.sync 6, 64;" ::: "memory");
                    if (lane == 0) { sts32(sb + OFF_WMX + 116, side); mbar_arrive(s_empty + EM_SD * 8); }
                }
            }
            if (lane == 0) sts32(sb + OFF_WMX + 112, side);
            side = __shfl_sync(0xffffffffu, side, 0);
            mbar_wait(s_full + it_v(PH_V) * 8);
#pragma unroll 1
            for (int u = c; u < 144; u += NCTA) {
                unsigned* q = scr + G_PART + u * 2048 + near_half(G_PART + u * 2048, side) + lane * 4;
#pragma unroll
                for (int i = 0; i < 8; i++) stg_ph(q + i * 128);
#pragma unroll
                for (int i = 0; i < XREP; i += 2) stg_rlx1(scr + x1w + (u >> 7) * 2048 + i * 4096, 2u);
            }
            unsigned* o = scr + G_OP + kvh * 4096 + (j >> 2) * 2048 + (j & 3) * 256 + lane * 4;
            stg_ph(o); stg_ph(o + 128); stg_ph(o + HALF); stg_ph(o + HALF + 128);
            __threadfence();
            __syncwarp();
            if (lane < 8) stg_rlx1(scr + G_SIDE + c * 8 + lane, (side << 4) | tag);
            if (lane == 0) mbar_arrive(s_empty + EM_PH * 8);
        } else {
            asm volatile("bar.arrive 6, 64;" ::: "memory");
            if (TM_PF && lane < 8) asm volatile("prefetch.tensormap [%0];" ::"l"(&maps.m[lane + ((wide && lane >= M_WG) ? 3 : 0)]) : "memory");
            mbar_wait(s_empty + EM_PH * 8);
            side = __float_as_uint(ldsf(sb + OFF_WMX + 112));
        }
        if (active) {
            int it = 0;
            do {
                ga = ldg_rlx1(scr + dual_near(G_MOD, 2 * 1152 + unit * 8 + r, side));
                gb = ldg_rlx1(scr + dual_near(G_MOD, 5 * 1152 + unit * 8 + r, side));
            } while (any_lane(((ga ^ tag) | (gb ^ tag)) & 7u) && ++it < SPIN_LIMIT);
            ga >>= 16; gb >>= 16;
        }
        __syncwarp();
        if (first) {
            const int ow = G_OP + kvh * 4096 + (g >> 2) * 2048;
            const unsigned* q = scr + ow + near_half(ow, side) + (g & 3) * 256 + j * 32 + t * 8;
            mbar_wait(s_full + it_v(15) * 8);
            uint4 lo, hi;
            int it = 0;
            do { lo = ldg_pkt(q); hi = ldg_pkt(q + 4); } while (any_lane(((lo.x ^ tag) | (hi.x ^ tag)) & 7u) && ++it < SPIN_LIMIT);
            float o[8] = {untagf(lo.x), __uint_as_float(lo.y), __uint_as_float(lo.z), __uint_as_float(lo.w),
                          untagf(hi.x), __uint_as_float(hi.y), __uint_as_float(hi.z), __uint_as_float(hi.w)};
            __syncwarp();
#pragma unroll
            for (int sft = 8; sft <= 16; sft <<= 1) {
#pragma unroll
                for (int i = 0; i < 8; i++) o[i] += shx(o[i], sft);
            }
            if (lane < 8)
                sts128(sb + OFF_FR + lane * 48, pack2(o[0], o[4]), pack2(o[2], o[6]), pack2(o[1], o[5]), pack2(o[3], o[7]));
            TS(lane == 0, 10);
        }
        asm volatile("bar.sync 3, 352;" ::: "memory");
        const unsigned* q = scr + G_PART + unit * 2048 + near_half(G_PART + unit * 2048, side) + lane * 4;
        if (DELAY_B) spin_cycles(DELAY_B);
        if (active) {
            const float k = reduce_unit(q, lane, tag);
            xold = badd2(xold, bmul2(ga, pack2(k, 0.f))) & 0xffffu;
#pragma unroll
            for (int i = 0; i < XREP; i += 2) stg_rlx1(scr + x1w + i * 4096, (xold << 16) | tag);
            TS(first && lane == 0, 12);
            TS(!first && lane == 0, 18);
        }
        if (first && lane == 0) mbar_arrive(s_empty + EM_X1 * 8);
        if (first) asm volatile("bar.sync 5, 128;" ::: "memory");
        else if (active) asm volatile("bar.sync 7, 128;" ::: "memory");
        if (active) {
            if (DELAY_D) spin_cycles(DELAY_D);
            const float k = reduce_unit(q, lane, tag | 4u);
            xold = badd2(xold, bmul2(gb, pack2(k, 0.f)));
            if (lane < 8) ((unsigned short*)out)[rcol] = (unsigned short)xold;
            if (c == 0 && first && lane == 0) stg_rlx1(scr + G_EPOCH, ep + 1u);
            TS(first && lane == 0, 16);
        }
        return;
    }

    const int vw = warp, tid = threadIdx.x;
    const int vecw = tid * 4 - (lane & 7) * 4 + t * 8 + bat * 4;
    unsigned* ppart = scr + G_PART + (vw * 16 + t * 4 + (g >> 1)) * 2048 + c * 8 + bat * 4;
    const unsigned* const pside = scr + G_SIDE + ((vw * 16 + t * 4 + (g >> 1)) & 127) * 8;
    const int qword = dual(G_Q, bat * 4096 + c * 32 + (tid >> 3) * 4 + t), mword = dual(G_MOD, c * 64 + (tid & 63));
    const uint32_t one2 = 0x3f803f80u;

    const unsigned ep = ldg_rlx1(scr + G_EPOCH);
    if (tid < 64) {
        if (c < NMOD) { stg_rlx1(scr + mword, 2u); stg_rlx1(scr + mword + HALF, 2u); }
        stg_rlx1(scr + qword, 2u); stg_rlx1(scr + qword + HALF, 2u);
    }
    uint32_t xw0, xw1, aw0, aw1;
    {
        const int col0 = bat * DM + (vw * 4 + mi) * 16 + 2 * t;
        const uint32_t cw0 = __ldg((const unsigned*)(cin + col0)), cw1 = __ldg((const unsigned*)(cin + col0 + 8));
        xw0 = __ldg((const unsigned*)(xin + col0)); xw1 = __ldg((const unsigned*)(xin + col0 + 8));
        if (lane == 0) {
            const int lo = (c < NMOD) ? 2 : 4;
#pragma unroll 1
            for (int i = vw; i < N_IT + N_EM; i += NCW) {
                const int e = i - N_IT;
                if (i >= lo) mbar_init(s_full + i * 8, (e < 0 || e >= EM_PH) ? 1 : (e < EM_K ? NCW : (e < EM_V ? 4 : 8)));
            }
            asm volatile("fence.proxy.async.shared::cta;" ::: "memory");
        }
        __syncwarp();
        asm volatile("bar.sync 2, 384;" ::: "memory");
        float cv[4] = {bflo(cw0), bfhi(cw0), bflo(cw1), bfhi(cw1)};
#pragma unroll
        for (int i = 0; i < 4; i++) cv[i] = cv[i] * rcp(1.0f + ex2(-1.4426950408889634f * cv[i]));
        aw0 = pack2(cv[0], cv[1]); aw1 = pack2(cv[2], cv[3]);
    }
    const unsigned tag = (ep + 1u) & 1u;
    const uint32_t st1 = sb + OFF_STAT + bat * 80, st2 = st1 + 160;
    ln_stage1(xw0, xw1, st1, vw, lane);

    if (c < NMOD) {
        const uint32_t m = gemv32(sb + OFF_WMOD, sb + OFF_RED, s_full + IT_WMOD * 8, s_empty + EM_WMOD * 8, aw0, aw1, tid);
        if (tid < 64) { stg_rlx1(scr + mword, m | tag); stg_rlx1(scr + mword + HALF, m | tag); }
    } else {
        bar_consumers();
    }
    TS(tid == 0, 4);
    mbar_wait(s_empty + EM_SD * 8);
    unsigned side = __float_as_uint(ldsf(sb + OFF_WMX + 116));
    {
        uint32_t y0, y1;
        ln_stage2(ln_load(st1), xw0, xw1, y0, y1);
        uint4 a, b;
        int it = 0;
        const unsigned *pa = scr + dual_near(G_MOD, vecw, side), *pb = scr + dual_near(G_MOD, 1152 + vecw, side);
        do { a = ldg_rlx4(pa); b = ldg_rlx4(pb); }
        while (any_lane((bad4(a, tag) | bad4(b, tag)) & 7u) && ++it < SPIN_LIMIT);
        __syncwarp();
        aw0 = badd2(bmul2(y0, badd2(one2, hi2(b.x, b.y))), hi2(a.x, a.y));
        aw1 = badd2(bmul2(y1, badd2(one2, hi2(b.z, b.w))), hi2(a.z, a.w));
        TS(tid == 0, 5);
        const uint32_t q = gemv32(sb + OFF_WQ, sb + OFF_RED + 2304, s_full + IT_WQ * 8, s_empty + EM_WQ * 8, aw0, aw1, tid);
        if (tid < 64) {
            stg_rlx1(scr + qword, q | tag); stg_rlx1(scr + qword + HALF, q | tag);
            uint4 v;
            int it = 0;
            const unsigned* pq = scr + dual_near(G_Q, bb * 4096 + kvh * 256 + tid * 4, side);
            do { v = ldg_rlx4(pq); } while (any_lane(bad4(v, tag) & 7u) && ++it < SPIN_LIMIT);
            sts64(sb + OFF_QS + (vw * 4 + t) * 80 + g * 8, hi2(v.x, v.y), hi2(v.z, v.w));
        }
        bar_consumers();
        TS(tid == 0, 6);
    }
    uint32_t sc0, sc1, sh0, sh1;
    {
        uint4 d, e;
        unsigned bad;
        int it = 0;
        do {
            d = ldg_rlx4(scr + dual_near(G_MOD, 3 * 1152 + vecw, side)); e = ldg_rlx4(scr + dual_near(G_MOD, 4 * 1152 + vecw, side));
            bad = bad4(d, tag) | bad4(e, tag);
        } while (any_lane(bad & 7u) && ++it < SPIN_LIMIT);
        __syncwarp();
        sh0 = hi2(d.x, d.y); sh1 = hi2(d.z, d.w);
        sc0 = badd2(one2, hi2(e.x, e.y)); sc1 = badd2(one2, hi2(e.z, e.w));
    }
    if (vw < 8) {
        uint4 qf[4];
#pragma unroll
        for (int i = 0; i < 4; i++) qf[i] = lds128(sb + OFF_QS + r * 80 + i * 16);
        const int mt = vw & 3;
        const uint32_t rowoff = (mt * 16 + r + 8 * (mi & 1)) * 128;
        const uint32_t sw = ((mi >> 1) ^ r) << 4;
        uint32_t mx = 0xff80ff80u;
#pragma unroll 1
        for (int i = (vw >> 2); i < 16; i += 2) {
            mbar_wait(s_full + (IT_K + i) * 8);
            const uint32_t base = sb + k_off(i) + rowoff;
            float c0[4] = {}, c1[4] = {};
            uint32_t a[4];
            ldsm4(a, base + sw);               mma16816(c0, a, qf[0].x, qf[0].y);
            ldsm4(a, base + 8192 + sw);        mma16816(c1, a, qf[2].x, qf[2].y);
            ldsm4(a, base + (sw ^ 32));        mma16816(c0, a, qf[0].z, qf[0].w);
            ldsm4(a, base + 8192 + (sw ^ 32)); mma16816(c1, a, qf[2].z, qf[2].w);
            ldsm4(a, base + (sw ^ 64));        mma16816(c0, a, qf[1].x, qf[1].y);
            ldsm4(a, base + 8192 + (sw ^ 64)); mma16816(c1, a, qf[3].x, qf[3].y);
            ldsm4(a, base + (sw ^ 96));        mma16816(c0, a, qf[1].z, qf[1].w);
            ldsm4(a, base + 8192 + (sw ^ 96)); mma16816(c1, a, qf[3].z, qf[3].w);
            __syncwarp();
            if (lane == 0) mbar_arrive(s_empty + (EM_K + i) * 8);
            const float scl = 0.08838834764831845f;
            uint32_t u0 = pack2(c0[0] + c1[0], c0[1] + c1[1]), u1 = pack2(c0[2] + c1[2], c0[3] + c1[3]);
            u0 = pack2(bflo(u0) * scl, bfhi(u0) * scl); u1 = pack2(bflo(u1) * scl, bfhi(u1) * scl);
            mx = bmax2(mx, bmax2(u0, u1));
            if (t == 0) {
                const uint32_t pa = sb + OFF_S + (i * 64 + 16 * (g >> 1) + 4 * mt + bat) * 4;
                sts32(pa, u0); sts32(pa + 8, u1);
            }
            if (i == PH_K && tid < 4) stg_ph(scr + G_ML + c * 8 + (tid & 1) * 4 + (tid & 2) * (HALF / 2));
        }
#pragma unroll
        for (int o = 4; o <= 16; o <<= 1) mx = bmax2(mx, __shfl_xor_sync(0xffffffffu, mx, o));
        if (lane == 0) sts32(sb + OFF_WMX + vw * 4, mx);
    }
    bar_consumers();
    TS(tid == 0, 7);
    {
        const float L2E = 1.4426950408889634f;
        uint4 sv = make_uint4(0, 0, 0, 0);
        float m0 = 0.f, m1 = 0.f;
        if (vw < 8) {
            uint4 ma = lds128(sb + OFF_WMX), mb = lds128(sb + OFF_WMX + 16);
            const uint32_t mx = bmax2(bmax2(bmax2(ma.x, ma.y), bmax2(ma.z, ma.w)), bmax2(bmax2(mb.x, mb.y), bmax2(mb.z, mb.w)));
            m0 = bflo(mx); m1 = bfhi(mx);
            sv = lds128(sb + OFF_S + tid * 16);
            float e0 = (ex2((bflo(sv.x) - m0) * L2E) + ex2((bflo(sv.y) - m0) * L2E)) + (ex2((bflo(sv.z) - m0) * L2E) + ex2((bflo(sv.w) - m0) * L2E));
            float e1 = (ex2((bfhi(sv.x) - m1) * L2E) + ex2((bfhi(sv.y) - m1) * L2E)) + (ex2((bfhi(sv.z) - m1) * L2E) + ex2((bfhi(sv.w) - m1) * L2E));
#pragma unroll
            for (int o = 16; o > 0; o >>= 1) { e0 += shx(e0, o); e1 += shx(e1, o); }
            if (lane == 0) sts64(sb + OFF_WMX + 32 + vw * 8, __float_as_uint(e0), __float_as_uint(e1));
        }
        bar_consumers();
        if (vw == 0) {
            float l0 = 0.f, l1 = 0.f;
#pragma unroll
            for (int w = 0; w < 4; w++) {
                uint4 s = lds128(sb + OFF_WMX + 32 + w * 16);
                l0 += __uint_as_float(s.x) + __uint_as_float(s.z); l1 += __uint_as_float(s.y) + __uint_as_float(s.w);
            }
            if (tid < 4) stg_pkt(scr + G_ML + c * 8 + (tid & 1) * 4 + (tid & 2) * (HALF / 2), m0, l0, m1, l1, tag);
            {
                const bool rd = lane < 4 && lane != sp;
                uint4 v = make_uint4(rd ? 2u : tag, 0, 0, 0);
                int it = 0;
                do { ldg_pkt_if(v, scr + G_ML + near_half(G_ML, side) + (kvh * 8 + (lane & 3) * 2 + bb) * 8, (v.x ^ tag) & 7u); }
                while (any_lane((v.x ^ tag) & 7u) && ++it < SPIN_LIMIT);
                if (rd) { m0 = untagf(v.x); l0 = __uint_as_float(v.y); m1 = __uint_as_float(v.z); l1 = __uint_as_float(v.w); }
            }
            float g0 = fmaxf(m0, shx(m0, 1)), g1 = fmaxf(m1, shx(m1, 1));
            g0 = fmaxf(g0, shx(g0, 2)); g1 = fmaxf(g1, shx(g1, 2));
            l0 *= ex2((m0 - g0) * L2E); l1 *= ex2((m1 - g1) * L2E);
            l0 += shx(l0, 1); l1 += shx(l1, 1);
            l0 += shx(l0, 2); l1 += shx(l1, 2);
            if (lane == 0)
                sts128(sb + OFF_WMX + 96, __float_as_uint(g0), __float_as_uint(g1), __float_as_uint(1.0f / l0), __float_as_uint(1.0f / l1));
        }
        bar_consumers();
        if (vw < 8) {
            const uint4 gs = lds128(sb + OFF_WMX + 96);
            const float g0 = __uint_as_float(gs.x), g1 = __uint_as_float(gs.y), i0 = __uint_as_float(gs.z), i1 = __uint_as_float(gs.w);
            const uint32_t a0 = pack2(ex2((bflo(sv.x) - g0) * L2E) * i0, ex2((bflo(sv.y) - g0) * L2E) * i0);
            const uint32_t a1 = pack2(ex2((bflo(sv.z) - g0) * L2E) * i0, ex2((bflo(sv.w) - g0) * L2E) * i0);
            const uint32_t b0 = pack2(ex2((bfhi(sv.x) - g1) * L2E) * i1, ex2((bfhi(sv.y) - g1) * L2E) * i1);
            const uint32_t b1 = pack2(ex2((bfhi(sv.z) - g1) * L2E) * i1, ex2((bfhi(sv.w) - g1) * L2E) * i1);
            sts64(sb + OFF_P + tid * 8, a0, a1); sts64(sb + OFF_P + PSTR + tid * 8, b0, b1);
        }
        bar_consumers();
        TS(tid == 0, 8);
    }
    const uint32_t rin = vw * 2048 + (r + 8 * (mi >> 1)) * 128;
    const uint32_t rsw = ((mi & 1) ^ r) << 4;
    uint32_t ra[2][4][4];
    unsigned sidew = 2u;
    if (vw < 8) {
        float c0[4] = {}, c1[4] = {};
        const uint32_t vo = (vw >> 2) * 8192 + (r + 8 * (mi >> 1)) * 128 + ((((2 * vw + (mi & 1)) & 7) ^ r) << 4);
        const uint32_t pa = sb + OFF_P + bat * PSTR + t * 32;
#pragma unroll 1
        for (int i = 0; i < 16; i++) {
            uint4 pb0 = lds128(pa + i * 128), pb1 = lds128(pa + i * 128 + 16);
            mbar_wait(s_full + it_v(i) * 8);
            const uint32_t base = sb + v_off(i) + vo;
            uint32_t a0[4], a1[4], a2[4], a3[4];
            ldsm4t(a0, base); ldsm4t(a1, base + 2048); ldsm4t(a2, base + 4096); ldsm4t(a3, base + 6144);
            mma16816(c0, a0, pb0.x, pb0.y);
            mma16816(c1, a1, pb0.z, pb0.w);
            mma16816(c0, a2, pb1.x, pb1.y);
            mma16816(c1, a3, pb1.z, pb1.w);
            __syncwarp();
            if (lane == 0) mbar_arrive(s_empty + (EM_V + i) * 8);
            if (i == SIDE_V) { mbar_wait(s_empty + EM_PH * 8); sidew = ldg_rlx1(pside); }
        }
        if (t < 2)
            stg_pkt(scr + G_OP + kvh * 4096 + (j >> 2) * 2048 + t * HALF + (j & 3) * 256 + vw * 32 + g * 4,
                    c0[0] + c1[0], c0[1] + c1[1], c0[2] + c1[2], c0[3] + c1[3], tag);
        TS(tid == 0, 9);
    } else {
        mbar_wait(s_full + it_v(SIDE_V) * 8);
        mbar_wait(s_empty + EM_PH * 8);
    }
    {
        int it = 0;
        while (any_lane((sidew ^ tag) & 7u) && ++it < SPIN_LIMIT) sidew = ldg_rlx1(pside);
        ppart += near_half(G_PART + (vw * 16 + t * 4 + (g >> 1)) * 2048, sidew >> 4);
    }
    side = __float_as_uint(ldsf(sb + OFF_WMX + 112));
    {
        mbar_wait(s_full + IT_WO * 8);
#pragma unroll
        for (int mt = 0; mt < 4; mt++) ldsm4t(ra[0][mt], sb + OFF_WO0 + rin + (rsw ^ (mt * 32)));
        mbar_wait(s_full + (IT_WO + 1) * 8);
#pragma unroll
        for (int mt = 0; mt < 4; mt++) ldsm4t(ra[1][mt], sb + OFF_WO1 + rin + (rsw ^ (mt * 32)));
        asm volatile("bar.sync 3, 352;" ::: "memory");
        const uint4 fr = lds128(sb + OFF_FR + r * 48);
        float cc[4][4] = {};
#pragma unroll
        for (int mt = 0; mt < 4; mt++) mma16816(cc[mt], ra[0][mt], fr.x, fr.y);
#pragma unroll
        for (int mt = 0; mt < 4; mt++) mma16816(cc[mt], ra[1][mt], fr.z, fr.w);
        publish_partials(ppart, t, cc, tag);
        TS(tid == 0, 11);
    }
    uint32_t ag[4][6][4];
    const uint32_t gub = s_full + (IT_GU + 2 * (vw / 3)) * 8;
    const uint32_t gpitch = wide ? 96 : 64, gsw = wide ? 0 : (r >> 1) << 4;
    const uint32_t gbase = sb + ((mi & 1) ? OFF_U : OFF_G) + (vw * 64 + r + 8 * (mi >> 1)) * gpitch;
    auto load_gu = [&]() {
#pragma unroll
        for (int ks = 0; ks < 4; ks++)
#pragma unroll
            for (int q = 0; q < 4; q++) ldsm4t(ag[ks][q], gbase + ks * 16 * gpitch + ((q << 4) ^ gsw));
        if (wide) {
#pragma unroll
            for (int ks = 0; ks < 4; ks++)
#pragma unroll
                for (int q = 4; q < 6; q++) ldsm4t(ag[ks][q], gbase + ks * 1536 + q * 16);
        }
    };
    bool gpre;
    while (true) {
        gpre = __all_sync(0xffffffffu, mbar_test(gub) && mbar_test(gub + 8));
        if (gpre || __all_sync(0xffffffffu, mbar_test(s_empty + EM_X1 * 8))) break;
    }
    if (gpre) {
        load_gu();
        mbar_wait(s_empty + EM_X1 * 8);
    }
    const uint32_t dbar = s_full + (IT_WD + (vw / 3 + 1) % 3) * 8;
    const uint32_t dbase = sb + OFF_D + ((vw / 3 + 1) % 3) * DSTR + (vw % 3) * (wide ? 6144 : 4096) + (r + 8 * (mi >> 1)) * 128;
    uint32_t ad[3][4][4];
    auto load_d = [&]() {
#pragma unroll
        for (int ks = 0; ks < 2; ks++)
#pragma unroll
            for (int mt = 0; mt < 4; mt++) ldsm4t(ad[ks][mt], dbase + ks * 2048 + (rsw ^ (mt * 32)));
        if (wide) {
#pragma unroll
            for (int mt = 0; mt < 4; mt++) ldsm4t(ad[2][mt], dbase + 4096 + (rsw ^ (mt * 32)));
        }
    };
    bool dpre;
    {
        uint4 v;
        int it = 0;
        const int xw = G_X1 + (vw >> 3) * 2048 + (c & (XREP - 1)) * 4096;
        const unsigned* px = scr + xw + near_half(xw, side) + (vecw & 1023);
        do { v = ldg_rlx4(px); } while (any_lane(bad4(v, tag) & 7u) && ++it < SPIN_LIMIT);
        xw0 = hi2(v.x, v.y); xw1 = hi2(v.z, v.w);
        ln_stage1(xw0, xw1, st2, vw, lane);
        bar_consumers();
        if (tid == 0) mbar_arrive(s_empty + EM_CH * 8);
        TS(tid == 0, 13);
        uint32_t y0, y1;
        ln_stage2(ln_load(st2), xw0, xw1, y0, y1);
        aw0 = badd2(bmul2(y0, sc0), sh0); aw1 = badd2(bmul2(y1, sc1), sh1);
        uint32_t bf[4][2];
        make_bfrags(bf, aw0, aw1, r);
        if (!gpre) { mbar_wait(gub); mbar_wait(gub + 8); load_gu(); }
        float cc[6][4] = {};
#pragma unroll
        for (int ks = 0; ks < 4; ks++)
#pragma unroll
            for (int q = 0; q < 4; q++) mma16816(cc[q], ag[ks][q], bf[ks][0], bf[ks][1]);
        if (wide) {
#pragma unroll
            for (int ks = 0; ks < 4; ks++)
#pragma unroll
                for (int q = 4; q < 6; q++) mma16816(cc[q], ag[ks][q], bf[ks][0], bf[ks][1]);
        }
        if (t == 0) {
#pragma unroll
            for (int q = 0; q < 6; q++) sts128f(sb + OFF_RED + vw * 768 + q * 128 + g * 16, cc[q]);
        }
        dpre = __all_sync(0xffffffffu, mbar_test(dbar));
        bar_consumers();
        TS(tid == 0, 14);
        if (tid < 192) {
            float sv[NCW];
#pragma unroll
            for (int w = 0; w < NCW; w++) sv[w] = ldsf(sb + OFF_RED + w * 768 + tid * 4);
            if (dpre) load_d();
            const float s = ((sv[0] + sv[1]) + (sv[2] + sv[3])) + ((sv[4] + sv[5]) + (sv[6] + sv[7])) + sv[8];
            const uint32_t gu = pack2(s, __shfl_down_sync(0xffffffffu, s, 2));
            const float gt = bflo(gu);
            const uint32_t hh = pack2(((gt > 0.f) ? gt : gt * 0.0f) * bfhi(gu), 0.f);
            const int rr = tid >> 2;
            if ((tid & 2) == 0)
                sts16(sb + OFF_FR + ((tid & 1) * 4 + ((rr & 7) >> 1)) * 48 + (rr >> 3) * 4 + (rr & 1) * 2, hh);
        } else if (dpre) {
            load_d();
        }
    }
    {
        bar_consumers();
        const uint4 fr = lds128(sb + OFF_FR + r * 48);
        const uint2 f2 = lds64(sb + OFF_FR + r * 48 + 16);
        if (!dpre) { mbar_wait(dbar); load_d(); }
        float cc[4][4] = {};
#pragma unroll
        for (int mt = 0; mt < 4; mt++) mma16816(cc[mt], ad[0][mt], fr.x, fr.y);
#pragma unroll
        for (int mt = 0; mt < 4; mt++) mma16816(cc[mt], ad[1][mt], fr.z, fr.w);
        if (wide) {
#pragma unroll
            for (int mt = 0; mt < 4; mt++) mma16816(cc[mt], ad[2][mt], f2.x, f2.y);
        }
        publish_partials(ppart, t, cc, tag | 4u);
        if (vw / 3 == c / 48) asm volatile("bar.arrive 5, 128;" ::: "memory");
        if (vw >= 6 && c < 16) asm volatile("bar.arrive 7, 128;" ::: "memory");
        TS(tid == 160, 15);
    }
}

typedef CUresult (*EncodeFn)(CUtensorMap*, CUtensorMapDataType, cuuint32_t, void*, const cuuint64_t*, const cuuint64_t*,
                             const cuuint32_t*, const cuuint32_t*, CUtensorMapInterleave, CUtensorMapSwizzle,
                             CUtensorMapL2promotion, CUtensorMapFloatOOBfill);

void make_map(EncodeFn enc, CUtensorMap* m, const void* p, cuuint64_t d0, cuuint64_t d1, cuuint64_t d2,
              cuuint64_t s1, cuuint64_t s2, cuuint32_t b0, cuuint32_t b1, cuuint32_t b2, CUtensorMapSwizzle sw,
              CUtensorMapL2promotion pr = CU_TENSOR_MAP_L2_PROMOTION_L2_128B) {
    cuuint64_t dims[3] = {d0, d1, d2};
    cuuint64_t str[2] = {s1, s2};
    cuuint32_t box[3] = {b0, b1, b2};
    cuuint32_t es[3] = {1, 1, 1};
    enc(m, CU_TENSOR_MAP_DATA_TYPE_BFLOAT16, 3, const_cast<void*>(p), dims, str, box, es,
        CU_TENSOR_MAP_INTERLEAVE_NONE, sw, pr, CU_TENSOR_MAP_FLOAT_OOB_FILL_NONE);
}

}

extern "C" void kernel_launch(void* const* d_in, const int* in_sizes, int n_in, void* d_out, int out_size) {
    (void)in_sizes; (void)n_in; (void)out_size;
    void* fn = nullptr;
    cudaDriverEntryPointQueryResult qr;
    cudaGetDriverEntryPoint("cuTensorMapEncodeTiled", &fn, cudaEnableDefault, &qr);
    EncodeFn enc = (EncodeFn)fn;
    cudaFuncSetAttribute(fused_block_kernel, cudaFuncAttributeMaxDynamicSharedMemorySize, SMEM_BYTES);

    const void *x = d_in[0], *kc = d_in[1], *vc = d_in[2], *wq = d_in[3], *wo = d_in[4];
    const void *wg = d_in[6], *wu = d_in[7], *wd = d_in[8], *cc = d_in[9], *wmod = d_in[10];
    const CUtensorMapSwizzle S128 = CU_TENSOR_MAP_SWIZZLE_128B, S64 = CU_TENSOR_MAP_SWIZZLE_64B, S0 = CU_TENSOR_MAP_SWIZZLE_NONE;
    void* raw = nullptr;
    cudaGetSymbolAddress(&raw, g_raw);
    unsigned* scr = (unsigned*)(((uintptr_t)raw + 0x1fffff) & ~(uintptr_t)0x1fffff);
    Maps m;
    make_map(enc, &m.m[M_K], kc, 64, 32ull * 32768, 2, 256, 128, 64, 64, 2, S128, CU_TENSOR_MAP_L2_PROMOTION_L2_256B);
    make_map(enc, &m.m[M_V], vc, 64, 32ull * 32768, 2, 256, 128, 64, 64, 2, S128, CU_TENSOR_MAP_L2_PROMOTION_L2_256B);
    make_map(enc, &m.m[M_WMOD], wmod, 3456, 144, 4, 3456 * 2, 3456 * 2 * 144, 32, 144, 2, S64);
    make_map(enc, &m.m[M_WQ], wq, 4096, 144, 4, 4096 * 2, 4096 * 2 * 144, 32, 144, 2, S64);
    make_map(enc, &m.m[M_WG], wg, 4608, 576, 1, 4608 * 2, 4608 * 2 * 576, 32, 192, 1, S64);
    make_map(enc, &m.m[M_WU], wu, 4608, 576, 1, 4608 * 2, 4608 * 2 * 576, 32, 192, 1, S64);
    make_map(enc, &m.m[M_WG48], wg, 4608, 576, 1, 4608 * 2, 4608 * 2 * 576, 48, 192, 1, S0);
    make_map(enc, &m.m[M_WU48], wu, 4608, 576, 1, 4608 * 2, 4608 * 2 * 576, 48, 192, 1, S0);
    make_map(enc, &m.m[M_WO], wo, 64, 4096, 9, 1152, 128, 64, 16, 9, S128);
    make_map(enc, &m.m[M_WD], wd, 64, 4608, 9, 1152, 128, 64, 32, 3, S128);
    make_map(enc, &m.m[M_WD48], wd, 64, 4608, 9, 1152, 128, 64, 48, 3, S128);
    fused_block_kernel<<<NCTA, NTHR, SMEM_BYTES>>>(m, (const __nv_bfloat16*)x, (const __nv_bfloat16*)cc,
                                                   (const __nv_bfloat16*)kc, (__nv_bfloat16*)d_out, scr TUNE_ARG);
}
```

```cpp
#include <cuda_runtime.h>
#include <cuda.h>
#include <cuda_bf16.h>
#include <stdint.h>

namespace {

constexpr int DM = 576;
constexpr int NCTA = 128;
constexpr int NCW = 9;
constexpr int NTHR = (NCW + 3) * 32;
constexpr int NMOD = 108;

#define WIN_MAIN 4
#define WIN_TAIL 3
#define WIN_SWITCH 38
#define PACE_GBS 3100
#define PACE_LEAD 28672
#define PACE_TAIL 2900
#define TAIL_GAP 250
#define PACE_D 3300
#define OPEN_WIN 1
#define DELAY_B 300
#define DELAY_D 150
#define CTL_GAIN 0
#define CTL_MAIN 57344
#define CTL_TAIL 40960
#define CTL_SWITCH 30
#define CTL_SUB 1
#define KVPAT 1
#define KVROT 1
#define WIN_G0 3
#define WIN_GN 0
#define EARLY_PF 8192
#define TM_PF 1
#define XREP 2
#define PH_V 7
#define SIDE_V 11
#define NPROBE 10
#define NPROBE0 3
#define PH_K 8

#define TUNE_PARAM
#define TUNE_ARG

constexpr int IT_WMOD = 0, IT_WQ = 2, IT_K = 4, IT_V = 20, IT_WO = 36, IT_GU = 38, IT_WD = 44, N_IT = 47;
__device__ __forceinline__ constexpr int it_v(int k) { return IT_V + k; }
constexpr int EM_WMOD = 0, EM_WQ = 1, EM_K = 2, EM_V = 18, EM_PH = 34, EM_X1 = 35, EM_CH = 36, EM_SD = 37, N_EM = 38;

constexpr int RING = 13 * 16384;
constexpr int OFF_WMOD = 0, OFF_WQ = 36864, OFF_K0 = 73728;
constexpr int OFF_WO0 = 194560, OFF_WO1 = 0, OFF_G = 18432, OFF_U = 73728;
constexpr int OFF_D = 129024, DSTR = 18432;
constexpr int PSTR = 2064;
constexpr int OFF_P = RING;
constexpr int OFF_S = OFF_P + 4160;
constexpr int OFF_RED = OFF_S + 4096;
constexpr int OFF_QS = OFF_RED + 6912;
constexpr int OFF_FR = OFF_QS + 640;
constexpr int OFF_STAT = OFF_FR + 384;
constexpr int OFF_WMX = OFF_STAT + 320;
constexpr int OFF_BAR = OFF_WMX + 128;
constexpr int SMEM_USED = OFF_BAR + (N_IT + N_EM) * 8;
constexpr int SMEM_BYTES = SMEM_USED + 1024;
static_assert(SMEM_BYTES <= 232448, "smem");

struct Maps { CUtensorMap m[11]; };
enum { M_K, M_V, M_WMOD, M_WQ, M_WO, M_WG, M_WU, M_WD, M_WG48, M_WU48, M_WD48 };

constexpr int HALF = 1024;
constexpr int G_PART = 0;
constexpr int G_OP = G_PART + 144 * 2048;
constexpr int G_X1 = G_OP + 16 * 4096;
constexpr int G_PROBE = G_X1 + XREP * 4096;
constexpr int G_SIDE = G_PROBE + 2048;
constexpr int G_EPOCH = G_SIDE + 1024;
constexpr int G_MOD = G_EPOCH + 1024;
constexpr int G_Q = G_MOD + 7 * 2048;
constexpr int G_ML = G_Q + 8 * 2048;
constexpr int G_WORDS = G_ML + 2048;
static_assert(G_MOD % 2048 == 0 && G_OP % 2048 == 0 && G_X1 % 2048 == 0 && G_PROBE % 2048 == 0, "halves");
static_assert(G_WORDS * 4 <= (2 << 20), "scratch must fit one 2 MB page");
__device__ __align__(128) unsigned g_raw[(2 << 20) / 4 + G_WORDS + 8192];
__device__ __forceinline__ int near_half(int w, unsigned side) { return ((__popc(w & 0x2C800) ^ side) & 1) << 10; }
__device__ __forceinline__ int dual(int base, int i) { return base + i + (i & ~1023); }
__device__ __forceinline__ int dual_near(int base, int i, unsigned side) { const int w = dual(base, i); return w + near_half(w, side); }
#define g_ts ((unsigned long long*)(scr + G_WORDS))

constexpr int SPIN_LIMIT = 1 << 20;

__device__ __forceinline__ uint32_t smem_u32(const void* p) { return (uint32_t)__cvta_generic_to_shared(p); }
__device__ __forceinline__ void mbar_init(uint32_t bar, int cnt) {
    asm volatile("mbarrier.init.shared::cta.b64 [%0], %1;" ::"r"(bar), "r"(cnt) : "memory");
}
__device__ __forceinline__ void mbar_expect_tx(uint32_t bar, uint32_t bytes) {
    asm volatile("mbarrier.arrive.expect_tx.shared::cta.b64 _, [%0], %1;" ::"r"(bar), "r"(bytes) : "memory");
}
__device__ __forceinline__ void mbar_arrive(uint32_t bar) {
    asm volatile("mbarrier.arrive.shared::cta.b64 _, [%0];" ::"r"(bar) : "memory");
}
__device__ __forceinline__ void mbar_wait(uint32_t bar) {
    asm volatile("{\n.reg .pred p;\nW_%=:\nmbarrier.try_wait.parity.shared::cta.b64 p, [%0], 0;\n@!p bra W_%=;\n}"
                 ::"r"(bar) : "memory");
}
__device__ __forceinline__ bool mbar_test(uint32_t bar) {
    uint32_t ok;
    asm volatile("{\n.reg .pred p;\nmbarrier.test_wait.parity.shared::cta.b64 p, [%1], 0;\nselp.u32 %0, 1, 0, p;\n}"
                 : "=r"(ok) : "r"(bar) : "memory");
    return ok;
}
__device__ __forceinline__ uint32_t gtime32() { uint32_t t; asm volatile("mov.u32 %0, %%globaltimer_lo;" : "=r"(t)); return t; }
__device__ __forceinline__ void tma3d(uint32_t dst, const CUtensorMap* m, int x, int y, int z, uint32_t bar) {
    asm volatile("cp.async.bulk.tensor.3d.shared::cluster.global.mbarrier::complete_tx::bytes [%0], [%1, {%3, %4, %5}], [%2];"
                 ::"r"(dst), "l"(m), "r"(bar), "r"(x), "r"(y), "r"(z) : "memory");
}
__device__ __forceinline__ void bar_consumers() { asm volatile("bar.sync 1, 288;" ::: "memory"); }

__device__ __forceinline__ void ldsm4(uint32_t (&a)[4], uint32_t addr) {
    asm volatile("ldmatrix.sync.aligned.m8n8.x4.shared.b16 {%0,%1,%2,%3}, [%4];"
                 : "=r"(a[0]), "=r"(a[1]), "=r"(a[2]), "=r"(a[3]) : "r"(addr) : "memory");
}
__device__ __forceinline__ void ldsm4t(uint32_t (&a)[4], uint32_t addr) {
    asm volatile("ldmatrix.sync.aligned.m8n8.x4.trans.shared.b16 {%0,%1,%2,%3}, [%4];"
                 : "=r"(a[0]), "=r"(a[1]), "=r"(a[2]), "=r"(a[3]) : "r"(addr) : "memory");
}
__device__ __forceinline__ void mma16816(float (&c)[4], const uint32_t (&a)[4], uint32_t b0, uint32_t b1) {
    asm volatile("mma.sync.aligned.m16n8k16.row.col.f32.bf16.bf16.f32 {%0,%1,%2,%3}, {%4,%5,%6,%7}, {%8,%9}, {%0,%1,%2,%3};"
                 : "+f"(c[0]), "+f"(c[1]), "+f"(c[2]), "+f"(c[3])
                 : "r"(a[0]), "r"(a[1]), "r"(a[2]), "r"(a[3]), "r"(b0), "r"(b1));
}
__device__ __forceinline__ float ldsf(uint32_t a) { float v; asm volatile("ld.shared.f32 %0, [%1];" : "=f"(v) : "r"(a) : "memory"); return v; }
__device__ __forceinline__ uint2 lds64(uint32_t a) {
    uint2 v; asm volatile("ld.shared.v2.u32 {%0,%1}, [%2];" : "=r"(v.x), "=r"(v.y) : "r"(a) : "memory"); return v;
}
__device__ __forceinline__ uint4 lds128(uint32_t a) {
    uint4 v; asm volatile("ld.shared.v4.u32 {%0,%1,%2,%3}, [%4];" : "=r"(v.x), "=r"(v.y), "=r"(v.z), "=r"(v.w) : "r"(a) : "memory"); return v;
}
__device__ __forceinline__ void sts16(uint32_t a, uint32_t v) { asm volatile("st.shared.u16 [%0], %1;" ::"r"(a), "h"((unsigned short)v) : "memory"); }
__device__ __forceinline__ void sts32(uint32_t a, uint32_t v) { asm volatile("st.shared.u32 [%0], %1;" ::"r"(a), "r"(v) : "memory"); }
__device__ __forceinline__ void sts64(uint32_t a, uint32_t x, uint32_t y) { asm volatile("st.shared.v2.u32 [%0], {%1,%2};" ::"r"(a), "r"(x), "r"(y) : "memory"); }
__device__ __forceinline__ void sts128(uint32_t a, uint32_t x, uint32_t y, uint32_t z, uint32_t w) {
    asm volatile("st.shared.v4.u32 [%0], {%1,%2,%3,%4};" ::"r"(a), "r"(x), "r"(y), "r"(z), "r"(w) : "memory");
}
__device__ __forceinline__ void sts128f(uint32_t a, const float (&c)[4]) {
    asm volatile("st.shared.v4.f32 [%0], {%1,%2,%3,%4};" ::"r"(a), "f"(c[0]), "f"(c[1]), "f"(c[2]), "f"(c[3]) : "memory");
}
__device__ __forceinline__ unsigned ldg_rlx1(const unsigned* p) {
    unsigned v; asm volatile("ld.relaxed.gpu.global.u32 %0, [%1];" : "=r"(v) : "l"(p) : "memory"); return v;
}
__device__ __forceinline__ uint4 ldg_rlx4(const unsigned* p) {
    uint4 v; asm volatile("ld.relaxed.gpu.global.v4.u32 {%0,%1,%2,%3}, [%4];" : "=r"(v.x), "=r"(v.y), "=r"(v.z), "=r"(v.w) : "l"(p) : "memory"); return v;
}
__device__ __forceinline__ uint4 ldg_pkt(const unsigned* p) {
    uint4 v;
    asm volatile("{\n.reg .b128 t;\n.reg .b64 lo, hi;\nld.relaxed.gpu.global.b128 t, [%4];\nmov.b128 {lo, hi}, t;\n"
                 "mov.b64 {%0,%1}, lo;\nmov.b64 {%2,%3}, hi;\n}"
                 : "=r"(v.x), "=r"(v.y), "=r"(v.z), "=r"(v.w) : "l"(p) : "memory");
    return v;
}
__device__ __forceinline__ void ldg_pkt_if(uint4& v, const unsigned* a, unsigned p) {
    asm volatile("{\n.reg .pred q;\n.reg .b128 t;\n.reg .b64 lo, hi;\nsetp.ne.u32 q, %5, 0;\n"
                 "mov.b64 lo, {%0,%1};\nmov.b64 hi, {%2,%3};\nmov.b128 t, {lo, hi};\n"
                 "@q ld.relaxed.gpu.global.b128 t, [%4];\nmov.b128 {lo, hi}, t;\n"
                 "mov.b64 {%0,%1}, lo;\nmov.b64 {%2,%3}, hi;\n}"
                 : "+r"(v.x), "+r"(v.y), "+r"(v.z), "+r"(v.w) : "l"(a), "r"(p) : "memory");
}
__device__ __forceinline__ bool any_lane(unsigned x) { return __any_sync(0xffffffffu, x != 0); }
__device__ __forceinline__ void stg_pkt(unsigned* p, float a, float b, float c, float d, unsigned tag) {
    unsigned x = (__float_as_uint(a) & ~7u) | tag;
    asm volatile("{\n.reg .b128 t;\n.reg .b64 lo, hi;\nmov.b64 lo, {%1,%2};\nmov.b64 hi, {%3,%4};\nmov.b128 t, {lo, hi};\n"
                 "st.relaxed.gpu.global.b128 [%0], t;\n}"
                 ::"l"(p), "r"(x), "r"(__float_as_uint(b)), "r"(__float_as_uint(c)), "r"(__float_as_uint(d)) : "memory");
}
__device__ __forceinline__ void stg_rlx1(unsigned* p, unsigned x) { asm volatile("st.relaxed.gpu.global.u32 [%0], %1;" ::"l"(p), "r"(x) : "memory"); }
__device__ __forceinline__ unsigned bad4(const uint4& v, unsigned tag) {
    return ((v.x ^ tag) | (v.y ^ tag)) | ((v.z ^ tag) | (v.w ^ tag));
}
__device__ __forceinline__ float untagf(unsigned w) { return __uint_as_float(w & ~7u); }
__device__ __forceinline__ uint32_t pack2(float lo, float hi) {
    uint32_t r; asm("cvt.rn.bf16x2.f32 %0, %1, %2;" : "=r"(r) : "f"(hi), "f"(lo)); return r;
}
__device__ __forceinline__ float bflo(uint32_t w) { return __uint_as_float(w << 16); }
__device__ __forceinline__ float bfhi(uint32_t w) { return __uint_as_float(w & 0xffff0000u); }
__device__ __forceinline__ uint32_t hi2(uint32_t a, uint32_t b) { return __byte_perm(a, b, 0x7632); }
__device__ __forceinline__ uint32_t badd2(uint32_t a, uint32_t b) { uint32_t r; asm("add.rn.bf16x2 %0, %1, %2;" : "=r"(r) : "r"(a), "r"(b)); return r; }
__device__ __forceinline__ uint32_t bsub2(uint32_t a, uint32_t b) { uint32_t r; asm("sub.rn.bf16x2 %0, %1, %2;" : "=r"(r) : "r"(a), "r"(b)); return r; }
__device__ __forceinline__ uint32_t bmul2(uint32_t a, uint32_t b) { uint32_t r; asm("mul.rn.bf16x2 %0, %1, %2;" : "=r"(r) : "r"(a), "r"(b)); return r; }
__device__ __forceinline__ uint32_t bmax2(uint32_t a, uint32_t b) { uint32_t r; asm("max.bf16x2 %0, %1, %2;" : "=r"(r) : "r"(a), "r"(b)); return r; }
__device__ __forceinline__ float ex2(float x) { float r; asm("ex2.approx.ftz.f32 %0, %1;" : "=f"(r) : "f"(x)); return r; }
__device__ __forceinline__ float rcp(float x) { float r; asm("rcp.approx.ftz.f32 %0, %1;" : "=f"(r) : "f"(x)); return r; }
__device__ __forceinline__ float fsqrt(float x) { float r; asm("sqrt.approx.ftz.f32 %0, %1;" : "=f"(r) : "f"(x)); return r; }
__device__ __forceinline__ float shx(float v, int m) { return __shfl_xor_sync(0xffffffffu, v, m); }
#define TS(cond, slot) do { } while (0)

__device__ __forceinline__ uint32_t k_off(int i) { return i < 8 ? OFF_K0 + i * 16384 : (i - 8) * 16384; }
__device__ __forceinline__ uint32_t v_off(int i) { return i < 5 ? (8 + i) * 16384 : (i - 5) * 16384; }

__device__ __forceinline__ void stg_ph(unsigned* p) { stg_pkt(p, 0.f, 0.f, 0.f, 0.f, 2u); }

__device__ __forceinline__ void ln_stage1(uint32_t xw0, uint32_t xw1, uint32_t st, int vw, int lane) {
    const float piv = __shfl_sync(0xffffffffu, bflo(xw0), lane & 4);
    const float d0 = bflo(xw0) - piv, d1 = bfhi(xw0) - piv, d2 = bflo(xw1) - piv, d3 = bfhi(xw1) - piv;
    float s1 = (d0 + d1) + (d2 + d3), s2 = (d0 * d0 + d1 * d1) + (d2 * d2 + d3 * d3);
    s1 += shx(s1, 1); s2 += shx(s2, 1);
    s1 += shx(s1, 2); s2 += shx(s2, 2);
    s1 += shx(s1, 8); s2 += shx(s2, 8);
    s1 += shx(s1, 16); s2 += shx(s2, 16);
    if ((lane & 27) == 0)
        sts64(st + vw * 8, __float_as_uint(piv + s1 * (1.0f / 64.0f)), __float_as_uint(s2 - s1 * s1 * (1.0f / 64.0f)));
}
struct LnStat { uint4 a, b, c, d; uint2 e; };
__device__ __forceinline__ LnStat ln_load(uint32_t st) {
    LnStat s; s.a = lds128(st); s.b = lds128(st + 16); s.c = lds128(st + 32); s.d = lds128(st + 48); s.e = lds64(st + 64);
    return s;
}
__device__ __forceinline__ void ln_stage2(const LnStat& s, uint32_t xw0, uint32_t xw1, uint32_t& y0, uint32_t& y1) {
    const float m[9] = {__uint_as_float(s.a.x), __uint_as_float(s.a.z), __uint_as_float(s.b.x), __uint_as_float(s.b.z),
                        __uint_as_float(s.c.x), __uint_as_float(s.c.z), __uint_as_float(s.d.x), __uint_as_float(s.d.z), __uint_as_float(s.e.x)};
    const float mean = (((m[0] + m[1]) + (m[2] + m[3])) + ((m[4] + m[5]) + (m[6] + m[7])) + m[8]) * (1.0f / NCW);
    const float m2 = ((__uint_as_float(s.a.y) + __uint_as_float(s.a.w)) + (__uint_as_float(s.b.y) + __uint_as_float(s.b.w))) +
                     ((__uint_as_float(s.c.y) + __uint_as_float(s.c.w)) + (__uint_as_float(s.d.y) + __uint_as_float(s.d.w))) + __uint_as_float(s.e.y);
    float d[9];
#pragma unroll
    for (int w = 0; w < 9; w++) d[w] = m[w] - mean;
    const float acc = (d[0] * d[0] + d[1] * d[1] + d[2] * d[2]) + (d[3] * d[3] + d[4] * d[4] + d[5] * d[5]) + (d[6] * d[6] + d[7] * d[7] + d[8] * d[8]);
    const float var = (m2 + 64.0f * acc) * (1.0f / DM);
    const uint32_t mv = pack2(mean, var);
    const float ve = bflo(pack2(bfhi(mv) + 1e-5f, 0.f));
    const float rinv = rcp(bflo(pack2(fsqrt(ve), 0.f)));
    const uint32_t mm = __byte_perm(mv, mv, 0x1010);
    const uint32_t e0 = bsub2(xw0, mm), e1 = bsub2(xw1, mm);
    y0 = pack2(bflo(e0) * rinv, bfhi(e0) * rinv); y1 = pack2(bflo(e1) * rinv, bfhi(e1) * rinv);
}
__device__ __forceinline__ void make_bfrags(uint32_t (&bf)[4][2], uint32_t aw0, uint32_t aw1, int r) {
#pragma unroll
    for (int ks = 0; ks < 4; ks++) {
        bf[ks][0] = __shfl_sync(0xffffffffu, aw0, ks * 8 + r);
        bf[ks][1] = __shfl_sync(0xffffffffu, aw1, ks * 8 + r);
    }
}
__device__ __forceinline__ uint32_t gemv32(uint32_t s_w, uint32_t red, uint32_t fullbar, uint32_t emptybar,
                                           uint32_t aw0, uint32_t aw1, int tid) {
    const int vw = tid >> 5, lane = tid & 31, g = lane >> 2, t = lane & 3, mi = lane >> 3, r = lane & 7;
    uint32_t bf[4][2];
    make_bfrags(bf, aw0, aw1, r);
    if (vw <= 4) mbar_wait(fullbar);
    if (vw >= 4) mbar_wait(fullbar + 8);
    float cc[2][4] = {};
    const uint32_t abase = s_w + (vw * 64 + r + 8 * (mi >> 1)) * 64;
    const uint32_t sw = ((mi & 1) ^ (r >> 1)) << 4;
#pragma unroll
    for (int ks = 0; ks < 4; ks++) {
#pragma unroll
        for (int mt = 0; mt < 2; mt++) {
            uint32_t a[4];
            ldsm4t(a, abase + ks * 1024 + (sw ^ (mt * 32)));
            mma16816(cc[mt], a, bf[ks][0], bf[ks][1]);
        }
    }
    if (t == 0) { sts128f(red + vw * 256 + g * 16, cc[0]); sts128f(red + vw * 256 + 128 + g * 16, cc[1]); }
    __syncwarp();
    if (lane == 0) mbar_arrive(emptybar);
    bar_consumers();
    float s = 0.f;
    if (tid < 64) {
        const uint32_t ra = red + ((tid & 58) | ((tid & 1) << 2) | ((tid >> 2) & 1)) * 4;
#pragma unroll
        for (int w = 0; w < NCW; w++) s += ldsf(ra + w * 256);
    }
    return pack2(0.f, s);
}
__device__ __forceinline__ void publish_partials(unsigned* q, int t, const float (&cc)[4][4], unsigned tag) {
    float v[4];
#pragma unroll
    for (int i = 0; i < 4; i++) {
        const float lo = (t & 1) ? cc[1][i] : cc[0][i], hi = (t & 1) ? cc[3][i] : cc[2][i];
        v[i] = (t & 2) ? hi : lo;
    }
    stg_pkt(q, v[0], v[1], v[2], v[3], tag);
}
__device__ __forceinline__ void spin_cycles(unsigned n) {
    const unsigned c0 = clock();
    while ((unsigned)clock() - c0 < n) { }
}
__device__ __forceinline__ float reduce_unit(const unsigned* q, int lane, unsigned tag) {
    uint4 v[8];
#pragma unroll
    for (int i = 0; i < 8; i++) v[i] = ldg_pkt(q + i * 128);
    int it = 0;
    while (true) {
        unsigned bad = 0;
#pragma unroll
        for (int i = 0; i < 8; i += 2) bad |= (v[i].x ^ tag) | (v[i + 1].x ^ tag);
        if (!any_lane(bad & 7u) || ++it >= SPIN_LIMIT) break;
#pragma unroll
        for (int i = 0; i < 8; i++) ldg_pkt_if(v[i], q + i * 128, (v[i].x ^ tag) & 7u);
    }
    float s0 = 0.f, s1 = 0.f, s2 = 0.f, s3 = 0.f, u0 = 0.f, u1 = 0.f, u2 = 0.f, u3 = 0.f;
#pragma unroll
    for (int i = 0; i < 8; i += 2) {
        s0 += untagf(v[i].x); s1 += __uint_as_float(v[i].y); s2 += __uint_as_float(v[i].z); s3 += __uint_as_float(v[i].w);
        u0 += untagf(v[i + 1].x); u1 += __uint_as_float(v[i + 1].y); u2 += __uint_as_float(v[i + 1].z); u3 += __uint_as_float(v[i + 1].w);
    }
    s0 += u0; s1 += u1; s2 += u2; s3 += u3;
    __syncwarp();
    const bool h8 = lane & 2, bat = lane & 4;
    const float k0 = (h8 ? s2 : s0) + shx(h8 ? s0 : s2, 2);
    const float k1 = (h8 ? s3 : s1) + shx(h8 ? s1 : s3, 2);
    float k = (bat ? k1 : k0) + shx(bat ? k0 : k1, 4);
    k += shx(k, 8);
    k += shx(k, 16);
    return k;
}

__global__ void __launch_bounds__(NTHR, 1)
fused_block_kernel(const __grid_constant__ Maps maps, const __nv_bfloat16* __restrict__ xin,
                   const __nv_bfloat16* __restrict__ cin, const __nv_bfloat16* __restrict__ kcache,
                   __nv_bfloat16* __restrict__ out, unsigned* const scr TUNE_PARAM) {
    extern __shared__ unsigned char smem_raw[];
    const int c = blockIdx.x;
    const int kvh = c >> 3, j = c & 7, bb = j & 1, sp = j >> 1;
    const bool wide = j >= 6;
    const int f0 = kvh * 288 + (wide ? 48 * j - 96 : 32 * j);
    const int kvrow0 = (bb * 16 + kvh) * 32768 + 28672 + sp * (KVPAT ? 64 : 1024);
    const int kvstep = KVPAT ? 256 : 64;
    if (EARLY_PF && threadIdx.x == 0)
        asm volatile("cp.async.bulk.prefetch.L2.global [%0], %1;" ::"l"((const char*)kcache + (size_t)kvrow0 * 256), "r"(EARLY_PF) : "memory");
    TS(threadIdx.x == 0, 0);
    const uint32_t sb = (smem_u32(smem_raw) + 1023u) & ~1023u;
    const int warp = threadIdx.x >> 5, lane = threadIdx.x & 31;
    const uint32_t s_full = sb + OFF_BAR, s_empty = s_full + N_IT * 8;

    if (warp == NCW) {
        const uint32_t t0 = gtime32();
        const int first = (c < NMOD) ? 0 : 2;
        if (lane == 0) {
#pragma unroll
            for (int i = 0; i < 2; i++) mbar_init(s_full + (first + i) * 8, 1);
            asm volatile("fence.proxy.async.shared::cta;" ::: "memory");
#pragma unroll
            for (int i = 0; i < 2; i++) {
                const uint32_t bar = s_full + (first + i) * 8;
                mbar_expect_tx(bar, 18432);
                tma3d(sb + (first + i) * 18432, &maps.m[M_WMOD + (first >> 1)], c * 32, 0, i * 2, bar);
            }
            TS(true, 17);
        }
        __syncwarp();
        uint32_t w0[2], w1[2], w2[2];
#pragma unroll
        for (int h = 0; h < 2; h++) {
            const int i = lane + 32 * h;
            int off, map, dep = -1, x = 0, y = 0, z = 0, sz = 36, cum;
            if (i < IT_K) {
                off = i * 18432; map = M_WMOD + (i >> 1); x = c * 32; z = (i & 1) * 2; cum = 31104 + (i - 2) * 18432;
            } else if (i < IT_V) {
                const int k = i - IT_K;
                off = k_off(k); map = M_K; y = kvrow0 + k * kvstep; sz = 32; cum = 67968 + k * 16384;
                if (k == 8 && c < NMOD) dep = EM_WMOD;
                if (k == 10) dep = EM_WQ;
                if (k >= 12) dep = EM_K + k - 12;
            } else if (i < IT_WO) {
                const int k = i - IT_V;
                off = v_off(k); map = M_V; y = kvrow0 + k * kvstep; sz = 32; cum = 330112 + k * 16384;
                dep = EM_K + 3 + k + (k < 4);
            } else if (i < IT_GU) {
                const int k = i - IT_WO;
                off = k ? OFF_WO1 : OFF_WO0; map = M_WO; y = kvh * 256 + k * 128 + j * 16; dep = EM_V + 4 + 2 * k;
                cum = 592256 + k * 18432;
            } else if (i < IT_WD) {
                const int k = i - IT_GU;
                sz = wide ? 36 : 24;
                off = ((k & 1) ? OFF_U : OFF_G) + (k >> 1) * sz * 512; map = M_WG + (k & 1) + (wide ? 3 : 0);
                x = f0; y = (k >> 1) * 192; dep = EM_V + 5 + ((off + sz * 512 - 1) >> 14);
                cum = 629120 + k * 13824;
            } else {
                const int k = i - IT_WD;
                off = OFF_D + k * DSTR; map = wide ? M_WD48 : M_WD; y = f0; z = ((k + 2) % 3) * 3; sz = wide ? 36 : 24; dep = EM_V + (k ? 15 : 13);
                cum = 712064 + k * 13824;
            }
            const int stag = (KVROT && i >= IT_K && i < IT_WO) ? (((kvh * 2 + bb) * 13) & 31) * 512 + sp * (KVROT - 1) * 128 : ((c * 37) & 127) * 128;
            cum += EARLY_PF - min(max(cum - 67968, 0), EARLY_PF);
            int due = (int)((float)max(min(cum, 629120) + stag - PACE_LEAD, 0) * (128.0f / PACE_GBS));
            if (i >= IT_GU) due += TAIL_GAP + (int)((float)(min(cum, 712064) - 629120) * (128.0f / PACE_TAIL));
            if (i >= IT_WD) due += (int)((float)(cum - 712064) * (128.0f / PACE_D));
            w0[h] = off | (map << 18) | ((dep + 1) << 22) | (z << 28);
            w1[h] = y | (sz << 24);
            w2[h] = x | (due << 13);
        }
        asm volatile("bar.sync 2, 384;" ::: "memory");
        uint32_t fb = s_full;
        asm volatile("" : "+r"(fb));
        bool open = false;
#pragma unroll 1
        for (int i = first + 2; i < N_IT; i++) {
            const bool hi = i >= 32;
            const uint32_t a = __shfl_sync(0xffffffffu, hi ? w0[1] : w0[0], i);
            const uint32_t b = __shfl_sync(0xffffffffu, hi ? w1[1] : w1[0], i);
            const uint32_t x = __shfl_sync(0xffffffffu, hi ? w2[1] : w2[0], i);
            if (lane == 0) {
                const uint32_t bar = fb + i * 8;
                if (!open) {
                    const int win = (i >= IT_GU && i < IT_GU + WIN_GN) ? WIN_G0 : (i >= WIN_SWITCH) ? WIN_TAIL : WIN_MAIN;
                    const int dep = (a >> 22) & 63;
                    const uint32_t due = t0 + (x >> 13);
                    if (dep) mbar_wait(fb + (N_IT - 1 + dep) * 8);
                    if (i < IT_GU || !OPEN_WIN) {
                        if (i - win >= first) mbar_wait(bar - win * 8);
                        while ((int)(gtime32() - due) < 0) { }
                    } else {
                        const uint32_t ch = fb + (N_IT + EM_CH) * 8;
                        while (!mbar_test(bar - win * 8)) { if (mbar_test(ch)) { open = true; break; } }
                        while (!open && (int)(gtime32() - due) < 0) open = mbar_test(ch);
                    }
                }
                if (open && OPEN_WIN > 1) mbar_wait(bar - OPEN_WIN * 8);
                mbar_expect_tx(bar, (b >> 24) * 512);
                tma3d(fb - OFF_BAR + (a & 0x3ffff), &maps.m[(a >> 18) & 15], x & 0x1fff, b & 0xffffff, a >> 28, bar);
                TS(i == IT_WO, 1);
                TS(i == N_IT - 1, 2);
            }
            __syncwarp();
        }
        return;
    }

    const int g = lane >> 2, t = lane & 3, mi = lane >> 3, r = lane & 7;
    const int bat = g & 1;

    if (warp > NCW) {
        const bool first = warp == NCW + 1, active = first || c < 16;
        const int unit = first ? c : NCTA + c;
        const int rcol = (unit >> 2) * 16 + (unit & 3) * 2 + (lane & 1) + (lane & 2) * 4 + bat * DM;
        const unsigned ep = ldg_rlx1(scr + G_EPOCH);
        uint32_t xold = 0, ga = 0, gb = 0;
        if (active) xold = __ldg((const unsigned short*)xin + rcol);
        if (!first) asm volatile("bar.sync 2, 384;" ::: "memory");
        const unsigned tag = (ep + 1u) & 1u;
        unsigned side = 0;
        const int x1w = G_X1 + (unit >> 7) * 2048 + (unit & 127) * 8 + r + (lane & 8) * (HALF / 8) + (lane >> 4) * 4096;
        if (first) {
            unsigned* pr = scr + G_PROBE + c * 8;
            if (lane < 16) stg_rlx1(pr + r + (lane & 8) * (HALF / 8), 0u);
            __syncwarp();
            asm volatile("bar.arrive 2, 384;" ::: "memory");
            unsigned best0 = ~0u, best1 = ~0u, v = 0, cp = 0;
#pragma unroll 1
            for (int i = 0; i <= 2 * NPROBE; i++) {
                if (lane == 0) {
                    asm volatile("atom.relaxed.gpu.global.add.u32 %0, [%1], 1;" : "=r"(v) : "l"(pr + (i & 1) * HALF + (v >> 31)) : "memory");
                    const unsigned cn = clock(), d = cn - cp;
                    cp = cn;
                    if (i & 1) best0 = min(best0, d); else if (i) best1 = min(best1, d);
                    side = (best1 < best0) ^ (__popc(G_PROBE & 0x2C800) & 1);
                }
                if (i == 2 * NPROBE0) {
                    asm volatile("bar.sync 6, 64;" ::: "memory");
                    if (lane == 0) { sts32(sb + OFF_WMX + 116, side); mbar_arrive(s_empty + EM_SD * 8); }
                }
            }
            if (lane == 0) sts32(sb + OFF_WMX + 112, side);
            side = __shfl_sync(0xffffffffu, side, 0);
            mbar_wait(s_full + it_v(PH_V) * 8);
#pragma unroll 1
            for (int u = c; u < 144; u += NCTA) {
                unsigned* q = scr + G_PART + u * 2048 + near_half(G_PART + u * 2048, side) + lane * 4;
#pragma unroll
                for (int i = 0; i < 8; i++) stg_ph(q + i * 128);
#pragma unroll
                for (int i = 0; i < XREP; i += 2) stg_rlx1(scr + x1w + (u >> 7) * 2048 + i * 4096, 2u);
            }
            unsigned* o = scr + G_OP + kvh * 4096 + (j >> 2) * 2048 + (j & 3) * 256 + lane * 4;
            stg_ph(o); stg_ph(o + 128); stg_ph(o + HALF); stg_ph(o + HALF + 128);
            __threadfence();
            __syncwarp();
            if (lane < 8) stg_rlx1(scr + G_SIDE + c * 8 + lane, (side << 4) | tag);
            if (lane == 0) mbar_arrive(s_empty + EM_PH * 8);
        } else {
            asm volatile("bar.arrive 6, 64;" ::: "memory");
            if (TM_PF && lane < 8) asm volatile("prefetch.tensormap [%0];" ::"l"(&maps.m[lane + ((wide && lane >= M_WG) ? 3 : 0)]) : "memory");
            mbar_wait(s_empty + EM_PH * 8);
            side = __float_as_uint(ldsf(sb + OFF_WMX + 112));
        }
        if (active) {
            int it = 0;
            do {
                ga = ldg_rlx1(scr + dual_near(G_MOD, 2 * 1152 + unit * 8 + r, side));
                gb = ldg_rlx1(scr + dual_near(G_MOD, 5 * 1152 + unit * 8 + r, side));
            } while (any_lane(((ga ^ tag) | (gb ^ tag)) & 7u) && ++it < SPIN_LIMIT);
            ga >>= 16; gb >>= 16;
        }
        __syncwarp();
        if (first) {
            const int ow = G_OP + kvh * 4096 + (g >> 2) * 2048;
            const unsigned* q = scr + ow + near_half(ow, side) + (g & 3) * 256 + j * 32 + t * 8;
            mbar_wait(s_full + it_v(15) * 8);
            uint4 lo, hi;
            int it = 0;
            do { lo = ldg_pkt(q); hi = ldg_pkt(q + 4); } while (any_lane(((lo.x ^ tag) | (hi.x ^ tag)) & 7u) && ++it < SPIN_LIMIT);
            float o[8] = {untagf(lo.x), __uint_as_float(lo.y), __uint_as_float(lo.z), __uint_as_float(lo.w),
                          untagf(hi.x), __uint_as_float(hi.y), __uint_as_float(hi.z), __uint_as_float(hi.w)};
            __syncwarp();
#pragma unroll
            for (int sft = 8; sft <= 16; sft <<= 1) {
#pragma unroll
                for (int i = 0; i < 8; i++) o[i] += shx(o[i], sft);
            }
            if (lane < 8)
                sts128(sb + OFF_FR + lane * 48, pack2(o[0], o[4]), pack2(o[2], o[6]), pack2(o[1], o[5]), pack2(o[3], o[7]));
            TS(lane == 0, 10);
        }
        asm volatile("bar.sync 3, 352;" ::: "memory");
        const unsigned* q = scr + G_PART + unit * 2048 + near_half(G_PART + unit * 2048, side) + lane * 4;
        if (!active) return;
#pragma unroll 1
        for (int ph = 0; ph < 2; ph++) {
            if (ph) asm volatile("bar.sync %0, 128;" ::"r"(first ? 5 : 7) : "memory");
            spin_cycles(ph ? DELAY_D : DELAY_B);
            const float k = reduce_unit(q, lane, tag | (ph * 4u));
            xold = badd2(xold, bmul2(ga, pack2(k, 0.f))) & 0xffffu;
            ga = gb;
            if (ph) {
                if (lane < 8) ((unsigned short*)out)[rcol] = (unsigned short)xold;
            } else {
#pragma unroll
                for (int i = 0; i < XREP; i += 2) stg_rlx1(scr + x1w + i * 4096, (xold << 16) | tag);
                if (first && lane == 0) mbar_arrive(s_empty + EM_X1 * 8);
            }
            TS(first && lane == 0, 12 + 4 * ph);
        }
        if (c == 0 && first && lane == 0) stg_rlx1(scr + G_EPOCH, ep + 1u);
        return;
    }

    const int vw = warp, tid = threadIdx.x;
    const int vecw = tid * 4 - (lane & 7) * 4 + t * 8 + bat * 4;
    unsigned* ppart = scr + G_PART + (vw * 16 + t * 4 + (g >> 1)) * 2048 + c * 8 + bat * 4;
    const unsigned* const pside = scr + G_SIDE + ((vw * 16 + t * 4 + (g >> 1)) & 127) * 8;
    const int qword = dual(G_Q, bat * 4096 + c * 32 + (tid >> 3) * 4 + t), mword = dual(G_MOD, c * 64 + (tid & 63));
    const uint32_t one2 = 0x3f803f80u;

    const unsigned ep = ldg_rlx1(scr + G_EPOCH);
    if (tid < 64) {
        if (c < NMOD) { stg_rlx1(scr + mword, 2u); stg_rlx1(scr + mword + HALF, 2u); }
        stg_rlx1(scr + qword, 2u); stg_rlx1(scr + qword + HALF, 2u);
    }
    uint32_t xw0, xw1, aw0, aw1;
    {
        const int col0 = bat * DM + (vw * 4 + mi) * 16 + 2 * t;
        const uint32_t cw0 = __ldg((const unsigned*)(cin + col0)), cw1 = __ldg((const unsigned*)(cin + col0 + 8));
        xw0 = __ldg((const unsigned*)(xin + col0)); xw1 = __ldg((const unsigned*)(xin + col0 + 8));
        if (lane == 0) {
            const int lo = (c < NMOD) ? 2 : 4;
#pragma unroll 1
            for (int i = vw; i < N_IT + N_EM; i += NCW) {
                const int e = i - N_IT;
                if (i >= lo) mbar_init(s_full + i * 8, (e < 0 || e >= EM_PH) ? 1 : (e < EM_K ? NCW : (e < EM_V ? 4 : 8)));
            }
            asm volatile("fence.proxy.async.shared::cta;" ::: "memory");
        }
        __syncwarp();
        asm volatile("bar.sync 2, 384;" ::: "memory");
        float cv[4] = {bflo(cw0), bfhi(cw0), bflo(cw1), bfhi(cw1)};
#pragma unroll
        for (int i = 0; i < 4; i++) cv[i] = cv[i] * rcp(1.0f + ex2(-1.4426950408889634f * cv[i]));
        aw0 = pack2(cv[0], cv[1]); aw1 = pack2(cv[2], cv[3]);
    }
    const unsigned tag = (ep + 1u) & 1u;
    const uint32_t st1 = sb + OFF_STAT + bat * 80, st2 = st1 + 160;
    ln_stage1(xw0, xw1, st1, vw, lane);

    if (c < NMOD) {
        const uint32_t m = gemv32(sb + OFF_WMOD, sb + OFF_RED, s_full + IT_WMOD * 8, s_empty + EM_WMOD * 8, aw0, aw1, tid);
        if (tid < 64) { stg_rlx1(scr + mword, m | tag); stg_rlx1(scr + mword + HALF, m | tag); }
    } else {
        bar_consumers();
    }
    TS(tid == 0, 4);
    mbar_wait(s_empty + EM_SD * 8);
    unsigned side = __float_as_uint(ldsf(sb + OFF_WMX + 116));
    {
        uint32_t y0, y1;
        ln_stage2(ln_load(st1), xw0, xw1, y0, y1);
        uint4 a, b;
        int it = 0;
        const unsigned *pa = scr + dual_near(G_MOD, vecw, side), *pb = scr + dual_near(G_MOD, 1152 + vecw, side);
        do { a = ldg_rlx4(pa); b = ldg_rlx4(pb); }
        while (any_lane((bad4(a, tag) | bad4(b, tag)) & 7u) && ++it < SPIN_LIMIT);
        __syncwarp();
        aw0 = badd2(bmul2(y0, badd2(one2, hi2(b.x, b.y))), hi2(a.x, a.y));
        aw1 = badd2(bmul2(y1, badd2(one2, hi2(b.z, b.w))), hi2(a.z, a.w));
        TS(tid == 0, 5);
        const uint32_t q = gemv32(sb + OFF_WQ, sb + OFF_RED + 2304, s_full + IT_WQ * 8, s_empty + EM_WQ * 8, aw0, aw1, tid);
        if (tid < 64) {
            stg_rlx1(scr + qword, q | tag); stg_rlx1(scr + qword + HALF, q | tag);
            uint4 v;
            int it = 0;
            const unsigned* pq = scr + dual_near(G_Q, bb * 4096 + kvh * 256 + tid * 4, side);
            do { v = ldg_rlx4(pq); } while (any_lane(bad4(v, tag) & 7u) && ++it < SPIN_LIMIT);
            sts64(sb + OFF_QS + (vw * 4 + t) * 80 + g * 8, hi2(v.x, v.y), hi2(v.z, v.w));
        }
        bar_consumers();
        TS(tid == 0, 6);
    }
    uint32_t sc0, sc1, sh0, sh1;
    {
        uint4 d, e;
        unsigned bad;
        int it = 0;
        do {
            d = ldg_rlx4(scr + dual_near(G_MOD, 3 * 1152 + vecw, side)); e = ldg_rlx4(scr + dual_near(G_MOD, 4 * 1152 + vecw, side));
            bad = bad4(d, tag) | bad4(e, tag);
        } while (any_lane(bad & 7u) && ++it < SPIN_LIMIT);
        __syncwarp();
        sh0 = hi2(d.x, d.y); sh1 = hi2(d.z, d.w);
        sc0 = badd2(one2, hi2(e.x, e.y)); sc1 = badd2(one2, hi2(e.z, e.w));
    }
    if (vw < 8) {
        uint4 qf[4];
#pragma unroll
        for (int i = 0; i < 4; i++) qf[i] = lds128(sb + OFF_QS + r * 80 + i * 16);
        const int mt = vw & 3;
        const uint32_t rowoff = (mt * 16 + r + 8 * (mi & 1)) * 128;
        const uint32_t sw = ((mi >> 1) ^ r) << 4;
        uint32_t mx = 0xff80ff80u;
#pragma unroll 1
        for (int i = (vw >> 2); i < 16; i += 2) {
            mbar_wait(s_full + (IT_K + i) * 8);
            const uint32_t base = sb + k_off(i) + rowoff;
            float c0[4] = {}, c1[4] = {};
            uint32_t a[4];
            ldsm4(a, base + sw);               mma16816(c0, a, qf[0].x, qf[0].y);
            ldsm4(a, base + 8192 + sw);        mma16816(c1, a, qf[2].x, qf[2].y);
            ldsm4(a, base + (sw ^ 32));        mma16816(c0, a, qf[0].z, qf[0].w);
            ldsm4(a, base + 8192 + (sw ^ 32)); mma16816(c1, a, qf[2].z, qf[2].w);
            ldsm4(a, base + (sw ^ 64));        mma16816(c0, a, qf[1].x, qf[1].y);
            ldsm4(a, base + 8192 + (sw ^ 64)); mma16816(c1, a, qf[3].x, qf[3].y);
            ldsm4(a, base + (sw ^ 96));        mma16816(c0, a, qf[1].z, qf[1].w);
            ldsm4(a, base + 8192 + (sw ^ 96)); mma16816(c1, a, qf[3].z, qf[3].w);
            __syncwarp();
            if (lane == 0) mbar_arrive(s_empty + (EM_K + i) * 8);
            const float scl = 0.08838834764831845f;
            uint32_t u0 = pack2(c0[0] + c1[0], c0[1] + c1[1]), u1 = pack2(c0[2] + c1[2], c0[3] + c1[3]);
            u0 = pack2(bflo(u0) * scl, bfhi(u0) * scl); u1 = pack2(bflo(u1) * scl, bfhi(u1) * scl);
            mx = bmax2(mx, bmax2(u0, u1));
            if (t == 0) {
                const uint32_t pa = sb + OFF_S + (i * 64 + 16 * (g >> 1) + 4 * mt + bat) * 4;
                sts32(pa, u0); sts32(pa + 8, u1);
            }
            if (i == PH_K && tid < 4) stg_ph(scr + G_ML + c * 8 + (tid & 1) * 4 + (tid & 2) * (HALF / 2));
        }
#pragma unroll
        for (int o = 4; o <= 16; o <<= 1) mx = bmax2(mx, __shfl_xor_sync(0xffffffffu, mx, o));
        if (lane == 0) sts32(sb + OFF_WMX + vw * 4, mx);
    }
    bar_consumers();
    TS(tid == 0, 7);
    {
        const float L2E = 1.4426950408889634f;
        uint4 sv = make_uint4(0, 0, 0, 0);
        float m0 = 0.f, m1 = 0.f;
        if (vw < 8) {
            uint4 ma = lds128(sb + OFF_WMX), mb = lds128(sb + OFF_WMX + 16);
            const uint32_t mx = bmax2(bmax2(bmax2(ma.x, ma.y), bmax2(ma.z, ma.w)), bmax2(bmax2(mb.x, mb.y), bmax2(mb.z, mb.w)));
            m0 = bflo(mx); m1 = bfhi(mx);
            sv = lds128(sb + OFF_S + tid * 16);
            float e0 = (ex2((bflo(sv.x) - m0) * L2E) + ex2((bflo(sv.y) - m0) * L2E)) + (ex2((bflo(sv.z) - m0) * L2E) + ex2((bflo(sv.w) - m0) * L2E));
            float e1 = (ex2((bfhi(sv.x) - m1) * L2E) + ex2((bfhi(sv.y) - m1) * L2E)) + (ex2((bfhi(sv.z) - m1) * L2E) + ex2((bfhi(sv.w) - m1) * L2E));
#pragma unroll
            for (int o = 16; o > 0; o >>= 1) { e0 += shx(e0, o); e1 += shx(e1, o); }
            if (lane == 0) sts64(sb + OFF_WMX + 32 + vw * 8, __float_as_uint(e0), __float_as_uint(e1));
        }
        bar_consumers();
        if (vw == 0) {
            float l0 = 0.f, l1 = 0.f;
#pragma unroll
            for (int w = 0; w < 4; w++) {
                uint4 s = lds128(sb + OFF_WMX + 32 + w * 16);
                l0 += __uint_as_float(s.x) + __uint_as_float(s.z); l1 += __uint_as_float(s.y) + __uint_as_float(s.w);
            }
            if (tid < 4) stg_pkt(scr + G_ML + c * 8 + (tid & 1) * 4 + (tid & 2) * (HALF / 2), m0, l0, m1, l1, tag);
            {
                const bool rd = lane < 4 && lane != sp;
                uint4 v = make_uint4(rd ? 2u : tag, 0, 0, 0);
                int it = 0;
                do { ldg_pkt_if(v, scr + G_ML + near_half(G_ML, side) + (kvh * 8 + (lane & 3) * 2 + bb) * 8, (v.x ^ tag) & 7u); }
                while (any_lane((v.x ^ tag) & 7u) && ++it < SPIN_LIMIT);
                if (rd) { m0 = untagf(v.x); l0 = __uint_as_float(v.y); m1 = __uint_as_float(v.z); l1 = __uint_as_float(v.w); }
            }
            float g0 = fmaxf(m0, shx(m0, 1)), g1 = fmaxf(m1, shx(m1, 1));
            g0 = fmaxf(g0, shx(g0, 2)); g1 = fmaxf(g1, shx(g1, 2));
            l0 *= ex2((m0 - g0) * L2E); l1 *= ex2((m1 - g1) * L2E);
            l0 += shx(l0, 1); l1 += shx(l1, 1);
            l0 += shx(l0, 2); l1 += shx(l1, 2);
            if (lane == 0)
                sts128(sb + OFF_WMX + 96, __float_as_uint(g0), __float_as_uint(g1), __float_as_uint(__frcp_rn(l0)), __float_as_uint(__frcp_rn(l1)));
        }
        bar_consumers();
        if (vw < 8) {
            const uint4 gs = lds128(sb + OFF_WMX + 96);
            const float g0 = __uint_as_float(gs.x), g1 = __uint_as_float(gs.y), i0 = __uint_as_float(gs.z), i1 = __uint_as_float(gs.w);
            const uint32_t a0 = pack2(ex2((bflo(sv.x) - g0) * L2E) * i0, ex2((bflo(sv.y) - g0) * L2E) * i0);
            const uint32_t a1 = pack2(ex2((bflo(sv.z) - g0) * L2E) * i0, ex2((bflo(sv.w) - g0) * L2E) * i0);
            const uint32_t b0 = pack2(ex2((bfhi(sv.x) - g1) * L2E) * i1, ex2((bfhi(sv.y) - g1) * L2E) * i1);
            const uint32_t b1 = pack2(ex2((bfhi(sv.z) - g1) * L2E) * i1, ex2((bfhi(sv.w) - g1) * L2E) * i1);
            sts64(sb + OFF_P + tid * 8, a0, a1); sts64(sb + OFF_P + PSTR + tid * 8, b0, b1);
        }
        bar_consumers();
        TS(tid == 0, 8);
    }
    const uint32_t rsw = ((mi & 1) ^ r) << 4;
    unsigned sidew = 2u;
    if (vw < 8) {
        float c0[4] = {}, c1[4] = {};
        const uint32_t vo = (vw >> 2) * 8192 + (r + 8 * (mi >> 1)) * 128 + ((((2 * vw + (mi & 1)) & 7) ^ r) << 4);
        const uint32_t pa = sb + OFF_P + bat * PSTR + t * 32;
#pragma unroll 1
        for (int i = 0; i < 16; i++) {
            uint4 pb0 = lds128(pa + i * 128), pb1 = lds128(pa + i * 128 + 16);
            mbar_wait(s_full + it_v(i) * 8);
            const uint32_t base = sb + v_off(i) + vo;
            uint32_t a0[4], a1[4], a2[4], a3[4];
            ldsm4t(a0, base); ldsm4t(a1, base + 2048); ldsm4t(a2, base + 4096); ldsm4t(a3, base + 6144);
            mma16816(c0, a0, pb0.x, pb0.y);
            mma16816(c1, a1, pb0.z, pb0.w);
            mma16816(c0, a2, pb1.x, pb1.y);
            mma16816(c1, a3, pb1.z, pb1.w);
            __syncwarp();
            if (lane == 0) mbar_arrive(s_empty + (EM_V + i) * 8);
            if (i == SIDE_V) { mbar_wait(s_empty + EM_PH * 8); sidew = ldg_rlx1(pside); }
        }
        if (t < 2)
            stg_pkt(scr + G_OP + kvh * 4096 + (j >> 2) * 2048 + t * HALF + (j & 3) * 256 + vw * 32 + g * 4,
                    c0[0] + c1[0], c0[1] + c1[1], c0[2] + c1[2], c0[3] + c1[3], tag);
        TS(tid == 0, 9);
    } else {
        mbar_wait(s_full + it_v(SIDE_V) * 8);
        mbar_wait(s_empty + EM_PH * 8);
    }
    {
        int it = 0;
        while (any_lane((sidew ^ tag) & 7u) && ++it < SPIN_LIMIT) sidew = ldg_rlx1(pside);
        ppart += near_half(G_PART + (vw * 16 + t * 4 + (g >> 1)) * 2048, sidew >> 4);
    }
    side = __float_as_uint(ldsf(sb + OFF_WMX + 112));
#pragma unroll 1
    for (int ph = 0; ph < 2; ph++) {
    if (ph) {
    uint32_t ag[4][6][4];
    const uint32_t gub = s_full + (IT_GU + 2 * (vw / 3)) * 8;
    const uint32_t gpitch = wide ? 96 : 64, gsw = wide ? 0 : (r >> 1) << 4;
    const uint32_t gbase = sb + ((mi & 1) ? OFF_U : OFF_G) + (vw * 64 + r + 8 * (mi >> 1)) * gpitch;
    auto load_gu = [&]() {
#pragma unroll
        for (int ks = 0; ks < 4; ks++)
#pragma unroll
            for (int q = 0; q < 4; q++) ldsm4t(ag[ks][q], gbase + ks * 16 * gpitch + ((q << 4) ^ gsw));
        if (wide) {
#pragma unroll
            for (int ks = 0; ks < 4; ks++)
#pragma unroll
                for (int q = 4; q < 6; q++) ldsm4t(ag[ks][q], gbase + ks * 1536 + q * 16);
        }
    };
    bool gpre;
    while (true) {
        gpre = __all_sync(0xffffffffu, mbar_test(gub) && mbar_test(gub + 8));
        if (gpre || __all_sync(0xffffffffu, mbar_test(s_empty + EM_X1 * 8))) break;
    }
    if (gpre) {
        load_gu();
        mbar_wait(s_empty + EM_X1 * 8);
    }
    {
        uint4 v;
        int it = 0;
        const int xw = G_X1 + (vw >> 3) * 2048 + (c & (XREP - 1)) * 4096;
        const unsigned* px = scr + xw + near_half(xw, side) + (vecw & 1023);
        do { v = ldg_rlx4(px); } while (any_lane(bad4(v, tag) & 7u) && ++it < SPIN_LIMIT);
        xw0 = hi2(v.x, v.y); xw1 = hi2(v.z, v.w);
        ln_stage1(xw0, xw1, st2, vw, lane);
        bar_consumers();
        if (tid == 0) mbar_arrive(s_empty + EM_CH * 8);
        TS(tid == 0, 13);
        uint32_t y0, y1;
        ln_stage2(ln_load(st2), xw0, xw1, y0, y1);
        aw0 = badd2(bmul2(y0, sc0), sh0); aw1 = badd2(bmul2(y1, sc1), sh1);
        uint32_t bf[4][2];
        make_bfrags(bf, aw0, aw1, r);
        if (!gpre) { mbar_wait(gub); mbar_wait(gub + 8); load_gu(); }
        float cc[6][4] = {};
#pragma unroll
        for (int ks = 0; ks < 4; ks++)
#pragma unroll
            for (int q = 0; q < 4; q++) mma16816(cc[q], ag[ks][q], bf[ks][0], bf[ks][1]);
        if (wide) {
#pragma unroll
            for (int ks = 0; ks < 4; ks++)
#pragma unroll
                for (int q = 4; q < 6; q++) mma16816(cc[q], ag[ks][q], bf[ks][0], bf[ks][1]);
        }
        if (t == 0) {
#pragma unroll
            for (int q = 0; q < 6; q++) sts128f(sb + OFF_RED + vw * 768 + q * 128 + g * 16, cc[q]);
        }
        bar_consumers();
        TS(tid == 0, 14);
        if (tid < 192) {
            float sv[NCW];
#pragma unroll
            for (int w = 0; w < NCW; w++) sv[w] = ldsf(sb + OFF_RED + w * 768 + tid * 4);
            const float s = ((sv[0] + sv[1]) + (sv[2] + sv[3])) + ((sv[4] + sv[5]) + (sv[6] + sv[7])) + sv[8];
            const uint32_t gu = pack2(s, __shfl_down_sync(0xffffffffu, s, 2));
            const float gt = bflo(gu);
            const uint32_t hh = pack2(((gt > 0.f) ? gt : gt * 0.0f) * bfhi(gu), 0.f);
            const int rr = tid >> 2;
            if ((tid & 2) == 0)
                sts16(sb + OFF_FR + ((tid & 1) * 4 + ((rr & 7) >> 1)) * 48 + (rr >> 3) * 4 + (rr & 1) * 2, hh);
        }
    }
    bar_consumers();
    }
    {
        const int di = (vw / 3 + 1) % 3;
        const uint32_t rrow = (r + 8 * (mi >> 1)) * 128;
        const uint32_t b0 = sb + rrow + (ph ? OFF_D + di * DSTR + (vw % 3) * (wide ? 6144 : 4096) : OFF_WO0 + vw * 2048);
        const uint32_t b1 = ph ? b0 + 2048 : sb + rrow + OFF_WO1 + vw * 2048;
        const uint32_t fb0 = s_full + (ph ? IT_WD + di : IT_WO) * 8;
        const bool k3 = ph && wide;
        uint32_t ad[3][4][4];
        mbar_wait(fb0);
#pragma unroll
        for (int mt = 0; mt < 4; mt++) ldsm4t(ad[0][mt], b0 + (rsw ^ (mt * 32)));
        if (!ph) mbar_wait(fb0 + 8);
#pragma unroll
        for (int mt = 0; mt < 4; mt++) ldsm4t(ad[1][mt], b1 + (rsw ^ (mt * 32)));
        if (k3) {
#pragma unroll
            for (int mt = 0; mt < 4; mt++) ldsm4t(ad[2][mt], b0 + 4096 + (rsw ^ (mt * 32)));
        }
        if (!ph) asm volatile("bar.sync 3, 352;" ::: "memory");
        const uint4 fr = lds128(sb + OFF_FR + r * 48);
        const uint2 f2 = lds64(sb + OFF_FR + r * 48 + 16);
        float cc[4][4] = {};
#pragma unroll
        for (int mt = 0; mt < 4; mt++) mma16816(cc[mt], ad[0][mt], fr.x, fr.y);
#pragma unroll
        for (int mt = 0; mt < 4; mt++) mma16816(cc[mt], ad[1][mt], fr.z, fr.w);
        if (k3) {
#pragma unroll
            for (int mt = 0; mt < 4; mt++) mma16816(cc[mt], ad[2][mt], f2.x, f2.y);
        }
        publish_partials(ppart, t, cc, tag | (ph * 4u));
        TS(tid == (ph ? 160 : 0), 11 + 4 * ph);
    }
    }
    if (vw / 3 == c / 48) asm volatile("bar.arrive 5, 128;" ::: "memory");
    if (vw >= 6 && c < 16) asm volatile("bar.arrive 7, 128;" ::: "memory");
}

typedef CUresult (*EncodeFn)(CUtensorMap*, CUtensorMapDataType, cuuint32_t, void*, const cuuint64_t*, const cuuint64_t*,
                             const cuuint32_t*, const cuuint32_t*, CUtensorMapInterleave, CUtensorMapSwizzle,
                             CUtensorMapL2promotion, CUtensorMapFloatOOBfill);

void make_map(EncodeFn enc, CUtensorMap* m, const void* p, cuuint64_t d0, cuuint64_t d1, cuuint64_t d2,
              cuuint64_t s1, cuuint64_t s2, cuuint32_t b0, cuuint32_t b1, cuuint32_t b2, CUtensorMapSwizzle sw,
              CUtensorMapL2promotion pr = CU_TENSOR_MAP_L2_PROMOTION_L2_128B) {
    cuuint64_t dims[3] = {d0, d1, d2};
    cuuint64_t str[2] = {s1, s2};
    cuuint32_t box[3] = {b0, b1, b2};
    cuuint32_t es[3] = {1, 1, 1};
    enc(m, CU_TENSOR_MAP_DATA_TYPE_BFLOAT16, 3, const_cast<void*>(p), dims, str, box, es,
        CU_TENSOR_MAP_INTERLEAVE_NONE, sw, pr, CU_TENSOR_MAP_FLOAT_OOB_FILL_NONE);
}

}

extern "C" void kernel_launch(void* const* d_in, const int* in_sizes, int n_in, void* d_out, int out_size) {
    (void)in_sizes; (void)n_in; (void)out_size;
    void* fn = nullptr;
    cudaDriverEntryPointQueryResult qr;
    cudaGetDriverEntryPoint("cuTensorMapEncodeTiled", &fn, cudaEnableDefault, &qr);
    EncodeFn enc = (EncodeFn)fn;
    cudaFuncSetAttribute(fused_block_kernel, cudaFuncAttributeMaxDynamicSharedMemorySize, SMEM_BYTES);

    const void *x = d_in[0], *kc = d_in[1], *vc = d_in[2], *wq = d_in[3], *wo = d_in[4];
    const void *wg = d_in[6], *wu = d_in[7], *wd = d_in[8], *cc = d_in[9], *wmod = d_in[10];
    const CUtensorMapSwizzle S128 = CU_TENSOR_MAP_SWIZZLE_128B, S64 = CU_TENSOR_MAP_SWIZZLE_64B, S0 = CU_TENSOR_MAP_SWIZZLE_NONE;
    void* raw = nullptr;
    cudaGetSymbolAddress(&raw, g_raw);
    unsigned* scr = (unsigned*)(((uintptr_t)raw + 0x1fffff) & ~(uintptr_t)0x1fffff);
    Maps m;
    make_map(enc, &m.m[M_K], kc, 64, 32ull * 32768, 2, 256, 128, 64, 64, 2, S128, CU_TENSOR_MAP_L2_PROMOTION_L2_256B);
    make_map(enc, &m.m[M_V], vc, 64, 32ull * 32768, 2, 256, 128, 64, 64, 2, S128, CU_TENSOR_MAP_L2_PROMOTION_L2_256B);
    make_map(enc, &m.m[M_WMOD], wmod, 3456, 144, 4, 3456 * 2, 3456 * 2 * 144, 32, 144, 2, S64);
    make_map(enc, &m.m[M_WQ], wq, 4096, 144, 4, 4096 * 2, 4096 * 2 * 144, 32, 144, 2, S64);
    make_map(enc, &m.m[M_WG], wg, 4608, 576, 1, 4608 * 2, 4608 * 2 * 576, 32, 192, 1, S64);
    make_map(enc, &m.m[M_WU], wu, 4608, 576, 1, 4608 * 2, 4608 * 2 * 576, 32, 192, 1, S64);
    make_map(enc, &m.m[M_WG48], wg, 4608, 576, 1, 4608 * 2, 4608 * 2 * 576, 48, 192, 1, S0);
    make_map(enc, &m.m[M_WU48], wu, 4608, 576, 1, 4608 * 2, 4608 * 2 * 576, 48, 192, 1, S0);
    make_map(enc, &m.m[M_WO], wo, 64, 4096, 9, 1152, 128, 64, 16, 9, S128);
    make_map(enc, &m.m[M_WD], wd, 64, 4608, 9, 1152, 128, 64, 32, 3, S128);
    make_map(enc, &m.m[M_WD48], wd, 64, 4608, 9, 1152, 128, 64, 48, 3, S128);
    fused_block_kernel<<<NCTA, NTHR, SMEM_BYTES>>>(m, (const __nv_bfloat16*)x, (const __nv_bfloat16*)cc,
                                                   (const __nv_bfloat16*)kc, (__nv_bfloat16*)d_out, scr TUNE_ARG);
}
```

```cpp
#include <cuda_runtime.h>
#include <cuda.h>
#include <cuda_bf16.h>
#include <stdint.h>

namespace {

constexpr int DM = 576;
constexpr int NCTA = 128;
constexpr int NCW = 9;
constexpr int NTHR = (NCW + 3) * 32;
constexpr int NMOD = 108;

#define WIN_MAIN 4
#define WIN_TAIL 3
#define WIN_SWITCH 38
#define PACE_GBS 3100
#define PACE_LEAD 28672
#define PACE_TAIL 3100
#define TAIL_GAP 0
#define PACE_D 3100
#define OPEN_WIN 1
#define DELAY_B 300
#define DELAY_D 150
#define CTL_GAIN 0
#define CTL_MAIN 57344
#define CTL_TAIL 40960
#define CTL_SWITCH 30
#define CTL_SUB 1
#define KVPAT 1
#define KVROT 1
#define WIN_G0 4
#define WIN_GN 0
#define EARLY_PF 8192
#define TM_PF 1
#define XREP 2
#define PH_V 7
#define SIDE_V 11
#define NPROBE 10
#define NPROBE0 3
#define PH_K 8

#define TUNE_PARAM
#define TUNE_ARG

constexpr int IT_WMOD = 0, IT_WQ = 2, IT_K = 4, IT_V = 20, IT_WO = 36, IT_WD = 38, IT_GU = 41, N_IT = 49;
constexpr int IT_TAIL = IT_WD;
__device__ __forceinline__ constexpr int it_v(int k) { return IT_V + k; }
constexpr int EM_WMOD = 0, EM_WQ = 1, EM_K = 2, EM_V = 18, EM_PH = 34, EM_X1 = 35, EM_CH = 36, EM_SD = 37, N_EM = 38;

constexpr int RING = 13 * 16384;
constexpr int OFF_WMOD = 0, OFF_WQ = 36864, OFF_K0 = 73728;
constexpr int OFF_WO0 = 194560, OFF_WO1 = 0, OFF_GU = 73728, GSTR = 13824;
constexpr int OFF_D = 18432, DSTR = 18432;
constexpr int PSTR = 2064;
constexpr int OFF_P = RING;
constexpr int OFF_S = OFF_P + 4160;
constexpr int OFF_RED = OFF_S + 4096;
constexpr int OFF_QS = OFF_RED + 6912;
constexpr int OFF_FR = OFF_QS + 640;
constexpr int OFF_STAT = OFF_FR + 384;
constexpr int OFF_WMX = OFF_STAT + 320;
constexpr int OFF_BAR = OFF_WMX + 128;
constexpr int SMEM_USED = OFF_BAR + (N_IT + N_EM) * 8;
constexpr int SMEM_BYTES = SMEM_USED + 1024;
static_assert(SMEM_BYTES <= 232448, "smem");

struct Maps { CUtensorMap m[11]; };
enum { M_K, M_V, M_WMOD, M_WQ, M_WO, M_WG, M_WU, M_WD, M_WG48, M_WU48, M_WD48 };

constexpr int HALF = 1024;
constexpr int G_PART = 0;
constexpr int G_OP = G_PART + 144 * 2048;
constexpr int G_X1 = G_OP + 16 * 4096;
constexpr int G_PROBE = G_X1 + XREP * 4096;
constexpr int G_SIDE = G_PROBE + 2048;
constexpr int G_EPOCH = G_SIDE + 1024;
constexpr int G_MOD = G_EPOCH + 1024;
constexpr int G_Q = G_MOD + 7 * 2048;
constexpr int G_ML = G_Q + 8 * 2048;
constexpr int G_WORDS = G_ML + 2048;
static_assert(G_MOD % 2048 == 0 && G_OP % 2048 == 0 && G_X1 % 2048 == 0 && G_PROBE % 2048 == 0, "halves");
static_assert(G_WORDS * 4 <= (2 << 20), "scratch must fit one 2 MB page");
__device__ __align__(128) unsigned g_raw[(2 << 20) / 4 + G_WORDS + 8192];
__device__ __forceinline__ int near_half(int w, unsigned side) { return ((__popc(w & 0x2C800) ^ side) & 1) << 10; }
__device__ __forceinline__ int dual(int base, int i) { return base + i + (i & ~1023); }
__device__ __forceinline__ int dual_near(int base, int i, unsigned side) { const int w = dual(base, i); return w + near_half(w, side); }
#define g_ts ((unsigned long long*)(scr + G_WORDS))

constexpr int SPIN_LIMIT = 1 << 20;

__device__ __forceinline__ uint32_t smem_u32(const void* p) { return (uint32_t)__cvta_generic_to_shared(p); }
__device__ __forceinline__ void mbar_init(uint32_t bar, int cnt) {
    asm volatile("mbarrier.init.shared::cta.b64 [%0], %1;" ::"r"(bar), "r"(cnt) : "memory");
}
__device__ __forceinline__ void mbar_expect_tx(uint32_t bar, uint32_t bytes) {
    asm volatile("mbarrier.arrive.expect_tx.shared::cta.b64 _, [%0], %1;" ::"r"(bar), "r"(bytes) : "memory");
}
__device__ __forceinline__ void mbar_arrive(uint32_t bar) {
    asm volatile("mbarrier.arrive.shared::cta.b64 _, [%0];" ::"r"(bar) : "memory");
}
__device__ __forceinline__ void mbar_wait(uint32_t bar) {
    asm volatile("{\n.reg .pred p;\nW_%=:\nmbarrier.try_wait.parity.shared::cta.b64 p, [%0], 0;\n@!p bra W_%=;\n}"
                 ::"r"(bar) : "memory");
}
__device__ __forceinline__ bool mbar_test(uint32_t bar) {
    uint32_t ok;
    asm volatile("{\n.reg .pred p;\nmbarrier.test_wait.parity.shared::cta.b64 p, [%1], 0;\nselp.u32 %0, 1, 0, p;\n}"
                 : "=r"(ok) : "r"(bar) : "memory");
    return ok;
}
__device__ __forceinline__ uint32_t gtime32() { uint32_t t; asm volatile("mov.u32 %0, %%globaltimer_lo;" : "=r"(t)); return t; }
__device__ __forceinline__ void tma3d(uint32_t dst, const CUtensorMap* m, int x, int y, int z, uint32_t bar) {
    asm volatile("cp.async.bulk.tensor.3d.shared::cluster.global.mbarrier::complete_tx::bytes [%0], [%1, {%3, %4, %5}], [%2];"
                 ::"r"(dst), "l"(m), "r"(bar), "r"(x), "r"(y), "r"(z) : "memory");
}
__device__ __forceinline__ void bar_consumers() { asm volatile("bar.sync 1, 288;" ::: "memory"); }

__device__ __forceinline__ void ldsm4(uint32_t (&a)[4], uint32_t addr) {
    asm volatile("ldmatrix.sync.aligned.m8n8.x4.shared.b16 {%0,%1,%2,%3}, [%4];"
                 : "=r"(a[0]), "=r"(a[1]), "=r"(a[2]), "=r"(a[3]) : "r"(addr) : "memory");
}
__device__ __forceinline__ void ldsm4t(uint32_t (&a)[4], uint32_t addr) {
    asm volatile("ldmatrix.sync.aligned.m8n8.x4.trans.shared.b16 {%0,%1,%2,%3}, [%4];"
                 : "=r"(a[0]), "=r"(a[1]), "=r"(a[2]), "=r"(a[3]) : "r"(addr) : "memory");
}
__device__ __forceinline__ void mma16816(float (&c)[4], const uint32_t (&a)[4], uint32_t b0, uint32_t b1) {
    asm volatile("mma.sync.aligned.m16n8k16.row.col.f32.bf16.bf16.f32 {%0,%1,%2,%3}, {%4,%5,%6,%7}, {%8,%9}, {%0,%1,%2,%3};"
                 : "+f"(c[0]), "+f"(c[1]), "+f"(c[2]), "+f"(c[3])
                 : "r"(a[0]), "r"(a[1]), "r"(a[2]), "r"(a[3]), "r"(b0), "r"(b1));
}
__device__ __forceinline__ float ldsf(uint32_t a) { float v; asm volatile("ld.shared.f32 %0, [%1];" : "=f"(v) : "r"(a) : "memory"); return v; }
__device__ __forceinline__ uint2 lds64(uint32_t a) {
    uint2 v; asm volatile("ld.shared.v2.u32 {%0,%1}, [%2];" : "=r"(v.x), "=r"(v.y) : "r"(a) : "memory"); return v;
}
__device__ __forceinline__ uint4 lds128(uint32_t a) {
    uint4 v; asm volatile("ld.shared.v4.u32 {%0,%1,%2,%3}, [%4];" : "=r"(v.x), "=r"(v.y), "=r"(v.z), "=r"(v.w) : "r"(a) : "memory"); return v;
}
__device__ __forceinline__ void sts16(uint32_t a, uint32_t v) { asm volatile("st.shared.u16 [%0], %1;" ::"r"(a), "h"((unsigned short)v) : "memory"); }
__device__ __forceinline__ void sts32(uint32_t a, uint32_t v) { asm volatile("st.shared.u32 [%0], %1;" ::"r"(a), "r"(v) : "memory"); }
__device__ __forceinline__ void sts64(uint32_t a, uint32_t x, uint32_t y) { asm volatile("st.shared.v2.u32 [%0], {%1,%2};" ::"r"(a), "r"(x), "r"(y) : "memory"); }
__device__ __forceinline__ void sts128(uint32_t a, uint32_t x, uint32_t y, uint32_t z, uint32_t w) {
    asm volatile("st.shared.v4.u32 [%0], {%1,%2,%3,%4};" ::"r"(a), "r"(x), "r"(y), "r"(z), "r"(w) : "memory");
}
__device__ __forceinline__ void sts128f(uint32_t a, const float (&c)[4]) {
    asm volatile("st.shared.v4.f32 [%0], {%1,%2,%3,%4};" ::"r"(a), "f"(c[0]), "f"(c[1]), "f"(c[2]), "f"(c[3]) : "memory");
}
__device__ __forceinline__ unsigned ldg_rlx1(const unsigned* p) {
    unsigned v; asm volatile("ld.relaxed.gpu.global.u32 %0, [%1];" : "=r"(v) : "l"(p) : "memory"); return v;
}
__device__ __forceinline__ uint4 ldg_rlx4(const unsigned* p) {
    uint4 v; asm volatile("ld.relaxed.gpu.global.v4.u32 {%0,%1,%2,%3}, [%4];" : "=r"(v.x), "=r"(v.y), "=r"(v.z), "=r"(v.w) : "l"(p) : "memory"); return v;
}
__device__ __forceinline__ uint4 ldg_pkt(const unsigned* p) {
    uint4 v;
    asm volatile("{\n.reg .b128 t;\n.reg .b64 lo, hi;\nld.relaxed.gpu.global.b128 t, [%4];\nmov.b128 {lo, hi}, t;\n"
                 "mov.b64 {%0,%1}, lo;\nmov.b64 {%2,%3}, hi;\n}"
                 : "=r"(v.x), "=r"(v.y), "=r"(v.z), "=r"(v.w) : "l"(p) : "memory");
    return v;
}
__device__ __forceinline__ void ldg_pkt_if(uint4& v, const unsigned* a, unsigned p) {
    asm volatile("{\n.reg .pred q;\n.reg .b128 t;\n.reg .b64 lo, hi;\nsetp.ne.u32 q, %5, 0;\n"
                 "mov.b64 lo, {%0,%1};\nmov.b64 hi, {%2,%3};\nmov.b128 t, {lo, hi};\n"
                 "@q ld.relaxed.gpu.global.b128 t, [%4];\nmov.b128 {lo, hi}, t;\n"
                 "mov.b64 {%0,%1}, lo;\nmov.b64 {%2,%3}, hi;\n}"
                 : "+r"(v.x), "+r"(v.y), "+r"(v.z), "+r"(v.w) : "l"(a), "r"(p) : "memory");
}
__device__ __forceinline__ bool any_lane(unsigned x) { return __any_sync(0xffffffffu, x != 0); }
__device__ __forceinline__ void stg_pkt(unsigned* p, float a, float b, float c, float d, unsigned tag) {
    unsigned x = (__float_as_uint(a) & ~7u) | tag;
    asm volatile("{\n.reg .b128 t;\n.reg .b64 lo, hi;\nmov.b64 lo, {%1,%2};\nmov.b64 hi, {%3,%4};\nmov.b128 t, {lo, hi};\n"
                 "st.relaxed.gpu.global.b128 [%0], t;\n}"
                 ::"l"(p), "r"(x), "r"(__float_as_uint(b)), "r"(__float_as_uint(c)), "r"(__float_as_uint(d)) : "memory");
}
__device__ __forceinline__ void stg_rlx1(unsigned* p, unsigned x) { asm volatile("st.relaxed.gpu.global.u32 [%0], %1;" ::"l"(p), "r"(x) : "memory"); }
__device__ __forceinline__ unsigned bad4(const uint4& v, unsigned tag) {
    return ((v.x ^ tag) | (v.y ^ tag)) | ((v.z ^ tag) | (v.w ^ tag));
}
__device__ __forceinline__ float untagf(unsigned w) { return __uint_as_float(w & ~7u); }
__device__ __forceinline__ uint32_t pack2(float lo, float hi) {
    uint32_t r; asm("cvt.rn.bf16x2.f32 %0, %1, %2;" : "=r"(r) : "f"(hi), "f"(lo)); return r;
}
__device__ __forceinline__ float bflo(uint32_t w) { return __uint_as_float(w << 16); }
__device__ __forceinline__ float bfhi(uint32_t w) { return __uint_as_float(w & 0xffff0000u); }
__device__ __forceinline__ uint32_t hi2(uint32_t a, uint32_t b) { return __byte_perm(a, b, 0x7632); }
__device__ __forceinline__ uint32_t badd2(uint32_t a, uint32_t b) { uint32_t r; asm("add.rn.bf16x2 %0, %1, %2;" : "=r"(r) : "r"(a), "r"(b)); return r; }
__device__ __forceinline__ uint32_t bsub2(uint32_t a, uint32_t b) { uint32_t r; asm("sub.rn.bf16x2 %0, %1, %2;" : "=r"(r) : "r"(a), "r"(b)); return r; }
__device__ __forceinline__ uint32_t bmul2(uint32_t a, uint32_t b) { uint32_t r; asm("mul.rn.bf16x2 %0, %1, %2;" : "=r"(r) : "r"(a), "r"(b)); return r; }
__device__ __forceinline__ uint32_t bmax2(uint32_t a, uint32_t b) { uint32_t r; asm("max.bf16x2 %0, %1, %2;" : "=r"(r) : "r"(a), "r"(b)); return r; }
__device__ __forceinline__ float ex2(float x) { float r; asm("ex2.approx.ftz.f32 %0, %1;" : "=f"(r) : "f"(x)); return r; }
__device__ __forceinline__ float rcp(float x) { float r; asm("rcp.approx.ftz.f32 %0, %1;" : "=f"(r) : "f"(x)); return r; }
__device__ __forceinline__ float fsqrt(float x) { float r; asm("sqrt.approx.ftz.f32 %0, %1;" : "=f"(r) : "f"(x)); return r; }
__device__ __forceinline__ float shx(float v, int m) { return __shfl_xor_sync(0xffffffffu, v, m); }
#define TS(cond, slot) do { } while (0)

__device__ __forceinline__ uint32_t k_off(int i) { return i < 8 ? OFF_K0 + i * 16384 : (i - 8) * 16384; }
__device__ __forceinline__ uint32_t v_off(int i) { return i < 5 ? (8 + i) * 16384 : (i - 5) * 16384; }

__device__ __forceinline__ void stg_ph(unsigned* p) { stg_pkt(p, 0.f, 0.f, 0.f, 0.f, 2u); }

__device__ __forceinline__ void ln_stage1(uint32_t xw0, uint32_t xw1, uint32_t st, int vw, int lane) {
    const float piv = __shfl_sync(0xffffffffu, bflo(xw0), lane & 4);
    const float d0 = bflo(xw0) - piv, d1 = bfhi(xw0) - piv, d2 = bflo(xw1) - piv, d3 = bfhi(xw1) - piv;
    float s1 = (d0 + d1) + (d2 + d3), s2 = (d0 * d0 + d1 * d1) + (d2 * d2 + d3 * d3);
    s1 += shx(s1, 1); s2 += shx(s2, 1);
    s1 += shx(s1, 2); s2 += shx(s2, 2);
    s1 += shx(s1, 8); s2 += shx(s2, 8);
    s1 += shx(s1, 16); s2 += shx(s2, 16);
    if ((lane & 27) == 0)
        sts64(st + vw * 8, __float_as_uint(piv + s1 * (1.0f / 64.0f)), __float_as_uint(s2 - s1 * s1 * (1.0f / 64.0f)));
}
struct LnStat { uint4 a, b, c, d; uint2 e; };
__device__ __forceinline__ LnStat ln_load(uint32_t st) {
    LnStat s; s.a = lds128(st); s.b = lds128(st + 16); s.c = lds128(st + 32); s.d = lds128(st + 48); s.e = lds64(st + 64);
    return s;
}
__device__ __forceinline__ void ln_stage2(const LnStat& s, uint32_t xw0, uint32_t xw1, uint32_t& y0, uint32_t& y1) {
    const float m[9] = {__uint_as_float(s.a.x), __uint_as_float(s.a.z), __uint_as_float(s.b.x), __uint_as_float(s.b.z),
                        __uint_as_float(s.c.x), __uint_as_float(s.c.z), __uint_as_float(s.d.x), __uint_as_float(s.d.z), __uint_as_float(s.e.x)};
    const float mean = (((m[0] + m[1]) + (m[2] + m[3])) + ((m[4] + m[5]) + (m[6] + m[7])) + m[8]) * (1.0f / NCW);
    const float m2 = ((__uint_as_float(s.a.y) + __uint_as_float(s.a.w)) + (__uint_as_float(s.b.y) + __uint_as_float(s.b.w))) +
                     ((__uint_as_float(s.c.y) + __uint_as_float(s.c.w)) + (__uint_as_float(s.d.y) + __uint_as_float(s.d.w))) + __uint_as_float(s.e.y);
    float d[9];
#pragma unroll
    for (int w = 0; w < 9; w++) d[w] = m[w] - mean;
    const float acc = (d[0] * d[0] + d[1] * d[1] + d[2] * d[2]) + (d[3] * d[3] + d[4] * d[4] + d[5] * d[5]) + (d[6] * d[6] + d[7] * d[7] + d[8] * d[8]);
    const float var = (m2 + 64.0f * acc) * (1.0f / DM);
    const uint32_t mv = pack2(mean, var);
    const float ve = bflo(pack2(bfhi(mv) + 1e-5f, 0.f));
    const float rinv = rcp(bflo(pack2(fsqrt(ve), 0.f)));
    const uint32_t mm = __byte_perm(mv, mv, 0x1010);
    const uint32_t e0 = bsub2(xw0, mm), e1 = bsub2(xw1, mm);
    y0 = pack2(bflo(e0) * rinv, bfhi(e0) * rinv); y1 = pack2(bflo(e1) * rinv, bfhi(e1) * rinv);
}
__device__ __forceinline__ void make_bfrags(uint32_t (&bf)[4][2], uint32_t aw0, uint32_t aw1, int r) {
#pragma unroll
    for (int ks = 0; ks < 4; ks++) {
        bf[ks][0] = __shfl_sync(0xffffffffu, aw0, ks * 8 + r);
        bf[ks][1] = __shfl_sync(0xffffffffu, aw1, ks * 8 + r);
    }
}
__device__ __forceinline__ uint32_t gemv32(uint32_t s_w, uint32_t red, uint32_t fullbar, uint32_t emptybar,
                                           uint32_t aw0, uint32_t aw1, int tid) {
    const int vw = tid >> 5, lane = tid & 31, g = lane >> 2, t = lane & 3, mi = lane >> 3, r = lane & 7;
    uint32_t bf[4][2];
    make_bfrags(bf, aw0, aw1, r);
    if (vw <= 4) mbar_wait(fullbar);
    if (vw >= 4) mbar_wait(fullbar + 8);
    float cc[2][4] = {};
    const uint32_t abase = s_w + (vw * 64 + r + 8 * (mi >> 1)) * 64;
    const uint32_t sw = ((mi & 1) ^ (r >> 1)) << 4;
#pragma unroll
    for (int ks = 0; ks < 4; ks++) {
#pragma unroll
        for (int mt = 0; mt < 2; mt++) {
            uint32_t a[4];
            ldsm4t(a, abase + ks * 1024 + (sw ^ (mt * 32)));
            mma16816(cc[mt], a, bf[ks][0], bf[ks][1]);
        }
    }
    if (t == 0) { sts128f(red + vw * 256 + g * 16, cc[0]); sts128f(red + vw * 256 + 128 + g * 16, cc[1]); }
    __syncwarp();
    if (lane == 0) mbar_arrive(emptybar);
    bar_consumers();
    float s = 0.f;
    if (tid < 64) {
        const uint32_t ra = red + ((tid & 58) | ((tid & 1) << 2) | ((tid >> 2) & 1)) * 4;
#pragma unroll
        for (int w = 0; w < NCW; w++) s += ldsf(ra + w * 256);
    }
    return pack2(0.f, s);
}
__device__ __forceinline__ void publish_partials(unsigned* q, int t, const float (&cc)[4][4], unsigned tag) {
    float v[4];
#pragma unroll
    for (int i = 0; i < 4; i++) {
        const float lo = (t & 1) ? cc[1][i] : cc[0][i], hi = (t & 1) ? cc[3][i] : cc[2][i];
        v[i] = (t & 2) ? hi : lo;
    }
    stg_pkt(q, v[0], v[1], v[2], v[3], tag);
}
__device__ __forceinline__ void spin_cycles(unsigned n) {
    const unsigned c0 = clock();
    while ((unsigned)clock() - c0 < n) { }
}
__device__ __forceinline__ float reduce_unit(const unsigned* q, int lane, unsigned tag, unsigned (&dur)[4]) {
    uint4 v[8];
#pragma unroll
    for (int i = 0; i < 8; i++) v[i] = ldg_pkt(q + i * 128);
    int it = 0;
    while (true) {
        unsigned bad = 0;
#pragma unroll
        for (int i = 0; i < 8; i += 2) bad |= (v[i].x ^ tag) | (v[i + 1].x ^ tag);
        const bool more = any_lane(bad & 7u);
        if (!more || ++it >= SPIN_LIMIT) break;
#pragma unroll
        for (int i = 0; i < 8; i++) ldg_pkt_if(v[i], q + i * 128, (v[i].x ^ tag) & 7u);
    }
    float s0 = 0.f, s1 = 0.f, s2 = 0.f, s3 = 0.f, u0 = 0.f, u1 = 0.f, u2 = 0.f, u3 = 0.f;
#pragma unroll
    for (int i = 0; i < 8; i += 2) {
        s0 += untagf(v[i].x); s1 += __uint_as_float(v[i].y); s2 += __uint_as_float(v[i].z); s3 += __uint_as_float(v[i].w);
        u0 += untagf(v[i + 1].x); u1 += __uint_as_float(v[i + 1].y); u2 += __uint_as_float(v[i + 1].z); u3 += __uint_as_float(v[i + 1].w);
    }
    s0 += u0; s1 += u1; s2 += u2; s3 += u3;
    __syncwarp();
    const bool h8 = lane & 2, bat = lane & 4;
    const float k0 = (h8 ? s2 : s0) + shx(h8 ? s0 : s2, 2);
    const float k1 = (h8 ? s3 : s1) + shx(h8 ? s1 : s3, 2);
    float k = (bat ? k1 : k0) + shx(bat ? k0 : k1, 4);
    k += shx(k, 8);
    k += shx(k, 16);
    return k;
}

__global__ void __launch_bounds__(NTHR, 1)
fused_block_kernel(const __grid_constant__ Maps maps, const __nv_bfloat16* __restrict__ xin,
                   const __nv_bfloat16* __restrict__ cin, const __nv_bfloat16* __restrict__ kcache,
                   __nv_bfloat16* __restrict__ out, unsigned* const scr TUNE_PARAM) {
    extern __shared__ unsigned char smem_raw[];
    const int c = blockIdx.x;
    const int kvh = c >> 3, j = c & 7, bb = j & 1, sp = j >> 1;
    const bool wide = j >= 6;
    const int f0 = kvh * 288 + (wide ? 48 * j - 96 : 32 * j);
    const int kvrow0 = (bb * 16 + kvh) * 32768 + 28672 + sp * (KVPAT ? 64 : 1024);
    const int kvstep = KVPAT ? 256 : 64;
    if (EARLY_PF && threadIdx.x == 0)
        asm volatile("cp.async.bulk.prefetch.L2.global [%0], %1;" ::"l"((const char*)kcache + (size_t)kvrow0 * 256), "r"(EARLY_PF) : "memory");
    TS(threadIdx.x == 0, 0);
    const uint32_t sb = (smem_u32(smem_raw) + 1023u) & ~1023u;
    const int warp = threadIdx.x >> 5, lane = threadIdx.x & 31;
    const uint32_t s_full = sb + OFF_BAR, s_empty = s_full + N_IT * 8;

    if (warp == NCW) {
        const uint32_t t0 = gtime32();
        const int first = (c < NMOD) ? 0 : 2;
        if (lane == 0) {
#pragma unroll
            for (int i = 0; i < 2; i++) mbar_init(s_full + (first + i) * 8, 1);
            asm volatile("fence.proxy.async.shared::cta;" ::: "memory");
#pragma unroll
            for (int i = 0; i < 2; i++) {
                const uint32_t bar = s_full + (first + i) * 8;
                mbar_expect_tx(bar, 18432);
                tma3d(sb + (first + i) * 18432, &maps.m[M_WMOD + (first >> 1)], c * 32, 0, i * 2, bar);
            }
            TS(true, 17);
        }
        __syncwarp();
        uint32_t w0[2], w1[2], w2[2];
#pragma unroll
        for (int h = 0; h < 2; h++) {
            const int i = lane + 32 * h;
            int off, map, dep = -1, x = 0, y = 0, z = 0, sz = 36, cum;
            if (i < IT_K) {
                off = i * 18432; map = M_WMOD + (i >> 1); x = c * 32; z = (i & 1) * 2; cum = 31104 + (i - 2) * 18432;
            } else if (i < IT_V) {
                const int k = i - IT_K;
                off = k_off(k); map = M_K; y = kvrow0 + k * kvstep; sz = 32; cum = 67968 + k * 16384;
                if (k == 8 && c < NMOD) dep = EM_WMOD;
                if (k == 10) dep = EM_WQ;
                if (k >= 12) dep = EM_K + k - 12;
            } else if (i < IT_WO) {
                const int k = i - IT_V;
                off = v_off(k); map = M_V; y = kvrow0 + k * kvstep; sz = 32; cum = 330112 + k * 16384;
                dep = EM_K + 3 + k + (k < 4);
            } else if (i < IT_WD) {
                const int k = i - IT_WO;
                off = k ? OFF_WO1 : OFF_WO0; map = M_WO; y = kvh * 256 + k * 128 + j * 16; dep = EM_V + 4 + 2 * k;
                cum = 592256 + k * 18432;
            } else if (i < IT_GU) {
                const int k = i - IT_WD;
                off = OFF_D + k * DSTR; map = wide ? M_WD48 : M_WD; y = f0; z = k * 3; sz = wide ? 36 : 24; dep = EM_V + 7 + k;
                cum = 629120 + k * 13824;
            } else {
                const int k = i - IT_GU;
                off = OFF_GU + k * GSTR; map = M_WG + (k & 1) + (wide ? 3 : 0);
                x = f0; y = (k >> 1) * 16; sz = wide ? 27 : 18; dep = min(EM_V + 5 + ((off + GSTR - 1) >> 14), EM_V + 15);
                cum = 670592 + k * 10368;
            }
            const int stag = (KVROT && i >= IT_K && i < IT_WO) ? (((kvh * 2 + bb) * 13) & 31) * 512 + sp * (KVROT - 1) * 128 : ((c * 37) & 127) * 128;
            cum += EARLY_PF - min(max(cum - 67968, 0), EARLY_PF);
            int due = (int)((float)max(min(cum, 629120) + stag - PACE_LEAD, 0) * (128.0f / PACE_GBS));
            if (i >= IT_WD) due += TAIL_GAP + (int)((float)(min(cum, 670592) - 629120) * (128.0f / PACE_D));
            if (i >= IT_GU) due += WIN_GN + (int)((float)(cum - 670592) * (128.0f / PACE_TAIL));
            w0[h] = off | (map << 18) | ((dep + 1) << 22) | (z << 28);
            w1[h] = y | (sz << 24);
            w2[h] = x | (due << 13);
        }
        asm volatile("bar.sync 2, 384;" ::: "memory");
        uint32_t fb = s_full;
        asm volatile("" : "+r"(fb));
        bool open = false;
#pragma unroll 1
        for (int i = first + 2; i < N_IT; i++) {
            const bool hi = i >= 32;
            const uint32_t a = __shfl_sync(0xffffffffu, hi ? w0[1] : w0[0], i);
            const uint32_t b = __shfl_sync(0xffffffffu, hi ? w1[1] : w1[0], i);
            const uint32_t x = __shfl_sync(0xffffffffu, hi ? w2[1] : w2[0], i);
            if (lane == 0) {
                const uint32_t bar = fb + i * 8;
                if (!open) {
                    const int win = i >= IT_GU ? WIN_G0 : (i >= WIN_SWITCH) ? WIN_TAIL : WIN_MAIN;
                    const int dep = (a >> 22) & 63;
                    const uint32_t due = t0 + (x >> 13);
                    if (dep) mbar_wait(fb + (N_IT - 1 + dep) * 8);
                    if (i < IT_TAIL || !OPEN_WIN) {
                        if (i - win >= first) mbar_wait(bar - win * 8);
                        while ((int)(gtime32() - due) < 0) { }
                    } else {
                        const uint32_t ch = fb + (N_IT + EM_CH) * 8;
                        while (!mbar_test(bar - win * 8)) { if (mbar_test(ch)) { open = true; break; } }
                        while (!open && (int)(gtime32() - due) < 0) open = mbar_test(ch);
                    }
                }
                if (open && OPEN_WIN > 1) mbar_wait(bar - OPEN_WIN * 8);
                mbar_expect_tx(bar, (b >> 24) * 512);
                tma3d(fb - OFF_BAR + (a & 0x3ffff), &maps.m[(a >> 18) & 15], x & 0x1fff, b & 0xffffff, a >> 28, bar);
                TS(i == IT_WO, 1);
                TS(i == N_IT - 1, 2);
            }
            __syncwarp();
        }
        return;
    }

    const int g = lane >> 2, t = lane & 3, mi = lane >> 3, r = lane & 7;
    const int bat = g & 1;

    if (warp > NCW) {
        const bool first = warp == NCW + 1, active = first || c < 16;
        const int unit = first ? c : NCTA + c;
        const int rcol = (unit >> 2) * 16 + (unit & 3) * 2 + (lane & 1) + (lane & 2) * 4 + bat * DM;
        const unsigned ep = ldg_rlx1(scr + G_EPOCH);
        uint32_t xold = 0, ga = 0, gb = 0;
        if (active) xold = __ldg((const unsigned short*)xin + rcol);
        if (!first) asm volatile("bar.sync 2, 384;" ::: "memory");
        const unsigned tag = (ep + 1u) & 1u;
        unsigned side = 0;
        const int x1w = G_X1 + (unit >> 7) * 2048 + (unit & 127) * 8 + r + (lane & 8) * (HALF / 8) + (lane >> 4) * 4096;
        if (first) {
            unsigned* pr = scr + G_PROBE + c * 8;
            if (lane < 16) stg_rlx1(pr + r + (lane & 8) * (HALF / 8), 0u);
            __syncwarp();
            asm volatile("bar.arrive 2, 384;" ::: "memory");
            unsigned best0 = ~0u, best1 = ~0u, v = 0, cp = 0;
#pragma unroll 1
            for (int i = 0; i <= 2 * NPROBE; i++) {
                if (lane == 0) {
                    asm volatile("atom.relaxed.gpu.global.add.u32 %0, [%1], 1;" : "=r"(v) : "l"(pr + (i & 1) * HALF + (v >> 31)) : "memory");
                    const unsigned cn = clock(), d = cn - cp;
                    cp = cn;
                    if (i & 1) best0 = min(best0, d); else if (i) best1 = min(best1, d);
                    side = (best1 < best0) ^ (__popc(G_PROBE & 0x2C800) & 1);
                }
                if (i == 2 * NPROBE0) {
                    asm volatile("bar.sync 6, 64;" ::: "memory");
                    if (lane == 0) { sts32(sb + OFF_WMX + 116, side); mbar_arrive(s_empty + EM_SD * 8); }
                }
            }
            if (lane == 0) sts32(sb + OFF_WMX + 112, side);
            side = __shfl_sync(0xffffffffu, side, 0);
            mbar_wait(s_full + it_v(PH_V) * 8);
#pragma unroll 1
            for (int u = c; u < 144; u += NCTA) {
                unsigned* q = scr + G_PART + u * 2048 + near_half(G_PART + u * 2048, side) + lane * 4;
#pragma unroll
                for (int i = 0; i < 8; i++) stg_ph(q + i * 128);
#pragma unroll
                for (int i = 0; i < XREP; i += 2) stg_rlx1(scr + x1w + (u >> 7) * 2048 + i * 4096, 2u);
            }
            unsigned* o = scr + G_OP + kvh * 4096 + (j >> 2) * 2048 + (j & 3) * 256 + lane * 4;
            stg_ph(o); stg_ph(o + 128); stg_ph(o + HALF); stg_ph(o + HALF + 128);
            __threadfence();
            __syncwarp();
            if (lane < 8) stg_rlx1(scr + G_SIDE + c * 8 + lane, (side << 4) | tag);
            if (lane == 0) mbar_arrive(s_empty + EM_PH * 8);
        } else {
            asm volatile("bar.arrive 6, 64;" ::: "memory");
            if (TM_PF && lane < 8) asm volatile("prefetch.tensormap [%0];" ::"l"(&maps.m[lane + ((wide && lane >= M_WG) ? 3 : 0)]) : "memory");
            mbar_wait(s_empty + EM_PH * 8);
            side = __float_as_uint(ldsf(sb + OFF_WMX + 112));
        }
        if (active) {
            int it = 0;
            do {
                ga = ldg_rlx1(scr + dual_near(G_MOD, 2 * 1152 + unit * 8 + r, side));
                gb = ldg_rlx1(scr + dual_near(G_MOD, 5 * 1152 + unit * 8 + r, side));
            } while (any_lane(((ga ^ tag) | (gb ^ tag)) & 7u) && ++it < SPIN_LIMIT);
            ga >>= 16; gb >>= 16;
        }
        __syncwarp();
        if (first) {
            const int ow = G_OP + kvh * 4096 + (g >> 2) * 2048;
            const unsigned* q = scr + ow + near_half(ow, side) + (g & 3) * 256 + j * 32 + t * 8;
            mbar_wait(s_full + it_v(15) * 8);
            uint4 lo, hi;
            int it = 0;
            do { lo = ldg_pkt(q); hi = ldg_pkt(q + 4); } while (any_lane(((lo.x ^ tag) | (hi.x ^ tag)) & 7u) && ++it < SPIN_LIMIT);
            float o[8] = {untagf(lo.x), __uint_as_float(lo.y), __uint_as_float(lo.z), __uint_as_float(lo.w),
                          untagf(hi.x), __uint_as_float(hi.y), __uint_as_float(hi.z), __uint_as_float(hi.w)};
            __syncwarp();
#pragma unroll
            for (int sft = 8; sft <= 16; sft <<= 1) {
#pragma unroll
                for (int i = 0; i < 8; i++) o[i] += shx(o[i], sft);
            }
            if (lane < 8)
                sts128(sb + OFF_FR + lane * 48, pack2(o[0], o[4]), pack2(o[2], o[6]), pack2(o[1], o[5]), pack2(o[3], o[7]));
            TS(lane == 0, 10);
        }
        asm volatile("bar.sync 3, 352;" ::: "memory");
        const unsigned* q = scr + G_PART + unit * 2048 + near_half(G_PART + unit * 2048, side) + lane * 4;
        if (!active) return;
#pragma unroll 1
        for (int ph = 0; ph < 2; ph++) {
            if (ph) asm volatile("bar.sync %0, 128;" ::"r"(first ? 5 : 7) : "memory");
            spin_cycles(ph ? DELAY_D : DELAY_B);
            unsigned dur[4] = {};
            TS(ph && first && lane == 0, 18);
            const float k = reduce_unit(q, lane, tag | (ph * 4u), dur);
            xold = badd2(xold, bmul2(ga, pack2(k, 0.f))) & 0xffffu;
            ga = gb;
            if (ph) {
                if (lane < 8) ((unsigned short*)out)[rcol] = (unsigned short)xold;
            } else {
#pragma unroll
                for (int i = 0; i < XREP; i += 2) stg_rlx1(scr + x1w + i * 4096, (xold << 16) | tag);
                if (first && lane == 0) mbar_arrive(s_empty + EM_X1 * 8);
            }
            TS(first && lane == 0, 12 + 4 * ph);
        }
        if (c == 0 && first && lane == 0) stg_rlx1(scr + G_EPOCH, ep + 1u);
        return;
    }

    const int vw = warp, tid = threadIdx.x;
    const int vecw = tid * 4 - (lane & 7) * 4 + t * 8 + bat * 4;
    unsigned* ppart = scr + G_PART + (vw * 16 + t * 4 + (g >> 1)) * 2048 + c * 8 + bat * 4;
    const unsigned* const pside = scr + G_SIDE + ((vw * 16 + t * 4 + (g >> 1)) & 127) * 8;
    const int qword = dual(G_Q, bat * 4096 + c * 32 + (tid >> 3) * 4 + t), mword = dual(G_MOD, c * 64 + (tid & 63));
    const uint32_t one2 = 0x3f803f80u;

    const unsigned ep = ldg_rlx1(scr + G_EPOCH);
    if (tid < 64) {
        if (c < NMOD) { stg_rlx1(scr + mword, 2u); stg_rlx1(scr + mword + HALF, 2u); }
        stg_rlx1(scr + qword, 2u); stg_rlx1(scr + qword + HALF, 2u);
    }
    uint32_t xw0, xw1, aw0, aw1;
    {
        const int col0 = bat * DM + (vw * 4 + mi) * 16 + 2 * t;
        const uint32_t cw0 = __ldg((const unsigned*)(cin + col0)), cw1 = __ldg((const unsigned*)(cin + col0 + 8));
        xw0 = __ldg((const unsigned*)(xin + col0)); xw1 = __ldg((const unsigned*)(xin + col0 + 8));
        if (lane == 0) {
            const int lo = (c < NMOD) ? 2 : 4;
#pragma unroll 1
            for (int i = vw; i < N_IT + N_EM; i += NCW) {
                const int e = i - N_IT;
                if (i >= lo) mbar_init(s_full + i * 8, (e < 0 || e >= EM_PH) ? 1 : (e < EM_K ? NCW : (e < EM_V ? 4 : 8)));
            }
            asm volatile("fence.proxy.async.shared::cta;" ::: "memory");
        }
        __syncwarp();
        asm volatile("bar.sync 2, 384;" ::: "memory");
        float cv[4] = {bflo(cw0), bfhi(cw0), bflo(cw1), bfhi(cw1)};
#pragma unroll
        for (int i = 0; i < 4; i++) cv[i] = cv[i] * rcp(1.0f + ex2(-1.4426950408889634f * cv[i]));
        aw0 = pack2(cv[0], cv[1]); aw1 = pack2(cv[2], cv[3]);
    }
    const unsigned tag = (ep + 1u) & 1u;
    const uint32_t st1 = sb + OFF_STAT + bat * 80, st2 = st1 + 160;
    ln_stage1(xw0, xw1, st1, vw, lane);

    if (c < NMOD) {
        const uint32_t m = gemv32(sb + OFF_WMOD, sb + OFF_RED, s_full + IT_WMOD * 8, s_empty + EM_WMOD * 8, aw0, aw1, tid);
        if (tid < 64) { stg_rlx1(scr + mword, m | tag); stg_rlx1(scr + mword + HALF, m | tag); }
    } else {
        bar_consumers();
    }
    TS(tid == 0, 4);
    mbar_wait(s_empty + EM_SD * 8);
    unsigned side = __float_as_uint(ldsf(sb + OFF_WMX + 116));
    {
        uint32_t y0, y1;
        ln_stage2(ln_load(st1), xw0, xw1, y0, y1);
        uint4 a, b;
        int it = 0;
        const unsigned *pa = scr + dual_near(G_MOD, vecw, side), *pb = scr + dual_near(G_MOD, 1152 + vecw, side);
        do { a = ldg_rlx4(pa); b = ldg_rlx4(pb); }
        while (any_lane((bad4(a, tag) | bad4(b, tag)) & 7u) && ++it < SPIN_LIMIT);
        __syncwarp();
        aw0 = badd2(bmul2(y0, badd2(one2, hi2(b.x, b.y))), hi2(a.x, a.y));
        aw1 = badd2(bmul2(y1, badd2(one2, hi2(b.z, b.w))), hi2(a.z, a.w));
        TS(tid == 0, 5);
        const uint32_t q = gemv32(sb + OFF_WQ, sb + OFF_RED + 2304, s_full + IT_WQ * 8, s_empty + EM_WQ * 8, aw0, aw1, tid);
        if (tid < 64) {
            stg_rlx1(scr + qword, q | tag); stg_rlx1(scr + qword + HALF, q | tag);
            uint4 v;
            int it = 0;
            const unsigned* pq = scr + dual_near(G_Q, bb * 4096 + kvh * 256 + tid * 4, side);
            do { v = ldg_rlx4(pq); } while (any_lane(bad4(v, tag) & 7u) && ++it < SPIN_LIMIT);
            sts64(sb + OFF_QS + (vw * 4 + t) * 80 + g * 8, hi2(v.x, v.y), hi2(v.z, v.w));
        }
        bar_consumers();
        TS(tid == 0, 6);
    }
    uint32_t sc0, sc1, sh0, sh1;
    {
        uint4 d, e;
        unsigned bad;
        int it = 0;
        do {
            d = ldg_rlx4(scr + dual_near(G_MOD, 3 * 1152 + vecw, side)); e = ldg_rlx4(scr + dual_near(G_MOD, 4 * 1152 + vecw, side));
            bad = bad4(d, tag) | bad4(e, tag);
        } while (any_lane(bad & 7u) && ++it < SPIN_LIMIT);
        __syncwarp();
        sh0 = hi2(d.x, d.y); sh1 = hi2(d.z, d.w);
        sc0 = badd2(one2, hi2(e.x, e.y)); sc1 = badd2(one2, hi2(e.z, e.w));
    }
    if (vw < 8) {
        uint4 qf[4];
#pragma unroll
        for (int i = 0; i < 4; i++) qf[i] = lds128(sb + OFF_QS + r * 80 + i * 16);
        const int mt = vw & 3;
        const uint32_t rowoff = (mt * 16 + r + 8 * (mi & 1)) * 128;
        const uint32_t sw = ((mi >> 1) ^ r) << 4;
        uint32_t mx = 0xff80ff80u;
#pragma unroll 1
        for (int i = (vw >> 2); i < 16; i += 2) {
            mbar_wait(s_full + (IT_K + i) * 8);
            const uint32_t base = sb + k_off(i) + rowoff;
            float c0[4] = {}, c1[4] = {};
            uint32_t a[4];
            ldsm4(a, base + sw);               mma16816(c0, a, qf[0].x, qf[0].y);
            ldsm4(a, base + 8192 + sw);        mma16816(c1, a, qf[2].x, qf[2].y);
            ldsm4(a, base + (sw ^ 32));        mma16816(c0, a, qf[0].z, qf[0].w);
            ldsm4(a, base + 8192 + (sw ^ 32)); mma16816(c1, a, qf[2].z, qf[2].w);
            ldsm4(a, base + (sw ^ 64));        mma16816(c0, a, qf[1].x, qf[1].y);
            ldsm4(a, base + 8192 + (sw ^ 64)); mma16816(c1, a, qf[3].x, qf[3].y);
            ldsm4(a, base + (sw ^ 96));        mma16816(c0, a, qf[1].z, qf[1].w);
            ldsm4(a, base + 8192 + (sw ^ 96)); mma16816(c1, a, qf[3].z, qf[3].w);
            __syncwarp();
            if (lane == 0) mbar_arrive(s_empty + (EM_K + i) * 8);
            const float scl = 0.08838834764831845f;
            uint32_t u0 = pack2(c0[0] + c1[0], c0[1] + c1[1]), u1 = pack2(c0[2] + c1[2], c0[3] + c1[3]);
            u0 = pack2(bflo(u0) * scl, bfhi(u0) * scl); u1 = pack2(bflo(u1) * scl, bfhi(u1) * scl);
            mx = bmax2(mx, bmax2(u0, u1));
            if (t == 0) {
                const uint32_t pa = sb + OFF_S + (i * 64 + 16 * (g >> 1) + 4 * mt + bat) * 4;
                sts32(pa, u0); sts32(pa + 8, u1);
            }
            if (i == PH_K && tid < 4) stg_ph(scr + G_ML + c * 8 + (tid & 1) * 4 + (tid & 2) * (HALF / 2));
        }
#pragma unroll
        for (int o = 4; o <= 16; o <<= 1) mx = bmax2(mx, __shfl_xor_sync(0xffffffffu, mx, o));
        if (lane == 0) sts32(sb + OFF_WMX + vw * 4, mx);
    }
    bar_consumers();
    TS(tid == 0, 7);
    {
        const float L2E = 1.4426950408889634f;
        uint4 sv = make_uint4(0, 0, 0, 0);
        float m0 = 0.f, m1 = 0.f;
        if (vw < 8) {
            uint4 ma = lds128(sb + OFF_WMX), mb = lds128(sb + OFF_WMX + 16);
            const uint32_t mx = bmax2(bmax2(bmax2(ma.x, ma.y), bmax2(ma.z, ma.w)), bmax2(bmax2(mb.x, mb.y), bmax2(mb.z, mb.w)));
            m0 = bflo(mx); m1 = bfhi(mx);
            sv = lds128(sb + OFF_S + tid * 16);
            float e0 = (ex2((bflo(sv.x) - m0) * L2E) + ex2((bflo(sv.y) - m0) * L2E)) + (ex2((bflo(sv.z) - m0) * L2E) + ex2((bflo(sv.w) - m0) * L2E));
            float e1 = (ex2((bfhi(sv.x) - m1) * L2E) + ex2((bfhi(sv.y) - m1) * L2E)) + (ex2((bfhi(sv.z) - m1) * L2E) + ex2((bfhi(sv.w) - m1) * L2E));
#pragma unroll
            for (int o = 16; o > 0; o >>= 1) { e0 += shx(e0, o); e1 += shx(e1, o); }
            if (lane == 0) sts64(sb + OFF_WMX + 32 + vw * 8, __float_as_uint(e0), __float_as_uint(e1));
        }
        bar_consumers();
        if (vw == 0) {
            float l0 = 0.f, l1 = 0.f;
#pragma unroll
            for (int w = 0; w < 4; w++) {
                uint4 s = lds128(sb + OFF_WMX + 32 + w * 16);
                l0 += __uint_as_float(s.x) + __uint_as_float(s.z); l1 += __uint_as_float(s.y) + __uint_as_float(s.w);
            }
            if (tid < 4) stg_pkt(scr + G_ML + c * 8 + (tid & 1) * 4 + (tid & 2) * (HALF / 2), m0, l0, m1, l1, tag);
            {
                const bool rd = lane < 4 && lane != sp;
                uint4 v = make_uint4(rd ? 2u : tag, 0, 0, 0);
                int it = 0;
                do { ldg_pkt_if(v, scr + G_ML + near_half(G_ML, side) + (kvh * 8 + (lane & 3) * 2 + bb) * 8, (v.x ^ tag) & 7u); }
                while (any_lane((v.x ^ tag) & 7u) && ++it < SPIN_LIMIT);
                if (rd) { m0 = untagf(v.x); l0 = __uint_as_float(v.y); m1 = __uint_as_float(v.z); l1 = __uint_as_float(v.w); }
            }
            float g0 = fmaxf(m0, shx(m0, 1)), g1 = fmaxf(m1, shx(m1, 1));
            g0 = fmaxf(g0, shx(g0, 2)); g1 = fmaxf(g1, shx(g1, 2));
            l0 *= ex2((m0 - g0) * L2E); l1 *= ex2((m1 - g1) * L2E);
            l0 += shx(l0, 1); l1 += shx(l1, 1);
            l0 += shx(l0, 2); l1 += shx(l1, 2);
            if (lane == 0)
                sts128(sb + OFF_WMX + 96, __float_as_uint(g0), __float_as_uint(g1), __float_as_uint(__frcp_rn(l0)), __float_as_uint(__frcp_rn(l1)));
        }
        bar_consumers();
        if (vw < 8) {
            const uint4 gs = lds128(sb + OFF_WMX + 96);
            const float g0 = __uint_as_float(gs.x), g1 = __uint_as_float(gs.y), i0 = __uint_as_float(gs.z), i1 = __uint_as_float(gs.w);
            const uint32_t a0 = pack2(ex2((bflo(sv.x) - g0) * L2E) * i0, ex2((bflo(sv.y) - g0) * L2E) * i0);
            const uint32_t a1 = pack2(ex2((bflo(sv.z) - g0) * L2E) * i0, ex2((bflo(sv.w) - g0) * L2E) * i0);
            const uint32_t b0 = pack2(ex2((bfhi(sv.x) - g1) * L2E) * i1, ex2((bfhi(sv.y) - g1) * L2E) * i1);
            const uint32_t b1 = pack2(ex2((bfhi(sv.z) - g1) * L2E) * i1, ex2((bfhi(sv.w) - g1) * L2E) * i1);
            sts64(sb + OFF_P + tid * 8, a0, a1); sts64(sb + OFF_P + PSTR + tid * 8, b0, b1);
        }
        bar_consumers();
        TS(tid == 0, 8);
    }
    const uint32_t rsw = ((mi & 1) ^ r) << 4;
    unsigned sidew = 2u;
    if (vw < 8) {
        float c0[4] = {}, c1[4] = {};
        const uint32_t vo = (vw >> 2) * 8192 + (r + 8 * (mi >> 1)) * 128 + ((((2 * vw + (mi & 1)) & 7) ^ r) << 4);
        const uint32_t pa = sb + OFF_P + bat * PSTR + t * 32;
#pragma unroll 1
        for (int i = 0; i < 16; i++) {
            uint4 pb0 = lds128(pa + i * 128), pb1 = lds128(pa + i * 128 + 16);
            mbar_wait(s_full + it_v(i) * 8);
            const uint32_t base = sb + v_off(i) + vo;
            uint32_t a0[4], a1[4], a2[4], a3[4];
            ldsm4t(a0, base); ldsm4t(a1, base + 2048); ldsm4t(a2, base + 4096); ldsm4t(a3, base + 6144);
            mma16816(c0, a0, pb0.x, pb0.y);
            mma16816(c1, a1, pb0.z, pb0.w);
            mma16816(c0, a2, pb1.x, pb1.y);
            mma16816(c1, a3, pb1.z, pb1.w);
            __syncwarp();
            if (lane == 0) mbar_arrive(s_empty + (EM_V + i) * 8);
            if (i == SIDE_V) { mbar_wait(s_empty + EM_PH * 8); sidew = ldg_rlx1(pside); }
        }
        if (t < 2)
            stg_pkt(scr + G_OP + kvh * 4096 + (j >> 2) * 2048 + t * HALF + (j & 3) * 256 + vw * 32 + g * 4,
                    c0[0] + c1[0], c0[1] + c1[1], c0[2] + c1[2], c0[3] + c1[3], tag);
        TS(tid == 0, 9);
    } else {
        mbar_wait(s_full + it_v(SIDE_V) * 8);
        mbar_wait(s_empty + EM_PH * 8);
    }
    {
        int it = 0;
        while (any_lane((sidew ^ tag) & 7u) && ++it < SPIN_LIMIT) sidew = ldg_rlx1(pside);
        ppart += near_half(G_PART + (vw * 16 + t * 4 + (g >> 1)) * 2048, sidew >> 4);
    }
    side = __float_as_uint(ldsf(sb + OFF_WMX + 112));
    const uint32_t rrow = sb + (r + 8 * (mi >> 1)) * 128;
    uint32_t ad[3][4][4];
    {
        mbar_wait(s_full + IT_WO * 8);
#pragma unroll
        for (int mt = 0; mt < 4; mt++) ldsm4t(ad[0][mt], rrow + OFF_WO0 + vw * 2048 + (rsw ^ (mt * 32)));
        mbar_wait(s_full + (IT_WO + 1) * 8);
#pragma unroll
        for (int mt = 0; mt < 4; mt++) ldsm4t(ad[1][mt], rrow + OFF_WO1 + vw * 2048 + (rsw ^ (mt * 32)));
        asm volatile("bar.sync 3, 352;" ::: "memory");
        const uint4 fr = lds128(sb + OFF_FR + r * 48);
        float cc[4][4] = {};
#pragma unroll
        for (int mt = 0; mt < 4; mt++) mma16816(cc[mt], ad[0][mt], fr.x, fr.y);
#pragma unroll
        for (int mt = 0; mt < 4; mt++) mma16816(cc[mt], ad[1][mt], fr.z, fr.w);
        publish_partials(ppart, t, cc, tag);
        TS(tid == 0, 11);
    }
    mbar_wait(s_empty + EM_X1 * 8);
    {
        uint4 v;
        int it = 0;
        const int xw = G_X1 + (vw >> 3) * 2048 + (c & (XREP - 1)) * 4096;
        const unsigned* px = scr + xw + near_half(xw, side) + (vecw & 1023);
        do { v = ldg_rlx4(px); } while (any_lane(bad4(v, tag) & 7u) && ++it < SPIN_LIMIT);
        xw0 = hi2(v.x, v.y); xw1 = hi2(v.z, v.w);
        ln_stage1(xw0, xw1, st2, vw, lane);
        bar_consumers();
        if (tid == 0) mbar_arrive(s_empty + EM_CH * 8);
        TS(tid == 0, 13);
        uint32_t y0, y1;
        ln_stage2(ln_load(st2), xw0, xw1, y0, y1);
        aw0 = badd2(bmul2(y0, sc0), sh0); aw1 = badd2(bmul2(y1, sc1), sh1);
        {
            const uint32_t db = rrow + OFF_D + (vw / 3) * DSTR + (vw % 3) * (wide ? 6144 : 4096);
            mbar_wait(s_full + (IT_WD + vw / 3) * 8);
#pragma unroll
            for (int ks = 0; ks < 2; ks++)
#pragma unroll
                for (int mt = 0; mt < 4; mt++) ldsm4t(ad[ks][mt], db + ks * 2048 + (rsw ^ (mt * 32)));
            if (wide) {
#pragma unroll
                for (int mt = 0; mt < 4; mt++) ldsm4t(ad[2][mt], db + 4096 + (rsw ^ (mt * 32)));
            }
        }
        const uint32_t gpitch = wide ? 96 : 64, gsw = wide ? 0 : (r >> 1) << 4;
        const uint32_t gbase = sb + OFF_GU + (mi & 1) * GSTR + (vw * 16 + r + 8 * (mi >> 1)) * gpitch;
        float cc[6][4] = {};
#pragma unroll 1
        for (int ks = 0; ks < 4; ks++) {
            const uint32_t b0 = __shfl_sync(0xffffffffu, aw0, ks * 8 + r), b1 = __shfl_sync(0xffffffffu, aw1, ks * 8 + r);
            const uint32_t ga = gbase + ks * 2 * GSTR;
            uint32_t ag[6][4];
            mbar_wait(s_full + (IT_GU + 2 * ks) * 8);
            mbar_wait(s_full + (IT_GU + 2 * ks + 1) * 8);
#pragma unroll
            for (int q = 0; q < 4; q++) ldsm4t(ag[q], ga + ((q << 4) ^ gsw));
            if (wide) { ldsm4t(ag[4], ga + 64); ldsm4t(ag[5], ga + 80); }
#pragma unroll
            for (int q = 0; q < 4; q++) mma16816(cc[q], ag[q], b0, b1);
            if (wide) { mma16816(cc[4], ag[4], b0, b1); mma16816(cc[5], ag[5], b0, b1); }
        }
        if (t == 0) {
#pragma unroll
            for (int q = 0; q < 6; q++) sts128f(sb + OFF_RED + vw * 768 + q * 128 + g * 16, cc[q]);
        }
        bar_consumers();
        TS(tid == 0, 14);
        if (tid < 192) {
            float sv[NCW];
#pragma unroll
            for (int w = 0; w < NCW; w++) sv[w] = ldsf(sb + OFF_RED + w * 768 + tid * 4);
            const float s = ((sv[0] + sv[1]) + (sv[2] + sv[3])) + ((sv[4] + sv[5]) + (sv[6] + sv[7])) + sv[8];
            const uint32_t gu = pack2(s, __shfl_down_sync(0xffffffffu, s, 2));
            const float gt = bflo(gu);
            const uint32_t hh = pack2(((gt > 0.f) ? gt : gt * 0.0f) * bfhi(gu), 0.f);
            const int rr = tid >> 2;
            if ((tid & 2) == 0)
                sts16(sb + OFF_FR + ((tid & 1) * 4 + ((rr & 7) >> 1)) * 48 + (rr >> 3) * 4 + (rr & 1) * 2, hh);
        }
    }
    {
        bar_consumers();
        const uint4 fr = lds128(sb + OFF_FR + r * 48);
        const uint2 f2 = lds64(sb + OFF_FR + r * 48 + 16);
        float cc[4][4] = {};
#pragma unroll
        for (int mt = 0; mt < 4; mt++) mma16816(cc[mt], ad[0][mt], fr.x, fr.y);
#pragma unroll
        for (int mt = 0; mt < 4; mt++) mma16816(cc[mt], ad[1][mt], fr.z, fr.w);
        if (wide) {
#pragma unroll
            for (int mt = 0; mt < 4; mt++) mma16816(cc[mt], ad[2][mt], f2.x, f2.y);
        }
        publish_partials(ppart, t, cc, tag | 4u);
        TS(tid == 160, 15);
    }
    if (vw / 3 == c / 48) asm volatile("bar.arrive 5, 128;" ::: "memory");
    if (vw >= 6 && c < 16) asm volatile("bar.arrive 7, 128;" ::: "memory");
}

typedef CUresult (*EncodeFn)(CUtensorMap*, CUtensorMapDataType, cuuint32_t, void*, const cuuint64_t*, const cuuint64_t*,
                             const cuuint32_t*, const cuuint32_t*, CUtensorMapInterleave, CUtensorMapSwizzle,
                             CUtensorMapL2promotion, CUtensorMapFloatOOBfill);

void make_map(EncodeFn enc, CUtensorMap* m, const void* p, cuuint64_t d0, cuuint64_t d1, cuuint64_t d2,
              cuuint64_t s1, cuuint64_t s2, cuuint32_t b0, cuuint32_t b1, cuuint32_t b2, CUtensorMapSwizzle sw,
              CUtensorMapL2promotion pr = CU_TENSOR_MAP_L2_PROMOTION_L2_128B) {
    cuuint64_t dims[3] = {d0, d1, d2};
    cuuint64_t str[2] = {s1, s2};
    cuuint32_t box[3] = {b0, b1, b2};
    cuuint32_t es[3] = {1, 1, 1};
    enc(m, CU_TENSOR_MAP_DATA_TYPE_BFLOAT16, 3, const_cast<void*>(p), dims, str, box, es,
        CU_TENSOR_MAP_INTERLEAVE_NONE, sw, pr, CU_TENSOR_MAP_FLOAT_OOB_FILL_NONE);
}

}

extern "C" void kernel_launch(void* const* d_in, const int* in_sizes, int n_in, void* d_out, int out_size) {
    (void)in_sizes; (void)n_in; (void)out_size;
    void* fn = nullptr;
    cudaDriverEntryPointQueryResult qr;
    cudaGetDriverEntryPoint("cuTensorMapEncodeTiled", &fn, cudaEnableDefault, &qr);
    EncodeFn enc = (EncodeFn)fn;
    cudaFuncSetAttribute(fused_block_kernel, cudaFuncAttributeMaxDynamicSharedMemorySize, SMEM_BYTES);

    const void *x = d_in[0], *kc = d_in[1], *vc = d_in[2], *wq = d_in[3], *wo = d_in[4];
    const void *wg = d_in[6], *wu = d_in[7], *wd = d_in[8], *cc = d_in[9], *wmod = d_in[10];
    const CUtensorMapSwizzle S128 = CU_TENSOR_MAP_SWIZZLE_128B, S64 = CU_TENSOR_MAP_SWIZZLE_64B, S0 = CU_TENSOR_MAP_SWIZZLE_NONE;
    void* raw = nullptr;
    cudaGetSymbolAddress(&raw, g_raw);
    unsigned* scr = (unsigned*)(((uintptr_t)raw + 0x1fffff) & ~(uintptr_t)0x1fffff);
    Maps m;
    make_map(enc, &m.m[M_K], kc, 64, 32ull * 32768, 2, 256, 128, 64, 64, 2, S128, CU_TENSOR_MAP_L2_PROMOTION_L2_256B);
    make_map(enc, &m.m[M_V], vc, 64, 32ull * 32768, 2, 256, 128, 64, 64, 2, S128, CU_TENSOR_MAP_L2_PROMOTION_L2_256B);
    make_map(enc, &m.m[M_WMOD], wmod, 3456, 144, 4, 3456 * 2, 3456 * 2 * 144, 32, 144, 2, S64);
    make_map(enc, &m.m[M_WQ], wq, 4096, 144, 4, 4096 * 2, 4096 * 2 * 144, 32, 144, 2, S64);
    make_map(enc, &m.m[M_WG], wg, 4608, 64, 9, 4608 * 2, 4608 * 2 * 64, 32, 16, 9, S64);
    make_map(enc, &m.m[M_WU], wu, 4608, 64, 9, 4608 * 2, 4608 * 2 * 64, 32, 16, 9, S64);
    make_map(enc, &m.m[M_WG48], wg, 4608, 64, 9, 4608 * 2, 4608 * 2 * 64, 48, 16, 9, S0);
    make_map(enc, &m.m[M_WU48], wu, 4608, 64, 9, 4608 * 2, 4608 * 2 * 64, 48, 16, 9, S0);
    make_map(enc, &m.m[M_WO], wo, 64, 4096, 9, 1152, 128, 64, 16, 9, S128);
    make_map(enc, &m.m[M_WD], wd, 64, 4608, 9, 1152, 128, 64, 32, 3, S128);
    make_map(enc, &m.m[M_WD48], wd, 64, 4608, 9, 1152, 128, 64, 48, 3, S128);
    fused_block_kernel<<<NCTA, NTHR, SMEM_BYTES>>>(m, (const __nv_bfloat16*)x, (const __nv_bfloat16*)cc,
                                                   (const __nv_bfloat16*)kc, (__nv_bfloat16*)d_out, scr TUNE_ARG);
}
```

```cpp
#include <cuda_runtime.h>
#include <cuda.h>
#include <cuda_bf16.h>
#include <stdint.h>

namespace {

constexpr int DM = 576;
constexpr int NCTA = 128;
constexpr int NCW = 9;
constexpr int NTHR = (NCW + 3) * 32;
constexpr int NMOD = 108;

#define WIN_MAIN 4
#define WIN_TAIL 3
#define WIN_SWITCH 38
#define PACE_GBS 3100
#define PACE_LEAD 28672
#define PACE_TAIL 2900
#define TAIL_GAP 250
#define PACE_D 3300
#define OPEN_WIN 1
#define DELAY_B 300
#define DELAY_D 150
#define CTL_GAIN 0
#define CTL_MAIN 57344
#define CTL_TAIL 40960
#define CTL_SWITCH 30
#define CTL_SUB 1
#define KVPAT 1
#define KVROT 1
#define WIN_G0 4
#define WIN_GN 2
#define EARLY_PF 8192
#define TM_PF 1
#define XREP 2
#define PH_V 7
#define SIDE_V 11
#define NPROBE 10
#define NPROBE0 3
#define PH_K 8

#define TUNE_PARAM
#define TUNE_ARG

constexpr int IT_WMOD = 0, IT_WQ = 2, IT_K = 4, IT_V = 20, IT_WO = 36, IT_GU = 38, IT_WD = 46, N_IT = 49;
constexpr int IT_TAIL = IT_GU;
__device__ __forceinline__ constexpr int it_v(int k) { return IT_V + k; }
constexpr int EM_WMOD = 0, EM_WQ = 1, EM_K = 2, EM_V = 18, EM_PH = 34, EM_X1 = 35, EM_CH = 36, EM_SD = 37, N_EM = 38;

constexpr int RING = 13 * 16384;
constexpr int OFF_WMOD = 0, OFF_WQ = 36864, OFF_K0 = 73728;
constexpr int OFF_WO0 = 194560, OFF_WO1 = 0, OFF_GU = 18432, GSTR = 13824;
constexpr int OFF_D = 129024, DSTR = 18432;
constexpr int PSTR = 2064;
constexpr int OFF_P = RING;
constexpr int OFF_S = OFF_P + 4160;
constexpr int OFF_RED = OFF_S + 4096;
constexpr int OFF_QS = OFF_RED + 6912;
constexpr int OFF_FR = OFF_QS + 640;
constexpr int OFF_STAT = OFF_FR + 384;
constexpr int OFF_WMX = OFF_STAT + 320;
constexpr int OFF_BAR = OFF_WMX + 128;
constexpr int SMEM_USED = OFF_BAR + (N_IT + N_EM) * 8;
constexpr int SMEM_BYTES = SMEM_USED + 1024;
static_assert(SMEM_BYTES <= 232448, "smem");

struct Maps { CUtensorMap m[11]; };
enum { M_K, M_V, M_WMOD, M_WQ, M_WO, M_WG, M_WU, M_WD, M_WG48, M_WU48, M_WD48 };

constexpr int HALF = 1024;
constexpr int G_PART = 0;
constexpr int G_OP = G_PART + 144 * 2048;
constexpr int G_X1 = G_OP + 16 * 4096;
constexpr int G_PROBE = G_X1 + XREP * 4096;
constexpr int G_SIDE = G_PROBE + 2048;
constexpr int G_EPOCH = G_SIDE + 1024;
constexpr int G_MOD = G_EPOCH + 1024;
constexpr int G_Q = G_MOD + 7 * 2048;
constexpr int G_ML = G_Q + 8 * 2048;
constexpr int G_WORDS = G_ML + 2048;
static_assert(G_MOD % 2048 == 0 && G_OP % 2048 == 0 && G_X1 % 2048 == 0 && G_PROBE % 2048 == 0, "halves");
static_assert(G_WORDS * 4 <= (2 << 20), "scratch must fit one 2 MB page");
__device__ __align__(128) unsigned g_raw[(2 << 20) / 4 + G_WORDS + 8192];
__device__ __forceinline__ int near_half(int w, unsigned side) { return ((__popc(w & 0x2C800) ^ side) & 1) << 10; }
__device__ __forceinline__ int dual(int base, int i) { return base + i + (i & ~1023); }
__device__ __forceinline__ int dual_near(int base, int i, unsigned side) { const int w = dual(base, i); return w + near_half(w, side); }
#define g_ts ((unsigned long long*)(scr + G_WORDS))

constexpr int SPIN_LIMIT = 1 << 20;

__device__ __forceinline__ uint32_t smem_u32(const void* p) { return (uint32_t)__cvta_generic_to_shared(p); }
__device__ __forceinline__ void mbar_init(uint32_t bar, int cnt) {
    asm volatile("mbarrier.init.shared::cta.b64 [%0], %1;" ::"r"(bar), "r"(cnt) : "memory");
}
__device__ __forceinline__ void mbar_expect_tx(uint32_t bar, uint32_t bytes) {
    asm volatile("mbarrier.arrive.expect_tx.shared::cta.b64 _, [%0], %1;" ::"r"(bar), "r"(bytes) : "memory");
}
__device__ __forceinline__ void mbar_arrive(uint32_t bar) {
    asm volatile("mbarrier.arrive.shared::cta.b64 _, [%0];" ::"r"(bar) : "memory");
}
__device__ __forceinline__ void mbar_wait(uint32_t bar) {
    asm volatile("{\n.reg .pred p;\nW_%=:\nmbarrier.try_wait.parity.shared::cta.b64 p, [%0], 0;\n@!p bra W_%=;\n}"
                 ::"r"(bar) : "memory");
}
__device__ __forceinline__ bool mbar_test(uint32_t bar) {
    uint32_t ok;
    asm volatile("{\n.reg .pred p;\nmbarrier.test_wait.parity.shared::cta.b64 p, [%1], 0;\nselp.u32 %0, 1, 0, p;\n}"
                 : "=r"(ok) : "r"(bar) : "memory");
    return ok;
}
__device__ __forceinline__ uint32_t gtime32() { uint32_t t; asm volatile("mov.u32 %0, %%globaltimer_lo;" : "=r"(t)); return t; }
__device__ __forceinline__ void tma3d(uint32_t dst, const CUtensorMap* m, int x, int y, int z, uint32_t bar) {
    asm volatile("cp.async.bulk.tensor.3d.shared::cluster.global.mbarrier::complete_tx::bytes [%0], [%1, {%3, %4, %5}], [%2];"
                 ::"r"(dst), "l"(m), "r"(bar), "r"(x), "r"(y), "r"(z) : "memory");
}
__device__ __forceinline__ void bar_consumers() { asm volatile("bar.sync 1, 288;" ::: "memory"); }

__device__ __forceinline__ void ldsm4(uint32_t (&a)[4], uint32_t addr) {
    asm volatile("ldmatrix.sync.aligned.m8n8.x4.shared.b16 {%0,%1,%2,%3}, [%4];"
                 : "=r"(a[0]), "=r"(a[1]), "=r"(a[2]), "=r"(a[3]) : "r"(addr) : "memory");
}
__device__ __forceinline__ void ldsm4t(uint32_t (&a)[4], uint32_t addr) {
    asm volatile("ldmatrix.sync.aligned.m8n8.x4.trans.shared.b16 {%0,%1,%2,%3}, [%4];"
                 : "=r"(a[0]), "=r"(a[1]), "=r"(a[2]), "=r"(a[3]) : "r"(addr) : "memory");
}
__device__ __forceinline__ void mma16816(float (&c)[4], const uint32_t (&a)[4], uint32_t b0, uint32_t b1) {
    asm volatile("mma.sync.aligned.m16n8k16.row.col.f32.bf16.bf16.f32 {%0,%1,%2,%3}, {%4,%5,%6,%7}, {%8,%9}, {%0,%1,%2,%3};"
                 : "+f"(c[0]), "+f"(c[1]), "+f"(c[2]), "+f"(c[3])
                 : "r"(a[0]), "r"(a[1]), "r"(a[2]), "r"(a[3]), "r"(b0), "r"(b1));
}
__device__ __forceinline__ float ldsf(uint32_t a) { float v; asm volatile("ld.shared.f32 %0, [%1];" : "=f"(v) : "r"(a) : "memory"); return v; }
__device__ __forceinline__ uint2 lds64(uint32_t a) {
    uint2 v; asm volatile("ld.shared.v2.u32 {%0,%1}, [%2];" : "=r"(v.x), "=r"(v.y) : "r"(a) : "memory"); return v;
}
__device__ __forceinline__ uint4 lds128(uint32_t a) {
    uint4 v; asm volatile("ld.shared.v4.u32 {%0,%1,%2,%3}, [%4];" : "=r"(v.x), "=r"(v.y), "=r"(v.z), "=r"(v.w) : "r"(a) : "memory"); return v;
}
__device__ __forceinline__ void sts16(uint32_t a, uint32_t v) { asm volatile("st.shared.u16 [%0], %1;" ::"r"(a), "h"((unsigned short)v) : "memory"); }
__device__ __forceinline__ void sts32(uint32_t a, uint32_t v) { asm volatile("st.shared.u32 [%0], %1;" ::"r"(a), "r"(v) : "memory"); }
__device__ __forceinline__ void sts64(uint32_t a, uint32_t x, uint32_t y) { asm volatile("st.shared.v2.u32 [%0], {%1,%2};" ::"r"(a), "r"(x), "r"(y) : "memory"); }
__device__ __forceinline__ void sts128(uint32_t a, uint32_t x, uint32_t y, uint32_t z, uint32_t w) {
    asm volatile("st.shared.v4.u32 [%0], {%1,%2,%3,%4};" ::"r"(a), "r"(x), "r"(y), "r"(z), "r"(w) : "memory");
}
__device__ __forceinline__ void sts128f(uint32_t a, const float (&c)[4]) {
    asm volatile("st.shared.v4.f32 [%0], {%1,%2,%3,%4};" ::"r"(a), "f"(c[0]), "f"(c[1]), "f"(c[2]), "f"(c[3]) : "memory");
}
__device__ __forceinline__ unsigned ldg_rlx1(const unsigned* p) {
    unsigned v; asm volatile("ld.relaxed.gpu.global.u32 %0, [%1];" : "=r"(v) : "l"(p) : "memory"); return v;
}
__device__ __forceinline__ uint4 ldg_rlx4(const unsigned* p) {
    uint4 v; asm volatile("ld.relaxed.gpu.global.v4.u32 {%0,%1,%2,%3}, [%4];" : "=r"(v.x), "=r"(v.y), "=r"(v.z), "=r"(v.w) : "l"(p) : "memory"); return v;
}
__device__ __forceinline__ uint4 ldg_pkt(const unsigned* p) {
    uint4 v;
    asm volatile("{\n.reg .b128 t;\n.reg .b64 lo, hi;\nld.relaxed.gpu.global.b128 t, [%4];\nmov.b128 {lo, hi}, t;\n"
                 "mov.b64 {%0,%1}, lo;\nmov.b64 {%2,%3}, hi;\n}"
                 : "=r"(v.x), "=r"(v.y), "=r"(v.z), "=r"(v.w) : "l"(p) : "memory");
    return v;
}
__device__ __forceinline__ void ldg_pkt_if(uint4& v, const unsigned* a, unsigned p) {
    asm volatile("{\n.reg .pred q;\n.reg .b128 t;\n.reg .b64 lo, hi;\nsetp.ne.u32 q, %5, 0;\n"
                 "mov.b64 lo, {%0,%1};\nmov.b64 hi, {%2,%3};\nmov.b128 t, {lo, hi};\n"
                 "@q ld.relaxed.gpu.global.b128 t, [%4];\nmov.b128 {lo, hi}, t;\n"
                 "mov.b64 {%0,%1}, lo;\nmov.b64 {%2,%3}, hi;\n}"
                 : "+r"(v.x), "+r"(v.y), "+r"(v.z), "+r"(v.w) : "l"(a), "r"(p) : "memory");
}
__device__ __forceinline__ bool any_lane(unsigned x) { return __any_sync(0xffffffffu, x != 0); }
__device__ __forceinline__ void stg_pkt(unsigned* p, float a, float b, float c, float d, unsigned tag) {
    unsigned x = (__float_as_uint(a) & ~7u) | tag;
    asm volatile("{\n.reg .b128 t;\n.reg .b64 lo, hi;\nmov.b64 lo, {%1,%2};\nmov.b64 hi, {%3,%4};\nmov.b128 t, {lo, hi};\n"
                 "st.relaxed.gpu.global.b128 [%0], t;\n}"
                 ::"l"(p), "r"(x), "r"(__float_as_uint(b)), "r"(__float_as_uint(c)), "r"(__float_as_uint(d)) : "memory");
}
__device__ __forceinline__ void stg_rlx1(unsigned* p, unsigned x) { asm volatile("st.relaxed.gpu.global.u32 [%0], %1;" ::"l"(p), "r"(x) : "memory"); }
__device__ __forceinline__ unsigned bad4(const uint4& v, unsigned tag) {
    return ((v.x ^ tag) | (v.y ^ tag)) | ((v.z ^ tag) | (v.w ^ tag));
}
__device__ __forceinline__ float untagf(unsigned w) { return __uint_as_float(w & ~7u); }
__device__ __forceinline__ uint32_t pack2(float lo, float hi) {
    uint32_t r; asm("cvt.rn.bf16x2.f32 %0, %1, %2;" : "=r"(r) : "f"(hi), "f"(lo)); return r;
}
__device__ __forceinline__ float bflo(uint32_t w) { return __uint_as_float(w << 16); }
__device__ __forceinline__ float bfhi(uint32_t w) { return __uint_as_float(w & 0xffff0000u); }
__device__ __forceinline__ uint32_t hi2(uint32_t a, uint32_t b) { return __byte_perm(a, b, 0x7632); }
__device__ __forceinline__ uint32_t badd2(uint32_t a, uint32_t b) { uint32_t r; asm("add.rn.bf16x2 %0, %1, %2;" : "=r"(r) : "r"(a), "r"(b)); return r; }
__device__ __forceinline__ uint32_t bsub2(uint32_t a, uint32_t b) { uint32_t r; asm("sub.rn.bf16x2 %0, %1, %2;" : "=r"(r) : "r"(a), "r"(b)); return r; }
__device__ __forceinline__ uint32_t bmul2(uint32_t a, uint32_t b) { uint32_t r; asm("mul.rn.bf16x2 %0, %1, %2;" : "=r"(r) : "r"(a), "r"(b)); return r; }
__device__ __forceinline__ uint32_t bmax2(uint32_t a, uint32_t b) { uint32_t r; asm("max.bf16x2 %0, %1, %2;" : "=r"(r) : "r"(a), "r"(b)); return r; }
__device__ __forceinline__ float ex2(float x) { float r; asm("ex2.approx.ftz.f32 %0, %1;" : "=f"(r) : "f"(x)); return r; }
__device__ __forceinline__ float rcp(float x) { float r; asm("rcp.approx.ftz.f32 %0, %1;" : "=f"(r) : "f"(x)); return r; }
__device__ __forceinline__ float fsqrt(float x) { float r; asm("sqrt.approx.ftz.f32 %0, %1;" : "=f"(r) : "f"(x)); return r; }
__device__ __forceinline__ float shx(float v, int m) { return __shfl_xor_sync(0xffffffffu, v, m); }
#define TS(cond, slot) do { } while (0)

__device__ __forceinline__ uint32_t k_off(int i) { return i < 8 ? OFF_K0 + i * 16384 : (i - 8) * 16384; }
__device__ __forceinline__ uint32_t v_off(int i) { return i < 5 ? (8 + i) * 16384 : (i - 5) * 16384; }

__device__ __forceinline__ void stg_ph(unsigned* p) { stg_pkt(p, 0.f, 0.f, 0.f, 0.f, 2u); }

__device__ __forceinline__ void ln_stage1(uint32_t xw0, uint32_t xw1, uint32_t st, int vw, int lane) {
    const float piv = __shfl_sync(0xffffffffu, bflo(xw0), lane & 4);
    const float d0 = bflo(xw0) - piv, d1 = bfhi(xw0) - piv, d2 = bflo(xw1) - piv, d3 = bfhi(xw1) - piv;
    float s1 = (d0 + d1) + (d2 + d3), s2 = (d0 * d0 + d1 * d1) + (d2 * d2 + d3 * d3);
    s1 += shx(s1, 1); s2 += shx(s2, 1);
    s1 += shx(s1, 2); s2 += shx(s2, 2);
    s1 += shx(s1, 8); s2 += shx(s2, 8);
    s1 += shx(s1, 16); s2 += shx(s2, 16);
    if ((lane & 27) == 0)
        sts64(st + vw * 8, __float_as_uint(piv + s1 * (1.0f / 64.0f)), __float_as_uint(s2 - s1 * s1 * (1.0f / 64.0f)));
}
struct LnStat { uint4 a, b, c, d; uint2 e; };
__device__ __forceinline__ LnStat ln_load(uint32_t st) {
    LnStat s; s.a = lds128(st); s.b = lds128(st + 16); s.c = lds128(st + 32); s.d = lds128(st + 48); s.e = lds64(st + 64);
    return s;
}
__device__ __forceinline__ void ln_stage2(const LnStat& s, uint32_t xw0, uint32_t xw1, uint32_t& y0, uint32_t& y1) {
    const float m[9] = {__uint_as_float(s.a.x), __uint_as_float(s.a.z), __uint_as_float(s.b.x), __uint_as_float(s.b.z),
                        __uint_as_float(s.c.x), __uint_as_float(s.c.z), __uint_as_float(s.d.x), __uint_as_float(s.d.z), __uint_as_float(s.e.x)};
    const float mean = (((m[0] + m[1]) + (m[2] + m[3])) + ((m[4] + m[5]) + (m[6] + m[7])) + m[8]) * (1.0f / NCW);
    const float m2 = ((__uint_as_float(s.a.y) + __uint_as_float(s.a.w)) + (__uint_as_float(s.b.y) + __uint_as_float(s.b.w))) +
                     ((__uint_as_float(s.c.y) + __uint_as_float(s.c.w)) + (__uint_as_float(s.d.y) + __uint_as_float(s.d.w))) + __uint_as_float(s.e.y);
    float d[9];
#pragma unroll
    for (int w = 0; w < 9; w++) d[w] = m[w] - mean;
    const float acc = (d[0] * d[0] + d[1] * d[1] + d[2] * d[2]) + (d[3] * d[3] + d[4] * d[4] + d[5] * d[5]) + (d[6] * d[6] + d[7] * d[7] + d[8] * d[8]);
    const float var = (m2 + 64.0f * acc) * (1.0f / DM);
    const uint32_t mv = pack2(mean, var);
    const float ve = bflo(pack2(bfhi(mv) + 1e-5f, 0.f));
    const float rinv = rcp(bflo(pack2(fsqrt(ve), 0.f)));
    const uint32_t mm = __byte_perm(mv, mv, 0x1010);
    const uint32_t e0 = bsub2(xw0, mm), e1 = bsub2(xw1, mm);
    y0 = pack2(bflo(e0) * rinv, bfhi(e0) * rinv); y1 = pack2(bflo(e1) * rinv, bfhi(e1) * rinv);
}
__device__ __forceinline__ void make_bfrags(uint32_t (&bf)[4][2], uint32_t aw0, uint32_t aw1, int r) {
#pragma unroll
    for (int ks = 0; ks < 4; ks++) {
        bf[ks][0] = __shfl_sync(0xffffffffu, aw0, ks * 8 + r);
        bf[ks][1] = __shfl_sync(0xffffffffu, aw1, ks * 8 + r);
    }
}
__device__ __forceinline__ uint32_t gemv32(uint32_t s_w, uint32_t red, uint32_t fullbar, uint32_t emptybar,
                                           uint32_t aw0, uint32_t aw1, int tid) {
    const int vw = tid >> 5, lane = tid & 31, g = lane >> 2, t = lane & 3, mi = lane >> 3, r = lane & 7;
    uint32_t bf[4][2];
    make_bfrags(bf, aw0, aw1, r);
    if (vw <= 4) mbar_wait(fullbar);
    if (vw >= 4) mbar_wait(fullbar + 8);
    float cc[2][4] = {};
    const uint32_t abase = s_w + (vw * 64 + r + 8 * (mi >> 1)) * 64;
    const uint32_t sw = ((mi & 1) ^ (r >> 1)) << 4;
#pragma unroll
    for (int ks = 0; ks < 4; ks++) {
#pragma unroll
        for (int mt = 0; mt < 2; mt++) {
            uint32_t a[4];
            ldsm4t(a, abase + ks * 1024 + (sw ^ (mt * 32)));
            mma16816(cc[mt], a, bf[ks][0], bf[ks][1]);
        }
    }
    if (t == 0) { sts128f(red + vw * 256 + g * 16, cc[0]); sts128f(red + vw * 256 + 128 + g * 16, cc[1]); }
    __syncwarp();
    if (lane == 0) mbar_arrive(emptybar);
    bar_consumers();
    float s = 0.f;
    if (tid < 64) {
        const uint32_t ra = red + ((tid & 58) | ((tid & 1) << 2) | ((tid >> 2) & 1)) * 4;
#pragma unroll
        for (int w = 0; w < NCW; w++) s += ldsf(ra + w * 256);
    }
    return pack2(0.f, s);
}
__device__ __forceinline__ void publish_partials(unsigned* q, int t, const float (&cc)[4][4], unsigned tag) {
    float v[4];
#pragma unroll
    for (int i = 0; i < 4; i++) {
        const float lo = (t & 1) ? cc[1][i] : cc[0][i], hi = (t & 1) ? cc[3][i] : cc[2][i];
        v[i] = (t & 2) ? hi : lo;
    }
    stg_pkt(q, v[0], v[1], v[2], v[3], tag);
}
__device__ __forceinline__ void spin_cycles(unsigned n) {
    const unsigned c0 = clock();
    while ((unsigned)clock() - c0 < n) { }
}
__device__ __forceinline__ float reduce_unit(const unsigned* q, int lane, unsigned tag, unsigned (&dur)[4]) {
    uint4 v[8];
#pragma unroll
    for (int i = 0; i < 8; i++) v[i] = ldg_pkt(q + i * 128);
    int it = 0;
    while (true) {
        unsigned bad = 0;
#pragma unroll
        for (int i = 0; i < 8; i += 2) bad |= (v[i].x ^ tag) | (v[i + 1].x ^ tag);
        const bool more = any_lane(bad & 7u);
        if (!more || ++it >= SPIN_LIMIT) break;
#pragma unroll
        for (int i = 0; i < 8; i++) ldg_pkt_if(v[i], q + i * 128, (v[i].x ^ tag) & 7u);
    }
    float s0 = 0.f, s1 = 0.f, s2 = 0.f, s3 = 0.f, u0 = 0.f, u1 = 0.f, u2 = 0.f, u3 = 0.f;
#pragma unroll
    for (int i = 0; i < 8; i += 2) {
        s0 += untagf(v[i].x); s1 += __uint_as_float(v[i].y); s2 += __uint_as_float(v[i].z); s3 += __uint_as_float(v[i].w);
        u0 += untagf(v[i + 1].x); u1 += __uint_as_float(v[i + 1].y); u2 += __uint_as_float(v[i + 1].z); u3 += __uint_as_float(v[i + 1].w);
    }
    s0 += u0; s1 += u1; s2 += u2; s3 += u3;
    __syncwarp();
    const bool h8 = lane & 2, bat = lane & 4;
    const float k0 = (h8 ? s2 : s0) + shx(h8 ? s0 : s2, 2);
    const float k1 = (h8 ? s3 : s1) + shx(h8 ? s1 : s3, 2);
    float k = (bat ? k1 : k0) + shx(bat ? k0 : k1, 4);
    k += shx(k, 8);
    k += shx(k, 16);
    return k;
}

__global__ void __launch_bounds__(NTHR, 1)
fused_block_kernel(const __grid_constant__ Maps maps, const __nv_bfloat16* __restrict__ xin,
                   const __nv_bfloat16* __restrict__ cin, const __nv_bfloat16* __restrict__ kcache,
                   __nv_bfloat16* __restrict__ out, unsigned* const scr TUNE_PARAM) {
    extern __shared__ unsigned char smem_raw[];
    const int c = blockIdx.x;
    const int kvh = c >> 3, j = c & 7, bb = j & 1, sp = j >> 1;
    const bool wide = j >= 6;
    const int f0 = kvh * 288 + (wide ? 48 * j - 96 : 32 * j);
    const int kvrow0 = (bb * 16 + kvh) * 32768 + 28672 + sp * (KVPAT ? 64 : 1024);
    const int kvstep = KVPAT ? 256 : 64;
    if (EARLY_PF && threadIdx.x == 0)
        asm volatile("cp.async.bulk.prefetch.L2.global [%0], %1;" ::"l"((const char*)kcache + (size_t)kvrow0 * 256), "r"(EARLY_PF) : "memory");
    TS(threadIdx.x == 0, 0);
    const uint32_t sb = (smem_u32(smem_raw) + 1023u) & ~1023u;
    const int warp = threadIdx.x >> 5, lane = threadIdx.x & 31;
    const uint32_t s_full = sb + OFF_BAR, s_empty = s_full + N_IT * 8;

    if (warp == NCW) {
        const uint32_t t0 = gtime32();
        const int first = (c < NMOD) ? 0 : 2;
        if (lane == 0) {
#pragma unroll
            for (int i = 0; i < 2; i++) mbar_init(s_full + (first + i) * 8, 1);
            asm volatile("fence.proxy.async.shared::cta;" ::: "memory");
#pragma unroll
            for (int i = 0; i < 2; i++) {
                const uint32_t bar = s_full + (first + i) * 8;
                mbar_expect_tx(bar, 18432);
                tma3d(sb + (first + i) * 18432, &maps.m[M_WMOD + (first >> 1)], c * 32, 0, i * 2, bar);
            }
            TS(true, 17);
        }
        __syncwarp();
        uint32_t w0[2], w1[2], w2[2];
#pragma unroll
        for (int h = 0; h < 2; h++) {
            const int i = lane + 32 * h;
            int off, map, dep = -1, x = 0, y = 0, z = 0, sz = 36, cum;
            if (i < IT_K) {
                off = i * 18432; map = M_WMOD + (i >> 1); x = c * 32; z = (i & 1) * 2; cum = 31104 + (i - 2) * 18432;
            } else if (i < IT_V) {
                const int k = i - IT_K;
                off = k_off(k); map = M_K; y = kvrow0 + k * kvstep; sz = 32; cum = 67968 + k * 16384;
                if (k == 8 && c < NMOD) dep = EM_WMOD;
                if (k == 10) dep = EM_WQ;
                if (k >= 12) dep = EM_K + k - 12;
            } else if (i < IT_WO) {
                const int k = i - IT_V;
                off = v_off(k); map = M_V; y = kvrow0 + k * kvstep; sz = 32; cum = 330112 + k * 16384;
                dep = EM_K + 3 + k + (k < 4);
            } else if (i < IT_GU) {
                const int k = i - IT_WO;
                off = k ? OFF_WO1 : OFF_WO0; map = M_WO; y = kvh * 256 + k * 128 + j * 16; dep = EM_V + 4 + 2 * k;
                cum = 592256 + k * 18432;
            } else if (i < IT_WD) {
                const int k = i - IT_GU;
                off = OFF_GU + k * GSTR; map = M_WG + (k & 1) + (wide ? 3 : 0);
                x = f0; y = (k >> 1) * 16; sz = wide ? 27 : 18; dep = EM_V + 5 + ((off + GSTR - 1) >> 14);
                cum = 629120 + k * 10368;
            } else {
                const int k = i - IT_WD;
                off = OFF_D + k * DSTR; map = wide ? M_WD48 : M_WD; y = f0; z = ((k + 2) % 3) * 3; sz = wide ? 36 : 24; dep = EM_V + (k ? 15 : 13);
                cum = 712064 + k * 13824;
            }
            const int stag = (KVROT && i >= IT_K && i < IT_WO) ? (((kvh * 2 + bb) * 13) & 31) * 512 + sp * (KVROT - 1) * 128 : ((c * 37) & 127) * 128;
            cum += EARLY_PF - min(max(cum - 67968, 0), EARLY_PF);
            int due = (int)((float)max(min(cum, 629120) + stag - PACE_LEAD, 0) * (128.0f / PACE_GBS));
            if (i >= IT_GU) due += TAIL_GAP + (int)((float)(min(cum, 712064) - 629120) * (128.0f / PACE_TAIL));
            if (i >= IT_WD) due += (int)((float)(cum - 712064) * (128.0f / PACE_D));
            w0[h] = off | (map << 18) | ((dep + 1) << 22) | (z << 28);
            w1[h] = y | (sz << 24);
            w2[h] = x | (due << 13);
        }
        asm volatile("bar.sync 2, 384;" ::: "memory");
        uint32_t fb = s_full;
        asm volatile("" : "+r"(fb));
        bool open = false;
#pragma unroll 1
        for (int i = first + 2; i < N_IT; i++) {
            const bool hi = i >= 32;
            const uint32_t a = __shfl_sync(0xffffffffu, hi ? w0[1] : w0[0], i);
            const uint32_t b = __shfl_sync(0xffffffffu, hi ? w1[1] : w1[0], i);
            const uint32_t x = __shfl_sync(0xffffffffu, hi ? w2[1] : w2[0], i);
            if (lane == 0) {
                const uint32_t bar = fb + i * 8;
                if (!open) {
                    const int win = i >= IT_GU + WIN_GN ? WIN_G0 : (i >= WIN_SWITCH) ? WIN_TAIL : WIN_MAIN;
                    const int dep = (a >> 22) & 63;
                    const uint32_t due = t0 + (x >> 13);
                    if (dep) mbar_wait(fb + (N_IT - 1 + dep) * 8);
                    if (i < IT_TAIL || !OPEN_WIN) {
                        if (i - win >= first) mbar_wait(bar - win * 8);
                        while ((int)(gtime32() - due) < 0) { }
                    } else {
                        const uint32_t ch = fb + (N_IT + EM_CH) * 8;
                        while (!mbar_test(bar - win * 8)) { if (mbar_test(ch)) { open = true; break; } }
                        while (!open && (int)(gtime32() - due) < 0) open = mbar_test(ch);
                    }
                }
                if (open && OPEN_WIN > 1) mbar_wait(bar - OPEN_WIN * 8);
                mbar_expect_tx(bar, (b >> 24) * 512);
                tma3d(fb - OFF_BAR + (a & 0x3ffff), &maps.m[(a >> 18) & 15], x & 0x1fff, b & 0xffffff, a >> 28, bar);
                TS(i == IT_WO, 1);
                TS(i == N_IT - 1, 2);
            }
            __syncwarp();
        }
        return;
    }

    const int g = lane >> 2, t = lane & 3, mi = lane >> 3, r = lane & 7;
    const int bat = g & 1;

    if (warp > NCW) {
        const bool first = warp == NCW + 1, active = first || c < 16;
        const int unit = first ? c : NCTA + c;
        const int rcol = (unit >> 2) * 16 + (unit & 3) * 2 + (lane & 1) + (lane & 2) * 4 + bat * DM;
        const unsigned ep = ldg_rlx1(scr + G_EPOCH);
        uint32_t xold = 0, ga = 0, gb = 0;
        if (active) xold = __ldg((const unsigned short*)xin + rcol);
        if (!first) asm volatile("bar.sync 2, 384;" ::: "memory");
        const unsigned tag = (ep + 1u) & 1u;
        unsigned side = 0;
        const int x1w = G_X1 + (unit >> 7) * 2048 + (unit & 127) * 8 + r + (lane & 8) * (HALF / 8) + (lane >> 4) * 4096;
        if (first) {
            unsigned* pr = scr + G_PROBE + c * 8;
            if (lane < 16) stg_rlx1(pr + r + (lane & 8) * (HALF / 8), 0u);
            __syncwarp();
            asm volatile("bar.arrive 2, 384;" ::: "memory");
            unsigned best0 = ~0u, best1 = ~0u, v = 0, cp = 0;
#pragma unroll 1
            for (int i = 0; i <= 2 * NPROBE; i++) {
                if (lane == 0) {
                    asm volatile("atom.relaxed.gpu.global.add.u32 %0, [%1], 1;" : "=r"(v) : "l"(pr + (i & 1) * HALF + (v >> 31)) : "memory");
                    const unsigned cn = clock(), d = cn - cp;
                    cp = cn;
                    if (i & 1) best0 = min(best0, d); else if (i) best1 = min(best1, d);
                    side = (best1 < best0) ^ (__popc(G_PROBE & 0x2C800) & 1);
                }
                if (i == 2 * NPROBE0) {
                    asm volatile("bar.sync 6, 64;" ::: "memory");
                    if (lane == 0) { sts32(sb + OFF_WMX + 116, side); mbar_arrive(s_empty + EM_SD * 8); }
                }
            }
            if (lane == 0) sts32(sb + OFF_WMX + 112, side);
            side = __shfl_sync(0xffffffffu, side, 0);
            mbar_wait(s_full + it_v(PH_V) * 8);
#pragma unroll 1
            for (int u = c; u < 144; u += NCTA) {
                unsigned* q = scr + G_PART + u * 2048 + near_half(G_PART + u * 2048, side) + lane * 4;
#pragma unroll
                for (int i = 0; i < 8; i++) stg_ph(q + i * 128);
#pragma unroll
                for (int i = 0; i < XREP; i += 2) stg_rlx1(scr + x1w + (u >> 7) * 2048 + i * 4096, 2u);
            }
            unsigned* o = scr + G_OP + kvh * 4096 + (j >> 2) * 2048 + (j & 3) * 256 + lane * 4;
            stg_ph(o); stg_ph(o + 128); stg_ph(o + HALF); stg_ph(o + HALF + 128);
            __threadfence();
            __syncwarp();
            if (lane < 8) stg_rlx1(scr + G_SIDE + c * 8 + lane, (side << 4) | tag);
            if (lane == 0) mbar_arrive(s_empty + EM_PH * 8);
        } else {
            asm volatile("bar.arrive 6, 64;" ::: "memory");
            if (TM_PF && lane < 8) asm volatile("prefetch.tensormap [%0];" ::"l"(&maps.m[lane + ((wide && lane >= M_WG) ? 3 : 0)]) : "memory");
            mbar_wait(s_empty + EM_PH * 8);
            side = __float_as_uint(ldsf(sb + OFF_WMX + 112));
        }
        if (active) {
            int it = 0;
            do {
                ga = ldg_rlx1(scr + dual_near(G_MOD, 2 * 1152 + unit * 8 + r, side));
                gb = ldg_rlx1(scr + dual_near(G_MOD, 5 * 1152 + unit * 8 + r, side));
            } while (any_lane(((ga ^ tag) | (gb ^ tag)) & 7u) && ++it < SPIN_LIMIT);
            ga >>= 16; gb >>= 16;
        }
        __syncwarp();
        if (first) {
            const int ow = G_OP + kvh * 4096 + (g >> 2) * 2048;
            const unsigned* q = scr + ow + near_half(ow, side) + (g & 3) * 256 + j * 32 + t * 8;
            mbar_wait(s_full + it_v(15) * 8);
            uint4 lo, hi;
            int it = 0;
            do { lo = ldg_pkt(q); hi = ldg_pkt(q + 4); } while (any_lane(((lo.x ^ tag) | (hi.x ^ tag)) & 7u) && ++it < SPIN_LIMIT);
            float o[8] = {untagf(lo.x), __uint_as_float(lo.y), __uint_as_float(lo.z), __uint_as_float(lo.w),
                          untagf(hi.x), __uint_as_float(hi.y), __uint_as_float(hi.z), __uint_as_float(hi.w)};
            __syncwarp();
#pragma unroll
            for (int sft = 8; sft <= 16; sft <<= 1) {
#pragma unroll
                for (int i = 0; i < 8; i++) o[i] += shx(o[i], sft);
            }
            if (lane < 8)
                sts128(sb + OFF_FR + lane * 48, pack2(o[0], o[4]), pack2(o[2], o[6]), pack2(o[1], o[5]), pack2(o[3], o[7]));
            TS(lane == 0, 10);
        }
        asm volatile("bar.sync 3, 352;" ::: "memory");
        const unsigned* q = scr + G_PART + unit * 2048 + near_half(G_PART + unit * 2048, side) + lane * 4;
        if (!active) return;
#pragma unroll 1
        for (int ph = 0; ph < 2; ph++) {
            if (ph) asm volatile("bar.sync %0, 128;" ::"r"(first ? 5 : 7) : "memory");
            spin_cycles(ph ? DELAY_D : DELAY_B);
            unsigned dur[4] = {};
            TS(ph && first && lane == 0, 18);
            const float k = reduce_unit(q, lane, tag | (ph * 4u), dur);
            xold = badd2(xold, bmul2(ga, pack2(k, 0.f))) & 0xffffu;
            ga = gb;
            if (ph) {
                if (lane < 8) ((unsigned short*)out)[rcol] = (unsigned short)xold;
            } else {
#pragma unroll
                for (int i = 0; i < XREP; i += 2) stg_rlx1(scr + x1w + i * 4096, (xold << 16) | tag);
                if (first && lane == 0) mbar_arrive(s_empty + EM_X1 * 8);
            }
            TS(first && lane == 0, 12 + 4 * ph);
        }
        if (c == 0 && first && lane == 0) stg_rlx1(scr + G_EPOCH, ep + 1u);
        return;
    }

    const int vw = warp, tid = threadIdx.x;
    const int vecw = tid * 4 - (lane & 7) * 4 + t * 8 + bat * 4;
    unsigned* ppart = scr + G_PART + (vw * 16 + t * 4 + (g >> 1)) * 2048 + c * 8 + bat * 4;
    const unsigned* const pside = scr + G_SIDE + ((vw * 16 + t * 4 + (g >> 1)) & 127) * 8;
    const int qword = dual(G_Q, bat * 4096 + c * 32 + (tid >> 3) * 4 + t), mword = dual(G_MOD, c * 64 + (tid & 63));
    const uint32_t one2 = 0x3f803f80u;

    const unsigned ep = ldg_rlx1(scr + G_EPOCH);
    if (tid < 64) {
        if (c < NMOD) { stg_rlx1(scr + mword, 2u); stg_rlx1(scr + mword + HALF, 2u); }
        stg_rlx1(scr + qword, 2u); stg_rlx1(scr + qword + HALF, 2u);
    }
    uint32_t xw0, xw1, aw0, aw1;
    {
        const int col0 = bat * DM + (vw * 4 + mi) * 16 + 2 * t;
        const uint32_t cw0 = __ldg((const unsigned*)(cin + col0)), cw1 = __ldg((const unsigned*)(cin + col0 + 8));
        xw0 = __ldg((const unsigned*)(xin + col0)); xw1 = __ldg((const unsigned*)(xin + col0 + 8));
        if (lane == 0) {
            const int lo = (c < NMOD) ? 2 : 4;
#pragma unroll 1
            for (int i = vw; i < N_IT + N_EM; i += NCW) {
                const int e = i - N_IT;
                if (i >= lo) mbar_init(s_full + i * 8, (e < 0 || e >= EM_PH) ? 1 : (e < EM_K ? NCW : (e < EM_V ? 4 : 8)));
            }
            asm volatile("fence.proxy.async.shared::cta;" ::: "memory");
        }
        __syncwarp();
        asm volatile("bar.sync 2, 384;" ::: "memory");
        float cv[4] = {bflo(cw0), bfhi(cw0), bflo(cw1), bfhi(cw1)};
#pragma unroll
        for (int i = 0; i < 4; i++) cv[i] = cv[i] * rcp(1.0f + ex2(-1.4426950408889634f * cv[i]));
        aw0 = pack2(cv[0], cv[1]); aw1 = pack2(cv[2], cv[3]);
    }
    const unsigned tag = (ep + 1u) & 1u;
    const uint32_t st1 = sb + OFF_STAT + bat * 80, st2 = st1 + 160;
    ln_stage1(xw0, xw1, st1, vw, lane);

    if (c < NMOD) {
        const uint32_t m = gemv32(sb + OFF_WMOD, sb + OFF_RED, s_full + IT_WMOD * 8, s_empty + EM_WMOD * 8, aw0, aw1, tid);
        if (tid < 64) { stg_rlx1(scr + mword, m | tag); stg_rlx1(scr + mword + HALF, m | tag); }
    } else {
        bar_consumers();
    }
    TS(tid == 0, 4);
    mbar_wait(s_empty + EM_SD * 8);
    unsigned side = __float_as_uint(ldsf(sb + OFF_WMX + 116));
    {
        uint32_t y0, y1;
        ln_stage2(ln_load(st1), xw0, xw1, y0, y1);
        uint4 a, b;
        int it = 0;
        const unsigned *pa = scr + dual_near(G_MOD, vecw, side), *pb = scr + dual_near(G_MOD, 1152 + vecw, side);
        do { a = ldg_rlx4(pa); b = ldg_rlx4(pb); }
        while (any_lane((bad4(a, tag) | bad4(b, tag)) & 7u) && ++it < SPIN_LIMIT);
        __syncwarp();
        aw0 = badd2(bmul2(y0, badd2(one2, hi2(b.x, b.y))), hi2(a.x, a.y));
        aw1 = badd2(bmul2(y1, badd2(one2, hi2(b.z, b.w))), hi2(a.z, a.w));
        TS(tid == 0, 5);
        const uint32_t q = gemv32(sb + OFF_WQ, sb + OFF_RED + 2304, s_full + IT_WQ * 8, s_empty + EM_WQ * 8, aw0, aw1, tid);
        if (tid < 64) {
            stg_rlx1(scr + qword, q | tag); stg_rlx1(scr + qword + HALF, q | tag);
            uint4 v;
            int it = 0;
            const unsigned* pq = scr + dual_near(G_Q, bb * 4096 + kvh * 256 + tid * 4, side);
            do { v = ldg_rlx4(pq); } while (any_lane(bad4(v, tag) & 7u) && ++it < SPIN_LIMIT);
            sts64(sb + OFF_QS + (vw * 4 + t) * 80 + g * 8, hi2(v.x, v.y), hi2(v.z, v.w));
        }
        bar_consumers();
        TS(tid == 0, 6);
    }
    uint32_t sc0, sc1, sh0, sh1;
    {
        uint4 d, e;
        unsigned bad;
        int it = 0;
        do {
            d = ldg_rlx4(scr + dual_near(G_MOD, 3 * 1152 + vecw, side)); e = ldg_rlx4(scr + dual_near(G_MOD, 4 * 1152 + vecw, side));
            bad = bad4(d, tag) | bad4(e, tag);
        } while (any_lane(bad & 7u) && ++it < SPIN_LIMIT);
        __syncwarp();
        sh0 = hi2(d.x, d.y); sh1 = hi2(d.z, d.w);
        sc0 = badd2(one2, hi2(e.x, e.y)); sc1 = badd2(one2, hi2(e.z, e.w));
    }
    if (vw < 8) {
        uint4 qf[4];
#pragma unroll
        for (int i = 0; i < 4; i++) qf[i] = lds128(sb + OFF_QS + r * 80 + i * 16);
        const int mt = vw & 3;
        const uint32_t rowoff = (mt * 16 + r + 8 * (mi & 1)) * 128;
        const uint32_t sw = ((mi >> 1) ^ r) << 4;
        uint32_t mx = 0xff80ff80u;
#pragma unroll 1
        for (int i = (vw >> 2); i < 16; i += 2) {
            mbar_wait(s_full + (IT_K + i) * 8);
            const uint32_t base = sb + k_off(i) + rowoff;
            float c0[4] = {}, c1[4] = {};
            uint32_t a[4];
            ldsm4(a, base + sw);               mma16816(c0, a, qf[0].x, qf[0].y);
            ldsm4(a, base + 8192 + sw);        mma16816(c1, a, qf[2].x, qf[2].y);
            ldsm4(a, base + (sw ^ 32));        mma16816(c0, a, qf[0].z, qf[0].w);
            ldsm4(a, base + 8192 + (sw ^ 32)); mma16816(c1, a, qf[2].z, qf[2].w);
            ldsm4(a, base + (sw ^ 64));        mma16816(c0, a, qf[1].x, qf[1].y);
            ldsm4(a, base + 8192 + (sw ^ 64)); mma16816(c1, a, qf[3].x, qf[3].y);
            ldsm4(a, base + (sw ^ 96));        mma16816(c0, a, qf[1].z, qf[1].w);
            ldsm4(a, base + 8192 + (sw ^ 96)); mma16816(c1, a, qf[3].z, qf[3].w);
            __syncwarp();
            if (lane == 0) mbar_arrive(s_empty + (EM_K + i) * 8);
            const float scl = 0.08838834764831845f;
            uint32_t u0 = pack2(c0[0] + c1[0], c0[1] + c1[1]), u1 = pack2(c0[2] + c1[2], c0[3] + c1[3]);
            u0 = pack2(bflo(u0) * scl, bfhi(u0) * scl); u1 = pack2(bflo(u1) * scl, bfhi(u1) * scl);
            mx = bmax2(mx, bmax2(u0, u1));
            if (t == 0) {
                const uint32_t pa = sb + OFF_S + (i * 64 + 16 * (g >> 1) + 4 * mt + bat) * 4;
                sts32(pa, u0); sts32(pa + 8, u1);
            }
            if (i == PH_K && tid < 4) stg_ph(scr + G_ML + c * 8 + (tid & 1) * 4 + (tid & 2) * (HALF / 2));
        }
#pragma unroll
        for (int o = 4; o <= 16; o <<= 1) mx = bmax2(mx, __shfl_xor_sync(0xffffffffu, mx, o));
        if (lane == 0) sts32(sb + OFF_WMX + vw * 4, mx);
    }
    bar_consumers();
    TS(tid == 0, 7);
    {
        const float L2E = 1.4426950408889634f;
        uint4 sv = make_uint4(0, 0, 0, 0);
        float m0 = 0.f, m1 = 0.f;
        if (vw < 8) {
            uint4 ma = lds128(sb + OFF_WMX), mb = lds128(sb + OFF_WMX + 16);
            const uint32_t mx = bmax2(bmax2(bmax2(ma.x, ma.y), bmax2(ma.z, ma.w)), bmax2(bmax2(mb.x, mb.y), bmax2(mb.z, mb.w)));
            m0 = bflo(mx); m1 = bfhi(mx);
            sv = lds128(sb + OFF_S + tid * 16);
            float e0 = (ex2((bflo(sv.x) - m0) * L2E) + ex2((bflo(sv.y) - m0) * L2E)) + (ex2((bflo(sv.z) - m0) * L2E) + ex2((bflo(sv.w) - m0) * L2E));
            float e1 = (ex2((bfhi(sv.x) - m1) * L2E) + ex2((bfhi(sv.y) - m1) * L2E)) + (ex2((bfhi(sv.z) - m1) * L2E) + ex2((bfhi(sv.w) - m1) * L2E));
#pragma unroll
            for (int o = 16; o > 0; o >>= 1) { e0 += shx(e0, o); e1 += shx(e1, o); }
            if (lane == 0) sts64(sb + OFF_WMX + 32 + vw * 8, __float_as_uint(e0), __float_as_uint(e1));
        }
        bar_consumers();
        if (vw == 0) {
            float l0 = 0.f, l1 = 0.f;
#pragma unroll
            for (int w = 0; w < 4; w++) {
                uint4 s = lds128(sb + OFF_WMX + 32 + w * 16);
                l0 += __uint_as_float(s.x) + __uint_as_float(s.z); l1 += __uint_as_float(s.y) + __uint_as_float(s.w);
            }
            if (tid < 4) stg_pkt(scr + G_ML + c * 8 + (tid & 1) * 4 + (tid & 2) * (HALF / 2), m0, l0, m1, l1, tag);
            {
                const bool rd = lane < 4 && lane != sp;
                uint4 v = make_uint4(rd ? 2u : tag, 0, 0, 0);
                int it = 0;
                do { ldg_pkt_if(v, scr + G_ML + near_half(G_ML, side) + (kvh * 8 + (lane & 3) * 2 + bb) * 8, (v.x ^ tag) & 7u); }
                while (any_lane((v.x ^ tag) & 7u) && ++it < SPIN_LIMIT);
                if (rd) { m0 = untagf(v.x); l0 = __uint_as_float(v.y); m1 = __uint_as_float(v.z); l1 = __uint_as_float(v.w); }
            }
            float g0 = fmaxf(m0, shx(m0, 1)), g1 = fmaxf(m1, shx(m1, 1));
            g0 = fmaxf(g0, shx(g0, 2)); g1 = fmaxf(g1, shx(g1, 2));
            l0 *= ex2((m0 - g0) * L2E); l1 *= ex2((m1 - g1) * L2E);
            l0 += shx(l0, 1); l1 += shx(l1, 1);
            l0 += shx(l0, 2); l1 += shx(l1, 2);
            if (lane == 0)
                sts128(sb + OFF_WMX + 96, __float_as_uint(g0), __float_as_uint(g1), __float_as_uint(__frcp_rn(l0)), __float_as_uint(__frcp_rn(l1)));
        }
        bar_consumers();
        if (vw < 8) {
            const uint4 gs = lds128(sb + OFF_WMX + 96);
            const float g0 = __uint_as_float(gs.x), g1 = __uint_as_float(gs.y), i0 = __uint_as_float(gs.z), i1 = __uint_as_float(gs.w);
            const uint32_t a0 = pack2(ex2((bflo(sv.x) - g0) * L2E) * i0, ex2((bflo(sv.y) - g0) * L2E) * i0);
            const uint32_t a1 = pack2(ex2((bflo(sv.z) - g0) * L2E) * i0, ex2((bflo(sv.w) - g0) * L2E) * i0);
            const uint32_t b0 = pack2(ex2((bfhi(sv.x) - g1) * L2E) * i1, ex2((bfhi(sv.y) - g1) * L2E) * i1);
            const uint32_t b1 = pack2(ex2((bfhi(sv.z) - g1) * L2E) * i1, ex2((bfhi(sv.w) - g1) * L2E) * i1);
            sts64(sb + OFF_P + tid * 8, a0, a1); sts64(sb + OFF_P + PSTR + tid * 8, b0, b1);
        }
        bar_consumers();
        TS(tid == 0, 8);
    }
    const uint32_t rsw = ((mi & 1) ^ r) << 4;
    unsigned sidew = 2u;
    if (vw < 8) {
        float c0[4] = {}, c1[4] = {};
        const uint32_t vo = (vw >> 2) * 8192 + (r + 8 * (mi >> 1)) * 128 + ((((2 * vw + (mi & 1)) & 7) ^ r) << 4);
        const uint32_t pa = sb + OFF_P + bat * PSTR + t * 32;
#pragma unroll 1
        for (int i = 0; i < 16; i++) {
            uint4 pb0 = lds128(pa + i * 128), pb1 = lds128(pa + i * 128 + 16);
            mbar_wait(s_full + it_v(i) * 8);
            const uint32_t base = sb + v_off(i) + vo;
            uint32_t a0[4], a1[4], a2[4], a3[4];
            ldsm4t(a0, base); ldsm4t(a1, base + 2048); ldsm4t(a2, base + 4096); ldsm4t(a3, base + 6144);
            mma16816(c0, a0, pb0.x, pb0.y);
            mma16816(c1, a1, pb0.z, pb0.w);
            mma16816(c0, a2, pb1.x, pb1.y);
            mma16816(c1, a3, pb1.z, pb1.w);
            __syncwarp();
            if (lane == 0) mbar_arrive(s_empty + (EM_V + i) * 8);
            if (i == SIDE_V) { mbar_wait(s_empty + EM_PH * 8); sidew = ldg_rlx1(pside); }
        }
        if (t < 2)
            stg_pkt(scr + G_OP + kvh * 4096 + (j >> 2) * 2048 + t * HALF + (j & 3) * 256 + vw * 32 + g * 4,
                    c0[0] + c1[0], c0[1] + c1[1], c0[2] + c1[2], c0[3] + c1[3], tag);
        TS(tid == 0, 9);
    } else {
        mbar_wait(s_full + it_v(SIDE_V) * 8);
        mbar_wait(s_empty + EM_PH * 8);
    }
    {
        int it = 0;
        while (any_lane((sidew ^ tag) & 7u) && ++it < SPIN_LIMIT) sidew = ldg_rlx1(pside);
        ppart += near_half(G_PART + (vw * 16 + t * 4 + (g >> 1)) * 2048, sidew >> 4);
    }
    side = __float_as_uint(ldsf(sb + OFF_WMX + 112));
    const uint32_t rrow = sb + (r + 8 * (mi >> 1)) * 128;
    uint32_t ad[3][4][4];
    {
        mbar_wait(s_full + IT_WO * 8);
#pragma unroll
        for (int mt = 0; mt < 4; mt++) ldsm4t(ad[0][mt], rrow + OFF_WO0 + vw * 2048 + (rsw ^ (mt * 32)));
        mbar_wait(s_full + (IT_WO + 1) * 8);
#pragma unroll
        for (int mt = 0; mt < 4; mt++) ldsm4t(ad[1][mt], rrow + OFF_WO1 + vw * 2048 + (rsw ^ (mt * 32)));
        asm volatile("bar.sync 3, 352;" ::: "memory");
        const uint4 fr = lds128(sb + OFF_FR + r * 48);
        float cc[4][4] = {};
#pragma unroll
        for (int mt = 0; mt < 4; mt++) mma16816(cc[mt], ad[0][mt], fr.x, fr.y);
#pragma unroll
        for (int mt = 0; mt < 4; mt++) mma16816(cc[mt], ad[1][mt], fr.z, fr.w);
        publish_partials(ppart, t, cc, tag);
        TS(tid == 0, 11);
    }
    mbar_wait(s_empty + EM_X1 * 8);
    {
        uint4 v;
        int it = 0;
        const int xw = G_X1 + (vw >> 3) * 2048 + (c & (XREP - 1)) * 4096;
        const unsigned* px = scr + xw + near_half(xw, side) + (vecw & 1023);
        do { v = ldg_rlx4(px); } while (any_lane(bad4(v, tag) & 7u) && ++it < SPIN_LIMIT);
        xw0 = hi2(v.x, v.y); xw1 = hi2(v.z, v.w);
        ln_stage1(xw0, xw1, st2, vw, lane);
        bar_consumers();
        if (tid == 0) mbar_arrive(s_empty + EM_CH * 8);
        TS(tid == 0, 13);
        uint32_t y0, y1;
        ln_stage2(ln_load(st2), xw0, xw1, y0, y1);
        aw0 = badd2(bmul2(y0, sc0), sh0); aw1 = badd2(bmul2(y1, sc1), sh1);
        const uint32_t gpitch = wide ? 96 : 64, gsw = wide ? 0 : (r >> 1) << 4;
        const uint32_t gbase = sb + OFF_GU + (mi & 1) * GSTR + (vw * 16 + r + 8 * (mi >> 1)) * gpitch;
        float cc[6][4] = {};
#pragma unroll 1
        for (int ks = 0; ks < 4; ks++) {
            const uint32_t b0 = __shfl_sync(0xffffffffu, aw0, ks * 8 + r), b1 = __shfl_sync(0xffffffffu, aw1, ks * 8 + r);
            const uint32_t ga = gbase + ks * 2 * GSTR;
            uint32_t ag[6][4];
            mbar_wait(s_full + (IT_GU + 2 * ks) * 8);
            mbar_wait(s_full + (IT_GU + 2 * ks + 1) * 8);
#pragma unroll
            for (int q = 0; q < 4; q++) ldsm4t(ag[q], ga + ((q << 4) ^ gsw));
            if (wide) { ldsm4t(ag[4], ga + 64); ldsm4t(ag[5], ga + 80); }
#pragma unroll
            for (int q = 0; q < 4; q++) mma16816(cc[q], ag[q], b0, b1);
            if (wide) { mma16816(cc[4], ag[4], b0, b1); mma16816(cc[5], ag[5], b0, b1); }
        }
        if (t == 0) {
#pragma unroll
            for (int q = 0; q < 6; q++) sts128f(sb + OFF_RED + vw * 768 + q * 128 + g * 16, cc[q]);
        }
        bar_consumers();
        TS(tid == 0, 14);
        if (tid < 192) {
            float sv[NCW];
#pragma unroll
            for (int w = 0; w < NCW; w++) sv[w] = ldsf(sb + OFF_RED + w * 768 + tid * 4);
            const float s = ((sv[0] + sv[1]) + (sv[2] + sv[3])) + ((sv[4] + sv[5]) + (sv[6] + sv[7])) + sv[8];
            const uint32_t gu = pack2(s, __shfl_down_sync(0xffffffffu, s, 2));
            const float gt = bflo(gu);
            const uint32_t hh = pack2(((gt > 0.f) ? gt : gt * 0.0f) * bfhi(gu), 0.f);
            const int rr = tid >> 2;
            if ((tid & 2) == 0)
                sts16(sb + OFF_FR + ((tid & 1) * 4 + ((rr & 7) >> 1)) * 48 + (rr >> 3) * 4 + (rr & 1) * 2, hh);
        }
    }
    {
        bar_consumers();
        const uint4 fr = lds128(sb + OFF_FR + r * 48);
        const uint2 f2 = lds64(sb + OFF_FR + r * 48 + 16);
        {
            const uint32_t db = rrow + OFF_D + ((vw / 3 + 1) % 3) * DSTR + (vw % 3) * (wide ? 6144 : 4096);
            mbar_wait(s_full + (IT_WD + (vw / 3 + 1) % 3) * 8);
#pragma unroll
            for (int ks = 0; ks < 2; ks++)
#pragma unroll
                for (int mt = 0; mt < 4; mt++) ldsm4t(ad[ks][mt], db + ks * 2048 + (rsw ^ (mt * 32)));
            if (wide) {
#pragma unroll
                for (int mt = 0; mt < 4; mt++) ldsm4t(ad[2][mt], db + 4096 + (rsw ^ (mt * 32)));
            }
        }
        float cc[4][4] = {};
#pragma unroll
        for (int mt = 0; mt < 4; mt++) mma16816(cc[mt], ad[0][mt], fr.x, fr.y);
#pragma unroll
        for (int mt = 0; mt < 4; mt++) mma16816(cc[mt], ad[1][mt], fr.z, fr.w);
        if (wide) {
#pragma unroll
            for (int mt = 0; mt < 4; mt++) mma16816(cc[mt], ad[2][mt], f2.x, f2.y);
        }
        publish_partials(ppart, t, cc, tag | 4u);
        TS(tid == 160, 15);
    }
    if (vw / 3 == c / 48) asm volatile("bar.arrive 5, 128;" ::: "memory");
    if (vw >= 6 && c < 16) asm volatile("bar.arrive 7, 128;" ::: "memory");
}

typedef CUresult (*EncodeFn)(CUtensorMap*, CUtensorMapDataType, cuuint32_t, void*, const cuuint64_t*, const cuuint64_t*,
                             const cuuint32_t*, const cuuint32_t*, CUtensorMapInterleave, CUtensorMapSwizzle,
                             CUtensorMapL2promotion, CUtensorMapFloatOOBfill);

void make_map(EncodeFn enc, CUtensorMap* m, const void* p, cuuint64_t d0, cuuint64_t d1, cuuint64_t d2,
              cuuint64_t s1, cuuint64_t s2, cuuint32_t b0, cuuint32_t b1, cuuint32_t b2, CUtensorMapSwizzle sw,
              CUtensorMapL2promotion pr = CU_TENSOR_MAP_L2_PROMOTION_L2_128B) {
    cuuint64_t dims[3] = {d0, d1, d2};
    cuuint64_t str[2] = {s1, s2};
    cuuint32_t box[3] = {b0, b1, b2};
    cuuint32_t es[3] = {1, 1, 1};
    enc(m, CU_TENSOR_MAP_DATA_TYPE_BFLOAT16, 3, const_cast<void*>(p), dims, str, box, es,
        CU_TENSOR_MAP_INTERLEAVE_NONE, sw, pr, CU_TENSOR_MAP_FLOAT_OOB_FILL_NONE);
}

}

extern "C" void kernel_launch(void* const* d_in, const int* in_sizes, int n_in, void* d_out, int out_size) {
    (void)in_sizes; (void)n_in; (void)out_size;
    void* fn = nullptr;
    cudaDriverEntryPointQueryResult qr;
    cudaGetDriverEntryPoint("cuTensorMapEncodeTiled", &fn, cudaEnableDefault, &qr);
    EncodeFn enc = (EncodeFn)fn;
    cudaFuncSetAttribute(fused_block_kernel, cudaFuncAttributeMaxDynamicSharedMemorySize, SMEM_BYTES);

    const void *x = d_in[0], *kc = d_in[1], *vc = d_in[2], *wq = d_in[3], *wo = d_in[4];
    const void *wg = d_in[6], *wu = d_in[7], *wd = d_in[8], *cc = d_in[9], *wmod = d_in[10];
    const CUtensorMapSwizzle S128 = CU_TENSOR_MAP_SWIZZLE_128B, S64 = CU_TENSOR_MAP_SWIZZLE_64B, S0 = CU_TENSOR_MAP_SWIZZLE_NONE;
    void* raw = nullptr;
    cudaGetSymbolAddress(&raw, g_raw);
    unsigned* scr = (unsigned*)(((uintptr_t)raw + 0x1fffff) & ~(uintptr_t)0x1fffff);
    Maps m;
    make_map(enc, &m.m[M_K], kc, 64, 32ull * 32768, 2, 256, 128, 64, 64, 2, S128, CU_TENSOR_MAP_L2_PROMOTION_L2_256B);
    make_map(enc, &m.m[M_V], vc, 64, 32ull * 32768, 2, 256, 128, 64, 64, 2, S128, CU_TENSOR_MAP_L2_PROMOTION_L2_256B);
    make_map(enc, &m.m[M_WMOD], wmod, 3456, 144, 4, 3456 * 2, 3456 * 2 * 144, 32, 144, 2, S64);
    make_map(enc, &m.m[M_WQ], wq, 4096, 144, 4, 4096 * 2, 4096 * 2 * 144, 32, 144, 2, S64);
    make_map(enc, &m.m[M_WG], wg, 4608, 64, 9, 4608 * 2, 4608 * 2 * 64, 32, 16, 9, S64);
    make_map(enc, &m.m[M_WU], wu, 4608, 64, 9, 4608 * 2, 4608 * 2 * 64, 32, 16, 9, S64);
    make_map(enc, &m.m[M_WG48], wg, 4608, 64, 9, 4608 * 2, 4608 * 2 * 64, 48, 16, 9, S0);
    make_map(enc, &m.m[M_WU48], wu, 4608, 64, 9, 4608 * 2, 4608 * 2 * 64, 48, 16, 9, S0);
    make_map(enc, &m.m[M_WO], wo, 64, 4096, 9, 1152, 128, 64, 16, 9, S128);
    make_map(enc, &m.m[M_WD], wd, 64, 4608, 9, 1152, 128, 64, 32, 3, S128);
    make_map(enc, &m.m[M_WD48], wd, 64, 4608, 9, 1152, 128, 64, 48, 3, S128);
    fused_block_kernel<<<NCTA, NTHR, SMEM_BYTES>>>(m, (const __nv_bfloat16*)x, (const __nv_bfloat16*)cc,
                                                   (const __nv_bfloat16*)kc, (__nv_bfloat16*)d_out, scr TUNE_ARG);
}
```

```cpp
#include <cuda_runtime.h>
#include <cuda.h>
#include <cuda_bf16.h>
#include <stdint.h>

namespace {

constexpr int DM = 576;
constexpr int NCTA = 128;
constexpr int NCW = 9;
constexpr int NTHR = (NCW + 3) * 32;
constexpr int NMOD = 108;

constexpr int WIN_MAIN = 4;
constexpr int WIN_TAIL = 3;
constexpr int PACE_GBS = 3175;
constexpr int PACE_LEAD = 19456;
constexpr int PACE_TAIL = 2900;
constexpr int TAIL_GAP = 300;
constexpr int PACE_D = 3300;
constexpr int EARLY_PF = 8192;
constexpr int DELAY_B = 300;
constexpr int DELAY_D = 150;
constexpr int XREP = 2;
constexpr int PH_K = 8;
constexpr int PH_V = 7;
constexpr int SIDE_V = 11;
constexpr int NPROBE0 = 3, NPROBE = 10;
#define SCRATCH_PAD (8  __H0__ )

constexpr int IT_WMOD = 0, IT_WQ = 2, IT_K = 4, IT_V = 20, IT_WO = 36, IT_GU = 38, IT_WD = 44, N_IT = 47;
constexpr int EM_WMOD = 0, EM_WQ = 1, EM_K = 2, EM_V = 18, EM_PH = 34, EM_X1 = 35, EM_CH = 36, EM_SD = 37, N_EM = 38;

constexpr int RING = 13 * 16384;
constexpr int OFF_WMOD = 0, OFF_WQ = 36864, OFF_K0 = 73728;
constexpr int OFF_WO0 = 194560, OFF_WO1 = 0, OFF_G = 18432, OFF_U = 73728;
constexpr int OFF_D = 129024, DSTR = 18432;
constexpr int PSTR = 2064;
constexpr int OFF_P = RING;
constexpr int OFF_S = OFF_P + 4160;
constexpr int OFF_RED = OFF_S + 4096;
constexpr int OFF_QS = OFF_RED + 6912;
constexpr int OFF_FR = OFF_QS + 640;
constexpr int OFF_STAT = OFF_FR + 384;
constexpr int OFF_WMX = OFF_STAT + 320;
constexpr int OFF_BAR = OFF_WMX + 128;
constexpr int SMEM_USED = OFF_BAR + (N_IT + N_EM) * 8;
constexpr int SMEM_BYTES = SMEM_USED + 1024;
static_assert(SMEM_BYTES <= 232448, "smem");

struct Maps { CUtensorMap m[11]; };
enum { M_K, M_V, M_WMOD, M_WQ, M_WO, M_WG, M_WU, M_WD, M_WG48, M_WU48, M_WD48 };

constexpr int HALF = 1024;
constexpr int G_PART = 0;
constexpr int G_OP = G_PART + 144 * 2048;
constexpr int G_X1 = G_OP + 16 * 4096;
constexpr int G_PROBE = G_X1 + XREP * 4096;
constexpr int G_SIDE = G_PROBE + 2048;
constexpr int G_EPOCH = G_SIDE + 1024;
constexpr int G_MOD = G_EPOCH + 1024;
constexpr int G_Q = G_MOD + 7 * 2048;
constexpr int G_ML = G_Q + 8 * 2048;
constexpr int G_WORDS = G_ML + 2048;
static_assert(G_MOD % 2048 == 0 && G_OP % 2048 == 0 && G_X1 % 2048 == 0 && G_PROBE % 2048 == 0, "halves");
static_assert(G_WORDS * 4 <= (2 << 20), "scratch must fit one 2 MB page");
__device__ __align__(128) unsigned g_raw[(2 << 20) / 4 + G_WORDS + SCRATCH_PAD];
__device__ __forceinline__ int near_half(int w, unsigned side) { return ((__popc(w & 0x2C800) ^ side) & 1) << 10; }
__device__ __forceinline__ int dual(int base, int i) { return base + i + (i & ~1023); }
__device__ __forceinline__ int dual_near(int base, int i, unsigned side) { const int w = dual(base, i); return w + near_half(w, side); }

constexpr int SPIN_LIMIT = 1 << 20;

__device__ __forceinline__ uint32_t smem_u32(const void* p) { return (uint32_t)__cvta_generic_to_shared(p); }
__device__ __forceinline__ void mbar_init(uint32_t bar, int cnt) {
    asm volatile("mbarrier.init.shared::cta.b64 [%0], %1;" ::"r"(bar), "r"(cnt) : "memory");
}
__device__ __forceinline__ void mbar_expect_tx(uint32_t bar, uint32_t bytes) {
    asm volatile("mbarrier.arrive.expect_tx.shared::cta.b64 _, [%0], %1;" ::"r"(bar), "r"(bytes) : "memory");
}
__device__ __forceinline__ void mbar_arrive(uint32_t bar) {
    asm volatile("mbarrier.arrive.shared::cta.b64 _, [%0];" ::"r"(bar) : "memory");
}
__device__ __forceinline__ void mbar_wait(uint32_t bar) {
    asm volatile("{\n.reg .pred p;\nW_%=:\nmbarrier.try_wait.parity.shared::cta.b64 p, [%0], 0;\n@!p bra W_%=;\n}"
                 ::"r"(bar) : "memory");
}
__device__ __forceinline__ bool mbar_test(uint32_t bar) {
    uint32_t ok;
    asm volatile("{\n.reg .pred p;\nmbarrier.test_wait.parity.shared::cta.b64 p, [%1], 0;\nselp.u32 %0, 1, 0, p;\n}"
                 : "=r"(ok) : "r"(bar) : "memory");
    return ok;
}
__device__ __forceinline__ uint32_t gtime32() { uint32_t t; asm volatile("mov.u32 %0, %%globaltimer_lo;" : "=r"(t)); return t; }
__device__ __forceinline__ void tma3d(uint32_t dst, const CUtensorMap* m, int x, int y, int z, uint32_t bar) {
    asm volatile("cp.async.bulk.tensor.3d.shared::cluster.global.mbarrier::complete_tx::bytes [%0], [%1, {%3, %4, %5}], [%2];"
                 ::"r"(dst), "l"(m), "r"(bar), "r"(x), "r"(y), "r"(z) : "memory");
}
__device__ __forceinline__ void bar_consumers() { asm volatile("bar.sync 1, 288;" ::: "memory"); }

__device__ __forceinline__ void ldsm4(uint32_t (&a)[4], uint32_t addr) {
    asm volatile("ldmatrix.sync.aligned.m8n8.x4.shared.b16 {%0,%1,%2,%3}, [%4];"
                 : "=r"(a[0]), "=r"(a[1]), "=r"(a[2]), "=r"(a[3]) : "r"(addr) : "memory");
}
__device__ __forceinline__ void ldsm4t(uint32_t (&a)[4], uint32_t addr) {
    asm volatile("ldmatrix.sync.aligned.m8n8.x4.trans.shared.b16 {%0,%1,%2,%3}, [%4];"
                 : "=r"(a[0]), "=r"(a[1]), "=r"(a[2]), "=r"(a[3]) : "r"(addr) : "memory");
}
__device__ __forceinline__ void mma16816(float (&c)[4], const uint32_t (&a)[4], uint32_t b0, uint32_t b1) {
    asm volatile("mma.sync.aligned.m16n8k16.row.col.f32.bf16.bf16.f32 {%0,%1,%2,%3}, {%4,%5,%6,%7}, {%8,%9}, {%0,%1,%2,%3};"
                 : "+f"(c[0]), "+f"(c[1]), "+f"(c[2]), "+f"(c[3])
                 : "r"(a[0]), "r"(a[1]), "r"(a[2]), "r"(a[3]), "r"(b0), "r"(b1));
}
__device__ __forceinline__ float ldsf(uint32_t a) { float v; asm volatile("ld.shared.f32 %0, [%1];" : "=f"(v) : "r"(a) : "memory"); return v; }
__device__ __forceinline__ uint2 lds64(uint32_t a) {
    uint2 v; asm volatile("ld.shared.v2.u32 {%0,%1}, [%2];" : "=r"(v.x), "=r"(v.y) : "r"(a) : "memory"); return v;
}
__device__ __forceinline__ uint4 lds128(uint32_t a) {
    uint4 v; asm volatile("ld.shared.v4.u32 {%0,%1,%2,%3}, [%4];" : "=r"(v.x), "=r"(v.y), "=r"(v.z), "=r"(v.w) : "r"(a) : "memory"); return v;
}
__device__ __forceinline__ void sts16(uint32_t a, uint32_t v) { asm volatile("st.shared.u16 [%0], %1;" ::"r"(a), "h"((unsigned short)v) : "memory"); }
__device__ __forceinline__ void sts32(uint32_t a, uint32_t v) { asm volatile("st.shared.u32 [%0], %1;" ::"r"(a), "r"(v) : "memory"); }
__device__ __forceinline__ void sts64(uint32_t a, uint32_t x, uint32_t y) { asm volatile("st.shared.v2.u32 [%0], {%1,%2};" ::"r"(a), "r"(x), "r"(y) : "memory"); }
__device__ __forceinline__ void sts128(uint32_t a, uint32_t x, uint32_t y, uint32_t z, uint32_t w) {
    asm volatile("st.shared.v4.u32 [%0], {%1,%2,%3,%4};" ::"r"(a), "r"(x), "r"(y), "r"(z), "r"(w) : "memory");
}
__device__ __forceinline__ void sts128f(uint32_t a, const float (&c)[4]) {
    asm volatile("st.shared.v4.f32 [%0], {%1,%2,%3,%4};" ::"r"(a), "f"(c[0]), "f"(c[1]), "f"(c[2]), "f"(c[3]) : "memory");
}
__device__ __forceinline__ unsigned ldg_rlx1(const unsigned* p) {
    unsigned v; asm volatile("ld.relaxed.gpu.global.u32 %0, [%1];" : "=r"(v) : "l"(p) : "memory"); return v;
}
__device__ __forceinline__ uint4 ldg_rlx4(const unsigned* p) {
    uint4 v; asm volatile("ld.relaxed.gpu.global.v4.u32 {%0,%1,%2,%3}, [%4];" : "=r"(v.x), "=r"(v.y), "=r"(v.z), "=r"(v.w) : "l"(p) : "memory"); return v;
}
__device__ __forceinline__ uint4 ldg_pkt(const unsigned* p) {
    uint4 v;
    asm volatile("{\n.reg .b128 t;\n.reg .b64 lo, hi;\nld.relaxed.gpu.global.b128 t, [%4];\nmov.b128 {lo, hi}, t;\n"
                 "mov.b64 {%0,%1}, lo;\nmov.b64 {%2,%3}, hi;\n}"
                 : "=r"(v.x), "=r"(v.y), "=r"(v.z), "=r"(v.w) : "l"(p) : "memory");
    return v;
}
__device__ __forceinline__ void ldg_pkt_if(uint4& v, const unsigned* a, unsigned p) {
    asm volatile("{\n.reg .pred q;\n.reg .b128 t;\n.reg .b64 lo, hi;\nsetp.ne.u32 q, %5, 0;\n"
                 "mov.b64 lo, {%0,%1};\nmov.b64 hi, {%2,%3};\nmov.b128 t, {lo, hi};\n"
                 "@q ld.relaxed.gpu.global.b128 t, [%4];\nmov.b128 {lo, hi}, t;\n"
                 "mov.b64 {%0,%1}, lo;\nmov.b64 {%2,%3}, hi;\n}"
                 : "+r"(v.x), "+r"(v.y), "+r"(v.z), "+r"(v.w) : "l"(a), "r"(p) : "memory");
}
__device__ __forceinline__ bool any_lane(unsigned x) { return __any_sync(0xffffffffu, x != 0); }
__device__ __forceinline__ void stg_pkt(unsigned* p, float a, float b, float c, float d, unsigned tag) {
    unsigned x = (__float_as_uint(a) & ~7u) | tag;
    asm volatile("{\n.reg .b128 t;\n.reg .b64 lo, hi;\nmov.b64 lo, {%1,%2};\nmov.b64 hi, {%3,%4};\nmov.b128 t, {lo, hi};\n"
                 "st.relaxed.gpu.global.b128 [%0], t;\n}"
                 ::"l"(p), "r"(x), "r"(__float_as_uint(b)), "r"(__float_as_uint(c)), "r"(__float_as_uint(d)) : "memory");
}
__device__ __forceinline__ void stg_rlx1(unsigned* p, unsigned x) { asm volatile("st.relaxed.gpu.global.u32 [%0], %1;" ::"l"(p), "r"(x) : "memory"); }
__device__ __forceinline__ unsigned bad4(const uint4& v, unsigned tag) {
    return ((v.x ^ tag) | (v.y ^ tag)) | ((v.z ^ tag) | (v.w ^ tag));
}
__device__ __forceinline__ float untagf(unsigned w) { return __uint_as_float(w & ~7u); }
__device__ __forceinline__ uint32_t pack2(float lo, float hi) {
    uint32_t r; asm("cvt.rn.bf16x2.f32 %0, %1, %2;" : "=r"(r) : "f"(hi), "f"(lo)); return r;
}
__device__ __forceinline__ float bflo(uint32_t w) { return __uint_as_float(w << 16); }
__device__ __forceinline__ float bfhi(uint32_t w) { return __uint_as_float(w & 0xffff0000u); }
__device__ __forceinline__ uint32_t hi2(uint32_t a, uint32_t b) { return __byte_perm(a, b, 0x7632); }
__device__ __forceinline__ uint32_t badd2(uint32_t a, uint32_t b) { uint32_t r; asm("add.rn.bf16x2 %0, %1, %2;" : "=r"(r) : "r"(a), "r"(b)); return r; }
__device__ __forceinline__ uint32_t bsub2(uint32_t a, uint32_t b) { uint32_t r; asm("sub.rn.bf16x2 %0, %1, %2;" : "=r"(r) : "r"(a), "r"(b)); return r; }
__device__ __forceinline__ uint32_t bmul2(uint32_t a, uint32_t b) { uint32_t r; asm("mul.rn.bf16x2 %0, %1, %2;" : "=r"(r) : "r"(a), "r"(b)); return r; }
__device__ __forceinline__ uint32_t bmax2(uint32_t a, uint32_t b) { uint32_t r; asm("max.bf16x2 %0, %1, %2;" : "=r"(r) : "r"(a), "r"(b)); return r; }
__device__ __forceinline__ float ex2(float x) { float r; asm("ex2.approx.ftz.f32 %0, %1;" : "=f"(r) : "f"(x)); return r; }
__device__ __forceinline__ float rcp(float x) { float r; asm("rcp.approx.ftz.f32 %0, %1;" : "=f"(r) : "f"(x)); return r; }
__device__ __forceinline__ float fsqrt(float x) { float r; asm("sqrt.approx.ftz.f32 %0, %1;" : "=f"(r) : "f"(x)); return r; }
__device__ __forceinline__ float shx(float v, int m) { return __shfl_xor_sync(0xffffffffu, v, m); }

__device__ __forceinline__ uint32_t k_off(int i) { return i < 8 ? OFF_K0 + i * 16384 : (i - 8) * 16384; }
__device__ __forceinline__ uint32_t v_off(int i) { return i < 5 ? (8 + i) * 16384 : (i - 5) * 16384; }

__device__ __forceinline__ void stg_ph(unsigned* p) { stg_pkt(p, 0.f, 0.f, 0.f, 0.f, 2u); }

__device__ __forceinline__ void ln_stage1(uint32_t xw0, uint32_t xw1, uint32_t st, int vw, int lane) {
    const float piv = __shfl_sync(0xffffffffu, bflo(xw0), lane & 4);
    const float d0 = bflo(xw0) - piv, d1 = bfhi(xw0) - piv, d2 = bflo(xw1) - piv, d3 = bfhi(xw1) - piv;
    float s1 = (d0 + d1) + (d2 + d3), s2 = (d0 * d0 + d1 * d1) + (d2 * d2 + d3 * d3);
    s1 += shx(s1, 1); s2 += shx(s2, 1);
    s1 += shx(s1, 2); s2 += shx(s2, 2);
    s1 += shx(s1, 8); s2 += shx(s2, 8);
    s1 += shx(s1, 16); s2 += shx(s2, 16);
    if ((lane & 27) == 0)
        sts64(st + vw * 8, __float_as_uint(piv + s1 * (1.0f / 64.0f)), __float_as_uint(s2 - s1 * s1 * (1.0f / 64.0f)));
}
struct LnStat { uint4 a, b, c, d; uint2 e; };
__device__ __forceinline__ LnStat ln_load(uint32_t st) {
    LnStat s; s.a = lds128(st); s.b = lds128(st + 16); s.c = lds128(st + 32); s.d = lds128(st + 48); s.e = lds64(st + 64);
    return s;
}
__device__ __forceinline__ void ln_stage2(const LnStat& s, uint32_t xw0, uint32_t xw1, uint32_t& y0, uint32_t& y1) {
    const float m[9] = {__uint_as_float(s.a.x), __uint_as_float(s.a.z), __uint_as_float(s.b.x), __uint_as_float(s.b.z),
                        __uint_as_float(s.c.x), __uint_as_float(s.c.z), __uint_as_float(s.d.x), __uint_as_float(s.d.z), __uint_as_float(s.e.x)};
    const float mean = (((m[0] + m[1]) + (m[2] + m[3])) + ((m[4] + m[5]) + (m[6] + m[7])) + m[8]) * (1.0f / NCW);
    const float m2 = ((__uint_as_float(s.a.y) + __uint_as_float(s.a.w)) + (__uint_as_float(s.b.y) + __uint_as_float(s.b.w))) +
                     ((__uint_as_float(s.c.y) + __uint_as_float(s.c.w)) + (__uint_as_float(s.d.y) + __uint_as_float(s.d.w))) + __uint_as_float(s.e.y);
    float d[9];
#pragma unroll
    for (int w = 0; w < 9; w++) d[w] = m[w] - mean;
    const float acc = (d[0] * d[0] + d[1] * d[1] + d[2] * d[2]) + (d[3] * d[3] + d[4] * d[4] + d[5] * d[5]) + (d[6] * d[6] + d[7] * d[7] + d[8] * d[8]);
    const float var = (m2 + 64.0f * acc) * (1.0f / DM);
    const uint32_t mv = pack2(mean, var);
    const float ve = bflo(pack2(bfhi(mv) + 1e-5f, 0.f));
    const float rinv = rcp(bflo(pack2(fsqrt(ve), 0.f)));
    const uint32_t mm = __byte_perm(mv, mv, 0x1010);
    const uint32_t e0 = bsub2(xw0, mm), e1 = bsub2(xw1, mm);
    y0 = pack2(bflo(e0) * rinv, bfhi(e0) * rinv); y1 = pack2(bflo(e1) * rinv, bfhi(e1) * rinv);
}
__device__ __forceinline__ void make_bfrags(uint32_t (&bf)[4][2], uint32_t aw0, uint32_t aw1, int r) {
#pragma unroll
    for (int ks = 0; ks < 4; ks++) {
        bf[ks][0] = __shfl_sync(0xffffffffu, aw0, ks * 8 + r);
        bf[ks][1] = __shfl_sync(0xffffffffu, aw1, ks * 8 + r);
    }
}
__device__ __forceinline__ uint32_t gemv32(uint32_t s_w, uint32_t red, uint32_t fullbar, uint32_t emptybar,
                                           uint32_t aw0, uint32_t aw1, int tid) {
    const int vw = tid >> 5, lane = tid & 31, g = lane >> 2, t = lane & 3, mi = lane >> 3, r = lane & 7;
    uint32_t bf[4][2];
    make_bfrags(bf, aw0, aw1, r);
    if (vw <= 4) mbar_wait(fullbar);
    if (vw >= 4) mbar_wait(fullbar + 8);
    float cc[2][4] = {};
    const uint32_t abase = s_w + (vw * 64 + r + 8 * (mi >> 1)) * 64;
    const uint32_t sw = ((mi & 1) ^ (r >> 1)) << 4;
#pragma unroll
    for (int ks = 0; ks < 4; ks++) {
#pragma unroll
        for (int mt = 0; mt < 2; mt++) {
            uint32_t a[4];
            ldsm4t(a, abase + ks * 1024 + (sw ^ (mt * 32)));
            mma16816(cc[mt], a, bf[ks][0], bf[ks][1]);
        }
    }
    if (t == 0) { sts128f(red + vw * 256 + g * 16, cc[0]); sts128f(red + vw * 256 + 128 + g * 16, cc[1]); }
    __syncwarp();
    if (lane == 0) mbar_arrive(emptybar);
    bar_consumers();
    float s = 0.f;
    if (tid < 64) {
        const uint32_t ra = red + ((tid & 58) | ((tid & 1) << 2) | ((tid >> 2) & 1)) * 4;
#pragma unroll
        for (int w = 0; w < NCW; w++) s += ldsf(ra + w * 256);
    }
    return pack2(0.f, s);
}
__device__ __forceinline__ void publish_partials(unsigned* q, int t, const float (&cc)[4][4], unsigned tag) {
    float v[4];
#pragma unroll
    for (int i = 0; i < 4; i++) {
        const float lo = (t & 1) ? cc[1][i] : cc[0][i], hi = (t & 1) ? cc[3][i] : cc[2][i];
        v[i] = (t & 2) ? hi : lo;
    }
    stg_pkt(q, v[0], v[1], v[2], v[3], tag);
}
__device__ __forceinline__ void spin_cycles(unsigned n) {
    const unsigned c0 = clock();
    while ((unsigned)clock() - c0 < n) { }
}
__device__ __forceinline__ float reduce_unit(const unsigned* q, int lane, unsigned tag) {
    uint4 v[8];
#pragma unroll
    for (int i = 0; i < 8; i++) v[i] = ldg_pkt(q + i * 128);
    int it = 0;
    while (true) {
        unsigned bad = 0;
#pragma unroll
        for (int i = 0; i < 8; i += 2) bad |= (v[i].x ^ tag) | (v[i + 1].x ^ tag);
        const bool more = any_lane(bad & 7u);
        if (!more || ++it >= SPIN_LIMIT) break;
#pragma unroll
        for (int i = 0; i < 8; i++) ldg_pkt_if(v[i], q + i * 128, (v[i].x ^ tag) & 7u);
    }
    float s0 = 0.f, s1 = 0.f, s2 = 0.f, s3 = 0.f, u0 = 0.f, u1 = 0.f, u2 = 0.f, u3 = 0.f;
#pragma unroll
    for (int i = 0; i < 8; i += 2) {
        s0 += untagf(v[i].x); s1 += __uint_as_float(v[i].y); s2 += __uint_as_float(v[i].z); s3 += __uint_as_float(v[i].w);
        u0 += untagf(v[i + 1].x); u1 += __uint_as_float(v[i + 1].y); u2 += __uint_as_float(v[i + 1].z); u3 += __uint_as_float(v[i + 1].w);
    }
    s0 += u0; s1 += u1; s2 += u2; s3 += u3;
    __syncwarp();
    const bool h8 = lane & 2, bat = lane & 4;
    const float k0 = (h8 ? s2 : s0) + shx(h8 ? s0 : s2, 2);
    const float k1 = (h8 ? s3 : s1) + shx(h8 ? s1 : s3, 2);
    float k = (bat ? k1 : k0) + shx(bat ? k0 : k1, 4);
    k += shx(k, 8);
    k += shx(k, 16);
    return k;
}

__global__ void __launch_bounds__(NTHR, 1)
fused_block_kernel(const __grid_constant__ Maps maps, const __nv_bfloat16* __restrict__ xin,
                   const __nv_bfloat16* __restrict__ cin, const __nv_bfloat16* __restrict__ kcache,
                   __nv_bfloat16* __restrict__ out, unsigned* const scr) {
    extern __shared__ unsigned char smem_raw[];
    const int c = blockIdx.x;
    const int kvh = c >> 3, j = c & 7, bb = j & 1, sp = j >> 1;
    const bool wide = j >= 6;
    const int f0 = kvh * 288 + (wide ? 48 * j - 96 : 32 * j);
    const int kvrow0 = (bb * 16 + kvh) * 32768 + 28672 + sp * 64;
    const int kvstep = 256;
    if (threadIdx.x == 0)
        asm volatile("cp.async.bulk.prefetch.L2.global [%0], %1;" ::"l"((const char*)kcache + (size_t)kvrow0 * 256), "r"(EARLY_PF) : "memory");
    const uint32_t sb = (smem_u32(smem_raw) + 1023u) & ~1023u;
    const int warp = threadIdx.x >> 5, lane = threadIdx.x & 31;
    const uint32_t s_full = sb + OFF_BAR, s_empty = s_full + N_IT * 8;

    if (warp == NCW) {
        const uint32_t t0 = gtime32();
        const int first = (c < NMOD) ? 0 : 2;
        if (lane == 0) {
#pragma unroll
            for (int i = 0; i < 2; i++) mbar_init(s_full + (first + i) * 8, 1);
            asm volatile("fence.proxy.async.shared::cta;" ::: "memory");
#pragma unroll
            for (int i = 0; i < 2; i++) {
                const uint32_t bar = s_full + (first + i) * 8;
                mbar_expect_tx(bar, 18432);
                tma3d(sb + (first + i) * 18432, &maps.m[M_WMOD + (first >> 1)], c * 32, 0, i * 2, bar);
            }
        }
        __syncwarp();
        uint32_t w0[2], w1[2], w2[2];
#pragma unroll
        for (int h = 0; h < 2; h++) {
            const int i = lane + 32 * h;
            int off, map, dep = -1, x = 0, y = 0, z = 0, sz = 36, cum;
            if (i < IT_K) {
                off = i * 18432; map = M_WMOD + (i >> 1); x = c * 32; z = (i & 1) * 2; cum = 31104 + (i - 2) * 18432;
            } else if (i < IT_V) {
                const int k = i - IT_K;
                off = k_off(k); map = M_K; y = kvrow0 + k * kvstep; sz = 32; cum = 67968 + k * 16384;
                if (k == 8 && c < NMOD) dep = EM_WMOD;
                if (k == 10) dep = EM_WQ;
                if (k >= 12) dep = EM_K + k - 12;
            } else if (i < IT_WO) {
                const int k = i - IT_V;
                off = v_off(k); map = M_V; y = kvrow0 + k * kvstep; sz = 32; cum = 330112 + k * 16384;
                dep = EM_K + 3 + k + (k < 4);
            } else if (i < IT_GU) {
                const int k = i - IT_WO;
                off = k ? OFF_WO1 : OFF_WO0; map = M_WO; y = kvh * 256 + k * 128 + j * 16; dep = EM_V + 4 + 2 * k;
                cum = 592256 + k * 18432;
            } else if (i < IT_WD) {
                const int k = i - IT_GU;
                sz = wide ? 36 : 24;
                off = ((k & 1) ? OFF_U : OFF_G) + (k >> 1) * sz * 512; map = M_WG + (k & 1) + (wide ? 3 : 0);
                x = f0; y = (k >> 1) * 192; dep = EM_V + 5 + ((off + sz * 512 - 1) >> 14);
                cum = 629120 + k * 13824;
            } else {
                const int k = i - IT_WD;
                off = OFF_D + k * DSTR; map = wide ? M_WD48 : M_WD; y = f0; z = ((k + 2) % 3) * 3; sz = wide ? 36 : 24; dep = EM_V + (k ? 15 : 13);
                cum = 712064 + k * 13824;
            }
            const int stag = (i >= IT_K && i < IT_WO) ? (((kvh * 2 + bb) * 13) & 31) * 512 : ((c * 37) & 127) * 128;
            cum += EARLY_PF - min(max(cum - 67968, 0), EARLY_PF);
            int due = (int)((float)max(min(cum, 629120) + stag - PACE_LEAD, 0) * (128.0f / PACE_GBS));
            if (i >= IT_GU) due += TAIL_GAP + (int)((float)(min(cum, 712064) - 629120) * (128.0f / PACE_TAIL));
            if (i >= IT_WD) due += (int)((float)(cum - 712064) * (128.0f / PACE_D));
            w0[h] = off | (map << 18) | ((dep + 1) << 22) | (z << 28);
            w1[h] = y | (sz << 24);
            w2[h] = x | (due << 13);
        }
        asm volatile("bar.sync 2, 384;" ::: "memory");
        uint32_t fb = s_full;
        asm volatile("" : "+r"(fb));
        bool open = false;
#pragma unroll 1
        for (int i = first + 2; i < N_IT; i++) {
            const bool hi = i >= 32;
            const uint32_t a = __shfl_sync(0xffffffffu, hi ? w0[1] : w0[0], i);
            const uint32_t b = __shfl_sync(0xffffffffu, hi ? w1[1] : w1[0], i);
            const uint32_t x = __shfl_sync(0xffffffffu, hi ? w2[1] : w2[0], i);
            if (lane == 0) {
                const uint32_t bar = fb + i * 8;
                if (!open) {
                    const int win = (i >= IT_GU) ? WIN_TAIL : WIN_MAIN;
                    const int dep = (a >> 22) & 63;
                    const uint32_t due = t0 + (x >> 13);
                    if (dep) mbar_wait(fb + (N_IT - 1 + dep) * 8);
                    if (i < IT_GU) {
                        if (i - win >= first) mbar_wait(bar - win * 8);
                        while ((int)(gtime32() - due) < 0) { }
                    } else {
                        const uint32_t ch = fb + (N_IT + EM_CH) * 8;
                        while (!mbar_test(bar - win * 8)) { if (mbar_test(ch)) { open = true; break; } }
                        while (!open && (int)(gtime32() - due) < 0) open = mbar_test(ch);
                    }
                }
                mbar_expect_tx(bar, (b >> 24) * 512);
                tma3d(fb - OFF_BAR + (a & 0x3ffff), &maps.m[(a >> 18) & 15], x & 0x1fff, b & 0xffffff, a >> 28, bar);
            }
            __syncwarp();
        }
        return;
    }

    const int g = lane >> 2, t = lane & 3, mi = lane >> 3, r = lane & 7;
    const int bat = g & 1;

    if (warp > NCW) {
        const bool first = warp == NCW + 1, active = first || c < 16;
        const int unit = first ? c : NCTA + c;
        const int rcol = (unit >> 2) * 16 + (unit & 3) * 2 + (lane & 1) + (lane & 2) * 4 + bat * DM;
        const unsigned ep = ldg_rlx1(scr + G_EPOCH);
        uint32_t xold = 0, ga = 0, gb = 0;
        if (active) xold = __ldg((const unsigned short*)xin + rcol);
        if (!first) asm volatile("bar.sync 2, 384;" ::: "memory");
        const unsigned tag = (ep + 1u) & 1u;
        unsigned side = 0;
        const int x1w = G_X1 + (unit >> 7) * 2048 + (unit & 127) * 8 + r + (lane & 8) * (HALF / 8) + (lane >> 4) * 4096;
        if (first) {
            unsigned* pr = scr + G_PROBE + c * 8;
            if (lane < 16) stg_rlx1(pr + r + (lane & 8) * (HALF / 8), 0u);
            __syncwarp();
            asm volatile("bar.arrive 2, 384;" ::: "memory");
            unsigned best0 = ~0u, best1 = ~0u, v = 0, cp = 0;
#pragma unroll 1
            for (int i = 0; i <= 2 * NPROBE; i++) {
                if (lane == 0) {
                    asm volatile("atom.relaxed.gpu.global.add.u32 %0, [%1], 1;" : "=r"(v) : "l"(pr + (i & 1) * HALF + (v >> 31)) : "memory");
                    const unsigned cn = clock(), d = cn - cp;
                    cp = cn;
                    if (i & 1) best0 = min(best0, d); else if (i) best1 = min(best1, d);
                    side = (best1 < best0) ^ (__popc(G_PROBE & 0x2C800) & 1);
                }
                if (i == 2 * NPROBE0) {
                    asm volatile("bar.sync 6, 64;" ::: "memory");
                    if (lane == 0) { sts32(sb + OFF_WMX + 116, side); mbar_arrive(s_empty + EM_SD * 8); }
                }
            }
            if (lane == 0) sts32(sb + OFF_WMX + 112, side);
            side = __shfl_sync(0xffffffffu, side, 0);
            mbar_wait(s_full + (IT_V + PH_V) * 8);
#pragma unroll 1
            for (int u = c; u < 144; u += NCTA) {
                unsigned* q = scr + G_PART + u * 2048 + near_half(G_PART + u * 2048, side) + lane * 4;
#pragma unroll
                for (int i = 0; i < 8; i++) stg_ph(q + i * 128);
#pragma unroll
                for (int i = 0; i < XREP; i += 2) stg_rlx1(scr + x1w + (u >> 7) * 2048 + i * 4096, 2u);
            }
            unsigned* o = scr + G_OP + kvh * 4096 + (j >> 2) * 2048 + (j & 3) * 256 + lane * 4;
            stg_ph(o); stg_ph(o + 128); stg_ph(o + HALF); stg_ph(o + HALF + 128);
            __threadfence();
            __syncwarp();
            if (lane < 8) stg_rlx1(scr + G_SIDE + c * 8 + lane, (side << 4) | tag);
            if (lane == 0) mbar_arrive(s_empty + EM_PH * 8);
        } else {
            asm volatile("bar.arrive 6, 64;" ::: "memory");
            if (lane < 8) asm volatile("prefetch.tensormap [%0];" ::"l"(&maps.m[lane + ((wide && lane >= M_WG) ? 3 : 0)]) : "memory");
            mbar_wait(s_empty + EM_PH * 8);
            side = __float_as_uint(ldsf(sb + OFF_WMX + 112));
        }
        if (active) {
            int it = 0;
            do {
                ga = ldg_rlx1(scr + dual_near(G_MOD, 2 * 1152 + unit * 8 + r, side));
                gb = ldg_rlx1(scr + dual_near(G_MOD, 5 * 1152 + unit * 8 + r, side));
            } while (any_lane(((ga ^ tag) | (gb ^ tag)) & 7u) && ++it < SPIN_LIMIT);
            ga >>= 16; gb >>= 16;
        }
        __syncwarp();
        if (first) {
            const int ow = G_OP + kvh * 4096 + (g >> 2) * 2048;
            const unsigned* q = scr + ow + near_half(ow, side) + (g & 3) * 256 + j * 32 + t * 8;
            mbar_wait(s_full + (IT_V + 15) * 8);
            uint4 lo, hi;
            int it = 0;
            do { lo = ldg_pkt(q); hi = ldg_pkt(q + 4); } while (any_lane(((lo.x ^ tag) | (hi.x ^ tag)) & 7u) && ++it < SPIN_LIMIT);
            float o[8] = {untagf(lo.x), __uint_as_float(lo.y), __uint_as_float(lo.z), __uint_as_float(lo.w),
                          untagf(hi.x), __uint_as_float(hi.y), __uint_as_float(hi.z), __uint_as_float(hi.w)};
            __syncwarp();
#pragma unroll
            for (int sft = 8; sft <= 16; sft <<= 1) {
#pragma unroll
                for (int i = 0; i < 8; i++) o[i] += shx(o[i], sft);
            }
            if (lane < 8)
                sts128(sb + OFF_FR + lane * 48, pack2(o[0], o[4]), pack2(o[2], o[6]), pack2(o[1], o[5]), pack2(o[3], o[7]));
        }
        asm volatile("bar.sync 3, 352;" ::: "memory");
        const unsigned* q = scr + G_PART + unit * 2048 + near_half(G_PART + unit * 2048, side) + lane * 4;
        if (!active) return;
#pragma unroll 1
        for (int ph = 0; ph < 2; ph++) {
            if (ph) asm volatile("bar.sync %0, 128;" ::"r"(first ? 5 : 7) : "memory");
            spin_cycles(ph ? DELAY_D : DELAY_B);
            const float k = reduce_unit(q, lane, tag | (ph * 4u));
            xold = badd2(xold, bmul2(ga, pack2(k, 0.f))) & 0xffffu;
            ga = gb;
            if (ph) {
                if (lane < 8) ((unsigned short*)out)[rcol] = (unsigned short)xold;
            } else {
#pragma unroll
                for (int i = 0; i < XREP; i += 2) stg_rlx1(scr + x1w + i * 4096, (xold << 16) | tag);
                if (first && lane == 0) mbar_arrive(s_empty + EM_X1 * 8);
            }
        }
        if (c == 0 && first && lane == 0) stg_rlx1(scr + G_EPOCH, ep + 1u);
        return;
    }

    const int vw = warp, tid = threadIdx.x;
    const int vecw = tid * 4 - (lane & 7) * 4 + t * 8 + bat * 4;
    unsigned* ppart = scr + G_PART + (vw * 16 + t * 4 + (g >> 1)) * 2048 + c * 8 + bat * 4;
    const unsigned* const pside = scr + G_SIDE + ((vw * 16 + t * 4 + (g >> 1)) & 127) * 8;
    const int qword = dual(G_Q, bat * 4096 + c * 32 + (tid >> 3) * 4 + t), mword = dual(G_MOD, c * 64 + (tid & 63));
    const uint32_t one2 = 0x3f803f80u;

    const unsigned ep = ldg_rlx1(scr + G_EPOCH);
    if (tid < 64) {
        if (c < NMOD) { stg_rlx1(scr + mword, 2u); stg_rlx1(scr + mword + HALF, 2u); }
        stg_rlx1(scr + qword, 2u); stg_rlx1(scr + qword + HALF, 2u);
    }
    uint32_t xw0, xw1, aw0, aw1;
    {
        const int col0 = bat * DM + (vw * 4 + mi) * 16 + 2 * t;
        const uint32_t cw0 = __ldg((const unsigned*)(cin + col0)), cw1 = __ldg((const unsigned*)(cin + col0 + 8));
        xw0 = __ldg((const unsigned*)(xin + col0)); xw1 = __ldg((const unsigned*)(xin + col0 + 8));
        if (lane == 0) {
            const int lo = (c < NMOD) ? 2 : 4;
#pragma unroll 1
            for (int i = vw; i < N_IT + N_EM; i += NCW) {
                const int e = i - N_IT;
                if (i >= lo) mbar_init(s_full + i * 8, (e < 0 || e >= EM_PH) ? 1 : (e < EM_K ? NCW : (e < EM_V ? 4 : 8)));
            }
            asm volatile("fence.proxy.async.shared::cta;" ::: "memory");
        }
        __syncwarp();
        asm volatile("bar.sync 2, 384;" ::: "memory");
        float cv[4] = {bflo(cw0), bfhi(cw0), bflo(cw1), bfhi(cw1)};
#pragma unroll
        for (int i = 0; i < 4; i++) cv[i] = cv[i] * rcp(1.0f + ex2(-1.4426950408889634f * cv[i]));
        aw0 = pack2(cv[0], cv[1]); aw1 = pack2(cv[2], cv[3]);
    }
    const unsigned tag = (ep + 1u) & 1u;
    const uint32_t st1 = sb + OFF_STAT + bat * 80, st2 = st1 + 160;
    ln_stage1(xw0, xw1, st1, vw, lane);

    if (c < NMOD) {
        const uint32_t m = gemv32(sb + OFF_WMOD, sb + OFF_RED, s_full + IT_WMOD * 8, s_empty + EM_WMOD * 8, aw0, aw1, tid);
        if (tid < 64) { stg_rlx1(scr + mword, m | tag); stg_rlx1(scr + mword + HALF, m | tag); }
    } else {
        bar_consumers();
    }
    mbar_wait(s_empty + EM_SD * 8);
    unsigned side = __float_as_uint(ldsf(sb + OFF_WMX + 116));
    {
        uint32_t y0, y1;
        ln_stage2(ln_load(st1), xw0, xw1, y0, y1);
        uint4 a, b;
        int it = 0;
        const unsigned *pa = scr + dual_near(G_MOD, vecw, side), *pb = scr + dual_near(G_MOD, 1152 + vecw, side);
        do { a = ldg_rlx4(pa); b = ldg_rlx4(pb); }
        while (any_lane((bad4(a, tag) | bad4(b, tag)) & 7u) && ++it < SPIN_LIMIT);
        __syncwarp();
        aw0 = badd2(bmul2(y0, badd2(one2, hi2(b.x, b.y))), hi2(a.x, a.y));
        aw1 = badd2(bmul2(y1, badd2(one2, hi2(b.z, b.w))), hi2(a.z, a.w));
        const uint32_t q = gemv32(sb + OFF_WQ, sb + OFF_RED + 2304, s_full + IT_WQ * 8, s_empty + EM_WQ * 8, aw0, aw1, tid);
        if (tid < 64) {
            stg_rlx1(scr + qword, q | tag); stg_rlx1(scr + qword + HALF, q | tag);
            uint4 v;
            int it = 0;
            const unsigned* pq = scr + dual_near(G_Q, bb * 4096 + kvh * 256 + tid * 4, side);
            do { v = ldg_rlx4(pq); } while (any_lane(bad4(v, tag) & 7u) && ++it < SPIN_LIMIT);
            sts64(sb + OFF_QS + (vw * 4 + t) * 80 + g * 8, hi2(v.x, v.y), hi2(v.z, v.w));
        }
        bar_consumers();
    }
    uint32_t sc0, sc1, sh0, sh1;
    {
        uint4 d, e;
        unsigned bad;
        int it = 0;
        do {
            d = ldg_rlx4(scr + dual_near(G_MOD, 3 * 1152 + vecw, side)); e = ldg_rlx4(scr + dual_near(G_MOD, 4 * 1152 + vecw, side));
            bad = bad4(d, tag) | bad4(e, tag);
        } while (any_lane(bad & 7u) && ++it < SPIN_LIMIT);
        __syncwarp();
        sh0 = hi2(d.x, d.y); sh1 = hi2(d.z, d.w);
        sc0 = badd2(one2, hi2(e.x, e.y)); sc1 = badd2(one2, hi2(e.z, e.w));
    }
    if (vw < 8) {
        uint4 qf[4];
#pragma unroll
        for (int i = 0; i < 4; i++) qf[i] = lds128(sb + OFF_QS + r * 80 + i * 16);
        const int mt = vw & 3;
        const uint32_t rowoff = (mt * 16 + r + 8 * (mi & 1)) * 128;
        const uint32_t sw = ((mi >> 1) ^ r) << 4;
        uint32_t mx = 0xff80ff80u;
#pragma unroll 1
        for (int i = (vw >> 2); i < 16; i += 2) {
            mbar_wait(s_full + (IT_K + i) * 8);
            const uint32_t base = sb + k_off(i) + rowoff;
            float c0[4] = {}, c1[4] = {};
            uint32_t a[4];
            ldsm4(a, base + sw);               mma16816(c0, a, qf[0].x, qf[0].y);
            ldsm4(a, base + 8192 + sw);        mma16816(c1, a, qf[2].x, qf[2].y);
            ldsm4(a, base + (sw ^ 32));        mma16816(c0, a, qf[0].z, qf[0].w);
            ldsm4(a, base + 8192 + (sw ^ 32)); mma16816(c1, a, qf[2].z, qf[2].w);
            ldsm4(a, base + (sw ^ 64));        mma16816(c0, a, qf[1].x, qf[1].y);
            ldsm4(a, base + 8192 + (sw ^ 64)); mma16816(c1, a, qf[3].x, qf[3].y);
            ldsm4(a, base + (sw ^ 96));        mma16816(c0, a, qf[1].z, qf[1].w);
            ldsm4(a, base + 8192 + (sw ^ 96)); mma16816(c1, a, qf[3].z, qf[3].w);
            __syncwarp();
            if (lane == 0) mbar_arrive(s_empty + (EM_K + i) * 8);
            const float scl = 0.08838834764831845f;
            uint32_t u0 = pack2(c0[0] + c1[0], c0[1] + c1[1]), u1 = pack2(c0[2] + c1[2], c0[3] + c1[3]);
            u0 = pack2(bflo(u0) * scl, bfhi(u0) * scl); u1 = pack2(bflo(u1) * scl, bfhi(u1) * scl);
            mx = bmax2(mx, bmax2(u0, u1));
            if (t == 0) {
                const uint32_t pa = sb + OFF_S + (i * 64 + 16 * (g >> 1) + 4 * mt + bat) * 4;
                sts32(pa, u0); sts32(pa + 8, u1);
            }
            if (i == PH_K && tid < 4) stg_ph(scr + G_ML + c * 8 + (tid & 1) * 4 + (tid & 2) * (HALF / 2));
        }
#pragma unroll
        for (int o = 4; o <= 16; o <<= 1) mx = bmax2(mx, __shfl_xor_sync(0xffffffffu, mx, o));
        if (lane == 0) sts32(sb + OFF_WMX + vw * 4, mx);
    }
    bar_consumers();
    {
        const float L2E = 1.4426950408889634f;
        uint4 sv = make_uint4(0, 0, 0, 0);
        float m0 = 0.f, m1 = 0.f;
        if (vw < 8) {
            uint4 ma = lds128(sb + OFF_WMX), mb = lds128(sb + OFF_WMX + 16);
            const uint32_t mx = bmax2(bmax2(bmax2(ma.x, ma.y), bmax2(ma.z, ma.w)), bmax2(bmax2(mb.x, mb.y), bmax2(mb.z, mb.w)));
            m0 = bflo(mx); m1 = bfhi(mx);
            sv = lds128(sb + OFF_S + tid * 16);
            float e0 = (ex2((bflo(sv.x) - m0) * L2E) + ex2((bflo(sv.y) - m0) * L2E)) + (ex2((bflo(sv.z) - m0) * L2E) + ex2((bflo(sv.w) - m0) * L2E));
            float e1 = (ex2((bfhi(sv.x) - m1) * L2E) + ex2((bfhi(sv.y) - m1) * L2E)) + (ex2((bfhi(sv.z) - m1) * L2E) + ex2((bfhi(sv.w) - m1) * L2E));
#pragma unroll
            for (int o = 16; o > 0; o >>= 1) { e0 += shx(e0, o); e1 += shx(e1, o); }
            if (lane == 0) sts64(sb + OFF_WMX + 32 + vw * 8, __float_as_uint(e0), __float_as_uint(e1));
        }
        bar_consumers();
        if (vw == 0) {
            float l0 = 0.f, l1 = 0.f;
#pragma unroll
            for (int w = 0; w < 4; w++) {
                uint4 s = lds128(sb + OFF_WMX + 32 + w * 16);
                l0 += __uint_as_float(s.x) + __uint_as_float(s.z); l1 += __uint_as_float(s.y) + __uint_as_float(s.w);
            }
            if (tid < 4) stg_pkt(scr + G_ML + c * 8 + (tid & 1) * 4 + (tid & 2) * (HALF / 2), m0, l0, m1, l1, tag);
            {
                const bool rd = lane < 4 && lane != sp;
                uint4 v = make_uint4(rd ? 2u : tag, 0, 0, 0);
                int it = 0;
                do { ldg_pkt_if(v, scr + G_ML + near_half(G_ML, side) + (kvh * 8 + (lane & 3) * 2 + bb) * 8, (v.x ^ tag) & 7u); }
                while (any_lane((v.x ^ tag) & 7u) && ++it < SPIN_LIMIT);
                if (rd) { m0 = untagf(v.x); l0 = __uint_as_float(v.y); m1 = __uint_as_float(v.z); l1 = __uint_as_float(v.w); }
            }
            float g0 = fmaxf(m0, shx(m0, 1)), g1 = fmaxf(m1, shx(m1, 1));
            g0 = fmaxf(g0, shx(g0, 2)); g1 = fmaxf(g1, shx(g1, 2));
            l0 *= ex2((m0 - g0) * L2E); l1 *= ex2((m1 - g1) * L2E);
            l0 += shx(l0, 1); l1 += shx(l1, 1);
            l0 += shx(l0, 2); l1 += shx(l1, 2);
            if (lane == 0)
                sts128(sb + OFF_WMX + 96, __float_as_uint(g0), __float_as_uint(g1), __float_as_uint(__frcp_rn(l0)), __float_as_uint(__frcp_rn(l1)));
        }
        bar_consumers();
        if (vw < 8) {
            const uint4 gs = lds128(sb + OFF_WMX + 96);
            const float g0 = __uint_as_float(gs.x), g1 = __uint_as_float(gs.y), i0 = __uint_as_float(gs.z), i1 = __uint_as_float(gs.w);
            const uint32_t a0 = pack2(ex2((bflo(sv.x) - g0) * L2E) * i0, ex2((bflo(sv.y) - g0) * L2E) * i0);
            const uint32_t a1 = pack2(ex2((bflo(sv.z) - g0) * L2E) * i0, ex2((bflo(sv.w) - g0) * L2E) * i0);
            const uint32_t b0 = pack2(ex2((bfhi(sv.x) - g1) * L2E) * i1, ex2((bfhi(sv.y) - g1) * L2E) * i1);
            const uint32_t b1 = pack2(ex2((bfhi(sv.z) - g1) * L2E) * i1, ex2((bfhi(sv.w) - g1) * L2E) * i1);
            sts64(sb + OFF_P + tid * 8, a0, a1); sts64(sb + OFF_P + PSTR + tid * 8, b0, b1);
        }
        bar_consumers();
    }
    const uint32_t rsw = ((mi & 1) ^ r) << 4;
    unsigned sidew = 2u;
    if (vw < 8) {
        float c0[4] = {}, c1[4] = {};
        const uint32_t vo = (vw >> 2) * 8192 + (r + 8 * (mi >> 1)) * 128 + ((((2 * vw + (mi & 1)) & 7) ^ r) << 4);
        const uint32_t pa = sb + OFF_P + bat * PSTR + t * 32;
#pragma unroll 1
        for (int i = 0; i < 16; i++) {
            uint4 pb0 = lds128(pa + i * 128), pb1 = lds128(pa + i * 128 + 16);
            mbar_wait(s_full + (IT_V + i) * 8);
            const uint32_t base = sb + v_off(i) + vo;
            uint32_t a0[4], a1[4], a2[4], a3[4];
            ldsm4t(a0, base); ldsm4t(a1, base + 2048); ldsm4t(a2, base + 4096); ldsm4t(a3, base + 6144);
            mma16816(c0, a0, pb0.x, pb0.y);
            mma16816(c1, a1, pb0.z, pb0.w);
            mma16816(c0, a2, pb1.x, pb1.y);
            mma16816(c1, a3, pb1.z, pb1.w);
            __syncwarp();
            if (lane == 0) mbar_arrive(s_empty + (EM_V + i) * 8);
            if (i == SIDE_V) { mbar_wait(s_empty + EM_PH * 8); sidew = ldg_rlx1(pside); }
        }
        if (t < 2)
            stg_pkt(scr + G_OP + kvh * 4096 + (j >> 2) * 2048 + t * HALF + (j & 3) * 256 + vw * 32 + g * 4,
                    c0[0] + c1[0], c0[1] + c1[1], c0[2] + c1[2], c0[3] + c1[3], tag);
    } else {
        mbar_wait(s_full + (IT_V + SIDE_V) * 8);
        mbar_wait(s_empty + EM_PH * 8);
    }
    {
        int it = 0;
        while (any_lane((sidew ^ tag) & 7u) && ++it < SPIN_LIMIT) sidew = ldg_rlx1(pside);
        ppart += near_half(G_PART + (vw * 16 + t * 4 + (g >> 1)) * 2048, sidew >> 4);
    }
    side = __float_as_uint(ldsf(sb + OFF_WMX + 112));
#pragma unroll 1
    for (int ph = 0; ph < 2; ph++) {
    if (ph) {
    uint32_t ag[4][6][4];
    const uint32_t gub = s_full + (IT_GU + 2 * (vw / 3)) * 8;
    const uint32_t gpitch = wide ? 96 : 64, gsw = wide ? 0 : (r >> 1) << 4;
    const uint32_t gbase = sb + ((mi & 1) ? OFF_U : OFF_G) + (vw * 64 + r + 8 * (mi >> 1)) * gpitch;
    auto load_gu = [&]() {
#pragma unroll
        for (int ks = 0; ks < 4; ks++)
#pragma unroll
            for (int q = 0; q < 4; q++) ldsm4t(ag[ks][q], gbase + ks * 16 * gpitch + ((q << 4) ^ gsw));
        if (wide) {
#pragma unroll
            for (int ks = 0; ks < 4; ks++)
#pragma unroll
                for (int q = 4; q < 6; q++) ldsm4t(ag[ks][q], gbase + ks * 1536 + q * 16);
        }
    };
    bool gpre;
    while (true) {
        gpre = __all_sync(0xffffffffu, mbar_test(gub) && mbar_test(gub + 8));
        if (gpre || __all_sync(0xffffffffu, mbar_test(s_empty + EM_X1 * 8))) break;
    }
    if (gpre) {
        load_gu();
        mbar_wait(s_empty + EM_X1 * 8);
    }
    {
        uint4 v;
        int it = 0;
        const int xw = G_X1 + (vw >> 3) * 2048 + (c & (XREP - 1)) * 4096;
        const unsigned* px = scr + xw + near_half(xw, side) + (vecw & 1023);
        do { v = ldg_rlx4(px); } while (any_lane(bad4(v, tag) & 7u) && ++it < SPIN_LIMIT);
        xw0 = hi2(v.x, v.y); xw1 = hi2(v.z, v.w);
        ln_stage1(xw0, xw1, st2, vw, lane);
        bar_consumers();
        if (tid == 0) mbar_arrive(s_empty + EM_CH * 8);
        uint32_t y0, y1;
        ln_stage2(ln_load(st2), xw0, xw1, y0, y1);
        aw0 = badd2(bmul2(y0, sc0), sh0); aw1 = badd2(bmul2(y1, sc1), sh1);
        uint32_t bf[4][2];
        make_bfrags(bf, aw0, aw1, r);
        if (!gpre) { mbar_wait(gub); mbar_wait(gub + 8); load_gu(); }
        float cc[6][4] = {};
#pragma unroll
        for (int ks = 0; ks < 4; ks++)
#pragma unroll
            for (int q = 0; q < 4; q++) mma16816(cc[q], ag[ks][q], bf[ks][0], bf[ks][1]);
        if (wide) {
#pragma unroll
            for (int ks = 0; ks < 4; ks++)
#pragma unroll
                for (int q = 4; q < 6; q++) mma16816(cc[q], ag[ks][q], bf[ks][0], bf[ks][1]);
        }
        if (t == 0) {
#pragma unroll
            for (int q = 0; q < 6; q++) sts128f(sb + OFF_RED + vw * 768 + q * 128 + g * 16, cc[q]);
        }
        bar_consumers();
        if (tid < 192) {
            float sv[NCW];
#pragma unroll
            for (int w = 0; w < NCW; w++) sv[w] = ldsf(sb + OFF_RED + w * 768 + tid * 4);
            const float s = ((sv[0] + sv[1]) + (sv[2] + sv[3])) + ((sv[4] + sv[5]) + (sv[6] + sv[7])) + sv[8];
            const uint32_t gu = pack2(s, __shfl_down_sync(0xffffffffu, s, 2));
            const float gt = bflo(gu);
            const uint32_t hh = pack2(((gt > 0.f) ? gt : gt * 0.0f) * bfhi(gu), 0.f);
            const int rr = tid >> 2;
            if ((tid & 2) == 0)
                sts16(sb + OFF_FR + ((tid & 1) * 4 + ((rr & 7) >> 1)) * 48 + (rr >> 3) * 4 + (rr & 1) * 2, hh);
        }
    }
    bar_consumers();
    }
    {
        const int di = (vw / 3 + 1) % 3;
        const uint32_t rrow = (r + 8 * (mi >> 1)) * 128;
        const uint32_t b0 = sb + rrow + (ph ? OFF_D + di * DSTR + (vw % 3) * (wide ? 6144 : 4096) : OFF_WO0 + vw * 2048);
        const uint32_t b1 = ph ? b0 + 2048 : sb + rrow + OFF_WO1 + vw * 2048;
        const uint32_t fb0 = s_full + (ph ? IT_WD + di : IT_WO) * 8;
        const bool k3 = ph && wide;
        uint32_t ad[3][4][4];
        mbar_wait(fb0);
#pragma unroll
        for (int mt = 0; mt < 4; mt++) ldsm4t(ad[0][mt], b0 + (rsw ^ (mt * 32)));
        if (!ph) mbar_wait(fb0 + 8);
#pragma unroll
        for (int mt = 0; mt < 4; mt++) ldsm4t(ad[1][mt], b1 + (rsw ^ (mt * 32)));
        if (k3) {
#pragma unroll
            for (int mt = 0; mt < 4; mt++) ldsm4t(ad[2][mt], b0 + 4096 + (rsw ^ (mt * 32)));
        }
        if (!ph) asm volatile("bar.sync 3, 352;" ::: "memory");
        const uint4 fr = lds128(sb + OFF_FR + r * 48);
        const uint2 f2 = lds64(sb + OFF_FR + r * 48 + 16);
        float cc[4][4] = {};
#pragma unroll
        for (int mt = 0; mt < 4; mt++) mma16816(cc[mt], ad[0][mt], fr.x, fr.y);
#pragma unroll
        for (int mt = 0; mt < 4; mt++) mma16816(cc[mt], ad[1][mt], fr.z, fr.w);
        if (k3) {
#pragma unroll
            for (int mt = 0; mt < 4; mt++) mma16816(cc[mt], ad[2][mt], f2.x, f2.y);
        }
        publish_partials(ppart, t, cc, tag | (ph * 4u));
    }
    }
    if (vw / 3 == c / 48) asm volatile("bar.arrive 5, 128;" ::: "memory");
    if (vw >= 6 && c < 16) asm volatile("bar.arrive 7, 128;" ::: "memory");
}

typedef CUresult (*EncodeFn)(CUtensorMap*, CUtensorMapDataType, cuuint32_t, void*, const cuuint64_t*, const cuuint64_t*,
                             const cuuint32_t*, const cuuint32_t*, CUtensorMapInterleave, CUtensorMapSwizzle,
                             CUtensorMapL2promotion, CUtensorMapFloatOOBfill);

void make_map(EncodeFn enc, CUtensorMap* m, const void* p, cuuint64_t d0, cuuint64_t d1, cuuint64_t d2,
              cuuint64_t s1, cuuint64_t s2, cuuint32_t b0, cuuint32_t b1, cuuint32_t b2, CUtensorMapSwizzle sw,
              CUtensorMapL2promotion pr = CU_TENSOR_MAP_L2_PROMOTION_L2_128B) {
    cuuint64_t dims[3] = {d0, d1, d2};
    cuuint64_t str[2] = {s1, s2};
    cuuint32_t box[3] = {b0, b1, b2};
    cuuint32_t es[3] = {1, 1, 1};
    enc(m, CU_TENSOR_MAP_DATA_TYPE_BFLOAT16, 3, const_cast<void*>(p), dims, str, box, es,
        CU_TENSOR_MAP_INTERLEAVE_NONE, sw, pr, CU_TENSOR_MAP_FLOAT_OOB_FILL_NONE);
}

}

extern "C" void kernel_launch(void* const* d_in, const int* in_sizes, int n_in, void* d_out, int out_size) {
    (void)in_sizes; (void)n_in; (void)out_size;
    void* fn = nullptr;
    cudaDriverEntryPointQueryResult qr;
    cudaGetDriverEntryPoint("cuTensorMapEncodeTiled", &fn, cudaEnableDefault, &qr);
    EncodeFn enc = (EncodeFn)fn;
    cudaFuncSetAttribute(fused_block_kernel, cudaFuncAttributeMaxDynamicSharedMemorySize, SMEM_BYTES);

    const void *x = d_in[0], *kc = d_in[1], *vc = d_in[2], *wq = d_in[3], *wo = d_in[4];
    const void *wg = d_in[6], *wu = d_in[7], *wd = d_in[8], *cc = d_in[9], *wmod = d_in[10];
    const CUtensorMapSwizzle S128 = CU_TENSOR_MAP_SWIZZLE_128B, S64 = CU_TENSOR_MAP_SWIZZLE_64B, S0 = CU_TENSOR_MAP_SWIZZLE_NONE;
    void* raw = nullptr;
    cudaGetSymbolAddress(&raw, g_raw);
    unsigned* scr = (unsigned*)(((uintptr_t)raw + 0x1fffff) & ~(uintptr_t)0x1fffff);
    Maps m;
    make_map(enc, &m.m[M_K], kc, 64, 32ull * 32768, 2, 256, 128, 64, 64, 2, S128, CU_TENSOR_MAP_L2_PROMOTION_L2_256B);
    make_map(enc, &m.m[M_V], vc, 64, 32ull * 32768, 2, 256, 128, 64, 64, 2, S128, CU_TENSOR_MAP_L2_PROMOTION_L2_256B);
    make_map(enc, &m.m[M_WMOD], wmod, 3456, 144, 4, 3456 * 2, 3456 * 2 * 144, 32, 144, 2, S64);
    make_map(enc, &m.m[M_WQ], wq, 4096, 144, 4, 4096 * 2, 4096 * 2 * 144, 32, 144, 2, S64);
    make_map(enc, &m.m[M_WG], wg, 4608, 576, 1, 4608 * 2, 4608 * 2 * 576, 32, 192, 1, S64);
    make_map(enc, &m.m[M_WU], wu, 4608, 576, 1, 4608 * 2, 4608 * 2 * 576, 32, 192, 1, S64);
    make_map(enc, &m.m[M_WG48], wg, 4608, 576, 1, 4608 * 2, 4608 * 2 * 576, 48, 192, 1, S0);
    make_map(enc, &m.m[M_WU48], wu, 4608, 576, 1, 4608 * 2, 4608 * 2 * 576, 48, 192, 1, S0);
    make_map(enc, &m.m[M_WO], wo, 64, 4096, 9, 1152, 128, 64, 16, 9, S128);
    make_map(enc, &m.m[M_WD], wd, 64, 4608, 9, 1152, 128, 64, 32, 3, S128);
    make_map(enc, &m.m[M_WD48], wd, 64, 4608, 9, 1152, 128, 64, 48, 3, S128);
    fused_block_kernel<<<NCTA, NTHR, SMEM_BYTES>>>(m, (const __nv_bfloat16*)x, (const __nv_bfloat16*)cc,
                                                   (const __nv_bfloat16*)kc, (__nv_bfloat16*)d_out, scr);
}
```

```cpp
#include <cuda_runtime.h>
#include <cuda.h>
#include <cuda_bf16.h>
#include <stdint.h>

namespace {

constexpr int DM = 576;
constexpr int NCTA = 128;
constexpr int NCW = 9;
constexpr int NTHR = (NCW + 3) * 32;
constexpr int NMOD = 108;

constexpr int WIN_MAIN = 4;
constexpr int WIN_TAIL = 3;
constexpr int PACE_GBS = 3185;
constexpr int PACE_LEAD = 19456;
constexpr int EARLY_PF = 8192;
constexpr int DELAY_B = 300;
constexpr int DELAY_D = 100;
constexpr int XREP = 2;
constexpr int PH_K = 0;
constexpr int PH_V = 0;
constexpr int SIDE_V = 6;
constexpr int NPROBE0 = 3, NPROBE = 10;
#define SCRATCH_PAD (8 << 20)

constexpr int IT_WMOD = 0, IT_WQ = 2, IT_K = 4, IT_V = 20, IT_WO = 36, IT_GU = 38, IT_WD = 44, N_IT = 47;
constexpr int EM_WMOD = 0, EM_WQ = 1, EM_K = 2, EM_V = 18, EM_PH = 34, EM_X1 = 35, EM_SD = 36, N_EM = 37;

constexpr int RING = 13 * 16384;
constexpr int OFF_WMOD = 0, OFF_WQ = 36864, OFF_K0 = 73728;
constexpr int OFF_WO0 = 194560, OFF_WO1 = 0, OFF_G = 18432, OFF_U = 73728;
constexpr int OFF_D = 129024, DSTR = 18432;
constexpr int PSTR = 2064;
constexpr int OFF_P = RING;
constexpr int OFF_S = OFF_P + 4160;
constexpr int OFF_RED = OFF_S + 4096;
constexpr int OFF_QS = OFF_RED + 6912;
constexpr int OFF_FR = OFF_QS + 640;
constexpr int OFF_STAT = OFF_FR + 384;
constexpr int OFF_WMX = OFF_STAT + 320;
constexpr int OFF_BAR = OFF_WMX + 128;
constexpr int SMEM_USED = OFF_BAR + (N_IT + N_EM) * 8;
constexpr int SMEM_BYTES = SMEM_USED + 1024;
static_assert(SMEM_BYTES <= 232448, "smem");

struct Maps { CUtensorMap m[11]; };
enum { M_K, M_V, M_WMOD, M_WQ, M_WO, M_WG, M_WU, M_WD, M_WG48, M_WU48, M_WD48 };

constexpr int HALF = 1024;
constexpr int G_PART = 0;
constexpr int G_OP = G_PART + 144 * 2048;
constexpr int G_X1 = G_OP + 16 * 4096;
constexpr int G_PROBE = G_X1 + XREP * 4096;
constexpr int G_SIDE = G_PROBE + 2048;
constexpr int G_EPOCH = G_SIDE + 1024;
constexpr int G_MOD = G_EPOCH + 1024;
constexpr int G_Q = G_MOD + 7 * 2048;
constexpr int G_ML = G_Q + 8 * 2048;
constexpr int G_WORDS = G_ML + 2048;
static_assert(G_MOD % 2048 == 0 && G_OP % 2048 == 0 && G_X1 % 2048 == 0 && G_PROBE % 2048 == 0, "halves");
static_assert(G_WORDS * 4 <= (2 << 20), "scratch must fit one 2 MB page");
__device__ __align__(128) unsigned g_raw[(2 << 20) / 4 + G_WORDS + SCRATCH_PAD];
__device__ __forceinline__ int near_half(int w, unsigned side) { return ((__popc(w & 0x2C800) ^ side) & 1) << 10; }
__device__ __forceinline__ int dual(int base, int i) { return base + i + (i & ~1023); }
__device__ __forceinline__ int dual_near(int base, int i, unsigned side) { const int w = dual(base, i); return w + near_half(w, side); }

constexpr int SPIN_LIMIT = 1 << 20;

__device__ __forceinline__ uint32_t smem_u32(const void* p) { return (uint32_t)__cvta_generic_to_shared(p); }
__device__ __forceinline__ void mbar_init(uint32_t bar, int cnt) {
    asm volatile("mbarrier.init.shared::cta.b64 [%0], %1;" ::"r"(bar), "r"(cnt) : "memory");
}
__device__ __forceinline__ void mbar_expect_tx(uint32_t bar, uint32_t bytes) {
    asm volatile("mbarrier.arrive.expect_tx.shared::cta.b64 _, [%0], %1;" ::"r"(bar), "r"(bytes) : "memory");
}
__device__ __forceinline__ void mbar_arrive(uint32_t bar) {
    asm volatile("mbarrier.arrive.shared::cta.b64 _, [%0];" ::"r"(bar) : "memory");
}
__device__ __forceinline__ void mbar_wait(uint32_t bar) {
    asm volatile("{\n.reg .pred p;\nW_%=:\nmbarrier.try_wait.parity.shared::cta.b64 p, [%0], 0;\n@!p bra W_%=;\n}"
                 ::"r"(bar) : "memory");
}
__device__ __forceinline__ bool mbar_test(uint32_t bar) {
    uint32_t ok;
    asm volatile("{\n.reg .pred p;\nmbarrier.test_wait.parity.shared::cta.b64 p, [%1], 0;\nselp.u32 %0, 1, 0, p;\n}"
                 : "=r"(ok) : "r"(bar) : "memory");
    return ok;
}
__device__ __forceinline__ uint32_t gtime32() { uint32_t t; asm volatile("mov.u32 %0, %%globaltimer_lo;" : "=r"(t)); return t; }
__device__ __forceinline__ uint64_t policy_stream() {
    uint64_t p; asm("createpolicy.fractional.L2::evict_first.b64 %0, 1.0;" : "=l"(p)); return p;
}
__device__ __forceinline__ void tma3d(uint32_t dst, const CUtensorMap* m, int x, int y, int z, uint32_t bar) {
    asm volatile("cp.async.bulk.tensor.3d.shared::cluster.global.mbarrier::complete_tx::bytes.L2::cache_hint [%0], [%1, {%3, %4, %5}], [%2], %6;"
                 ::"r"(dst), "l"(m), "r"(bar), "r"(x), "r"(y), "r"(z), "l"(policy_stream()) : "memory");
}
__device__ __forceinline__ void bar_consumers() { asm volatile("bar.sync 1, 288;" ::: "memory"); }

__device__ __forceinline__ void ldsm4(uint32_t (&a)[4], uint32_t addr) {
    asm volatile("ldmatrix.sync.aligned.m8n8.x4.shared.b16 {%0,%1,%2,%3}, [%4];"
                 : "=r"(a[0]), "=r"(a[1]), "=r"(a[2]), "=r"(a[3]) : "r"(addr) : "memory");
}
__device__ __forceinline__ void ldsm4t(uint32_t (&a)[4], uint32_t addr) {
    asm volatile("ldmatrix.sync.aligned.m8n8.x4.trans.shared.b16 {%0,%1,%2,%3}, [%4];"
                 : "=r"(a[0]), "=r"(a[1]), "=r"(a[2]), "=r"(a[3]) : "r"(addr) : "memory");
}
__device__ __forceinline__ void mma16816(float (&c)[4], const uint32_t (&a)[4], uint32_t b0, uint32_t b1) {
    asm volatile("mma.sync.aligned.m16n8k16.row.col.f32.bf16.bf16.f32 {%0,%1,%2,%3}, {%4,%5,%6,%7}, {%8,%9}, {%0,%1,%2,%3};"
                 : "+f"(c[0]), "+f"(c[1]), "+f"(c[2]), "+f"(c[3])
                 : "r"(a[0]), "r"(a[1]), "r"(a[2]), "r"(a[3]), "r"(b0), "r"(b1));
}
__device__ __forceinline__ float ldsf(uint32_t a) { float v; asm volatile("ld.shared.f32 %0, [%1];" : "=f"(v) : "r"(a) : "memory"); return v; }
__device__ __forceinline__ uint2 lds64(uint32_t a) {
    uint2 v; asm volatile("ld.shared.v2.u32 {%0,%1}, [%2];" : "=r"(v.x), "=r"(v.y) : "r"(a) : "memory"); return v;
}
__device__ __forceinline__ uint4 lds128(uint32_t a) {
    uint4 v; asm volatile("ld.shared.v4.u32 {%0,%1,%2,%3}, [%4];" : "=r"(v.x), "=r"(v.y), "=r"(v.z), "=r"(v.w) : "r"(a) : "memory"); return v;
}
__device__ __forceinline__ void sts16(uint32_t a, uint32_t v) { asm volatile("st.shared.u16 [%0], %1;" ::"r"(a), "h"((unsigned short)v) : "memory"); }
__device__ __forceinline__ void sts32(uint32_t a, uint32_t v) { asm volatile("st.shared.u32 [%0], %1;" ::"r"(a), "r"(v) : "memory"); }
__device__ __forceinline__ void sts64(uint32_t a, uint32_t x, uint32_t y) { asm volatile("st.shared.v2.u32 [%0], {%1,%2};" ::"r"(a), "r"(x), "r"(y) : "memory"); }
__device__ __forceinline__ void sts128(uint32_t a, uint32_t x, uint32_t y, uint32_t z, uint32_t w) {
    asm volatile("st.shared.v4.u32 [%0], {%1,%2,%3,%4};" ::"r"(a), "r"(x), "r"(y), "r"(z), "r"(w) : "memory");
}
__device__ __forceinline__ void sts128f(uint32_t a, const float (&c)[4]) {
    asm volatile("st.shared.v4.f32 [%0], {%1,%2,%3,%4};" ::"r"(a), "f"(c[0]), "f"(c[1]), "f"(c[2]), "f"(c[3]) : "memory");
}
__device__ __forceinline__ unsigned ldg_rlx1(const unsigned* p) {
    unsigned v; asm volatile("ld.relaxed.gpu.global.u32 %0, [%1];" : "=r"(v) : "l"(p) : "memory"); return v;
}
__device__ __forceinline__ uint4 ldg_rlx4(const unsigned* p) {
    uint4 v; asm volatile("ld.relaxed.gpu.global.v4.u32 {%0,%1,%2,%3}, [%4];" : "=r"(v.x), "=r"(v.y), "=r"(v.z), "=r"(v.w) : "l"(p) : "memory"); return v;
}
__device__ __forceinline__ uint4 ldg_pkt(const unsigned* p) {
    uint4 v;
    asm volatile("{\n.reg .b128 t;\n.reg .b64 lo, hi;\nld.relaxed.gpu.global.b128 t, [%4];\nmov.b128 {lo, hi}, t;\n"
                 "mov.b64 {%0,%1}, lo;\nmov.b64 {%2,%3}, hi;\n}"
                 : "=r"(v.x), "=r"(v.y), "=r"(v.z), "=r"(v.w) : "l"(p) : "memory");
    return v;
}
__device__ __forceinline__ void ldg_pkt_if(uint4& v, const unsigned* a, unsigned p) {
    asm volatile("{\n.reg .pred q;\n.reg .b128 t;\n.reg .b64 lo, hi;\nsetp.ne.u32 q, %5, 0;\n"
                 "mov.b64 lo, {%0,%1};\nmov.b64 hi, {%2,%3};\nmov.b128 t, {lo, hi};\n"
                 "@q ld.relaxed.gpu.global.b128 t, [%4];\nmov.b128 {lo, hi}, t;\n"
                 "mov.b64 {%0,%1}, lo;\nmov.b64 {%2,%3}, hi;\n}"
                 : "+r"(v.x), "+r"(v.y), "+r"(v.z), "+r"(v.w) : "l"(a), "r"(p) : "memory");
}
__device__ __forceinline__ bool any_lane(unsigned x) { return __any_sync(0xffffffffu, x != 0); }
__device__ __forceinline__ void stg_pkt(unsigned* p, float a, float b, float c, float d, unsigned tag) {
    unsigned x = (__float_as_uint(a) & ~7u) | tag;
    asm volatile("{\n.reg .b128 t;\n.reg .b64 lo, hi;\nmov.b64 lo, {%1,%2};\nmov.b64 hi, {%3,%4};\nmov.b128 t, {lo, hi};\n"
                 "st.relaxed.gpu.global.b128 [%0], t;\n}"
                 ::"l"(p), "r"(x), "r"(__float_as_uint(b)), "r"(__float_as_uint(c)), "r"(__float_as_uint(d)) : "memory");
}
__device__ __forceinline__ void stg_rlx1(unsigned* p, unsigned x) { asm volatile("st.relaxed.gpu.global.u32 [%0], %1;" ::"l"(p), "r"(x) : "memory"); }
__device__ __forceinline__ unsigned bad4(const uint4& v, unsigned tag) {
    return ((v.x ^ tag) | (v.y ^ tag)) | ((v.z ^ tag) | (v.w ^ tag));
}
__device__ __forceinline__ float untagf(unsigned w) { return __uint_as_float(w & ~7u); }
__device__ __forceinline__ uint32_t pack2(float lo, float hi) {
    uint32_t r; asm("cvt.rn.bf16x2.f32 %0, %1, %2;" : "=r"(r) : "f"(hi), "f"(lo)); return r;
}
__device__ __forceinline__ float bflo(uint32_t w) { return __uint_as_float(w << 16); }
__device__ __forceinline__ float bfhi(uint32_t w) { return __uint_as_float(w & 0xffff0000u); }
__device__ __forceinline__ uint32_t hi2(uint32_t a, uint32_t b) { return __byte_perm(a, b, 0x7632); }
__device__ __forceinline__ uint32_t badd2(uint32_t a, uint32_t b) { uint32_t r; asm("add.rn.bf16x2 %0, %1, %2;" : "=r"(r) : "r"(a), "r"(b)); return r; }
__device__ __forceinline__ uint32_t bsub2(uint32_t a, uint32_t b) { uint32_t r; asm("sub.rn.bf16x2 %0, %1, %2;" : "=r"(r) : "r"(a), "r"(b)); return r; }
__device__ __forceinline__ uint32_t bmul2(uint32_t a, uint32_t b) { uint32_t r; asm("mul.rn.bf16x2 %0, %1, %2;" : "=r"(r) : "r"(a), "r"(b)); return r; }
__device__ __forceinline__ uint32_t bmax2(uint32_t a, uint32_t b) { uint32_t r; asm("max.bf16x2 %0, %1, %2;" : "=r"(r) : "r"(a), "r"(b)); return r; }
__device__ __forceinline__ float ex2(float x) { float r; asm("ex2.approx.ftz.f32 %0, %1;" : "=f"(r) : "f"(x)); return r; }
__device__ __forceinline__ float rcp(float x) { float r; asm("rcp.approx.ftz.f32 %0, %1;" : "=f"(r) : "f"(x)); return r; }
__device__ __forceinline__ float fsqrt(float x) { float r; asm("sqrt.approx.ftz.f32 %0, %1;" : "=f"(r) : "f"(x)); return r; }
__device__ __forceinline__ float shx(float v, int m) { return __shfl_xor_sync(0xffffffffu, v, m); }

__device__ __forceinline__ uint32_t k_off(int i) { return i < 8 ? OFF_K0 + i * 16384 : (i - 8) * 16384; }
__device__ __forceinline__ uint32_t v_off(int i) { return i < 5 ? (8 + i) * 16384 : (i - 5) * 16384; }

__device__ __forceinline__ void stg_ph(unsigned* p) { stg_pkt(p, 0.f, 0.f, 0.f, 0.f, 2u); }

__device__ __forceinline__ void ln_stage1(uint32_t xw0, uint32_t xw1, uint32_t st, int vw, int lane) {
    const float piv = __shfl_sync(0xffffffffu, bflo(xw0), lane & 4);
    const float d0 = bflo(xw0) - piv, d1 = bfhi(xw0) - piv, d2 = bflo(xw1) - piv, d3 = bfhi(xw1) - piv;
    float s1 = (d0 + d1) + (d2 + d3), s2 = (d0 * d0 + d1 * d1) + (d2 * d2 + d3 * d3);
    s1 += shx(s1, 1); s2 += shx(s2, 1);
    s1 += shx(s1, 2); s2 += shx(s2, 2);
    s1 += shx(s1, 8); s2 += shx(s2, 8);
    s1 += shx(s1, 16); s2 += shx(s2, 16);
    if ((lane & 27) == 0)
        sts64(st + vw * 8, __float_as_uint(piv + s1 * (1.0f / 64.0f)), __float_as_uint(s2 - s1 * s1 * (1.0f / 64.0f)));
}
struct LnStat { uint4 a, b, c, d; uint2 e; };
__device__ __forceinline__ LnStat ln_load(uint32_t st) {
    LnStat s; s.a = lds128(st); s.b = lds128(st + 16); s.c = lds128(st + 32); s.d = lds128(st + 48); s.e = lds64(st + 64);
    return s;
}
__device__ __forceinline__ void ln_stage2(const LnStat& s, uint32_t xw0, uint32_t xw1, uint32_t& y0, uint32_t& y1) {
    const float m[9] = {__uint_as_float(s.a.x), __uint_as_float(s.a.z), __uint_as_float(s.b.x), __uint_as_float(s.b.z),
                        __uint_as_float(s.c.x), __uint_as_float(s.c.z), __uint_as_float(s.d.x), __uint_as_float(s.d.z), __uint_as_float(s.e.x)};
    const float mean = (((m[0] + m[1]) + (m[2] + m[3])) + ((m[4] + m[5]) + (m[6] + m[7])) + m[8]) * (1.0f / NCW);
    const float m2 = ((__uint_as_float(s.a.y) + __uint_as_float(s.a.w)) + (__uint_as_float(s.b.y) + __uint_as_float(s.b.w))) +
                     ((__uint_as_float(s.c.y) + __uint_as_float(s.c.w)) + (__uint_as_float(s.d.y) + __uint_as_float(s.d.w))) + __uint_as_float(s.e.y);
    float d[9];
#pragma unroll
    for (int w = 0; w < 9; w++) d[w] = m[w] - mean;
    const float acc = (d[0] * d[0] + d[1] * d[1] + d[2] * d[2]) + (d[3] * d[3] + d[4] * d[4] + d[5] * d[5]) + (d[6] * d[6] + d[7] * d[7] + d[8] * d[8]);
    const float var = (m2 + 64.0f * acc) * (1.0f / DM);
    const uint32_t mv = pack2(mean, var);
    const float ve = bflo(pack2(bfhi(mv) + 1e-5f, 0.f));
    const float rinv = rcp(bflo(pack2(fsqrt(ve), 0.f)));
    const uint32_t mm = __byte_perm(mv, mv, 0x1010);
    const uint32_t e0 = bsub2(xw0, mm), e1 = bsub2(xw1, mm);
    y0 = pack2(bflo(e0) * rinv, bfhi(e0) * rinv); y1 = pack2(bflo(e1) * rinv, bfhi(e1) * rinv);
}
__device__ __forceinline__ void make_bfrags(uint32_t (&bf)[4][2], uint32_t aw0, uint32_t aw1, int r) {
#pragma unroll
    for (int ks = 0; ks < 4; ks++) {
        bf[ks][0] = __shfl_sync(0xffffffffu, aw0, ks * 8 + r);
        bf[ks][1] = __shfl_sync(0xffffffffu, aw1, ks * 8 + r);
    }
}
__device__ __forceinline__ uint32_t gemv32(uint32_t s_w, uint32_t red, uint32_t fullbar, uint32_t emptybar,
                                           uint32_t aw0, uint32_t aw1, int tid) {
    const int vw = tid >> 5, lane = tid & 31, g = lane >> 2, t = lane & 3, mi = lane >> 3, r = lane & 7;
    uint32_t bf[4][2];
    make_bfrags(bf, aw0, aw1, r);
    if (vw <= 4) mbar_wait(fullbar);
    if (vw >= 4) mbar_wait(fullbar + 8);
    float cc[2][4] = {};
    const uint32_t abase = s_w + (vw * 64 + r + 8 * (mi >> 1)) * 64;
    const uint32_t sw = ((mi & 1) ^ (r >> 1)) << 4;
#pragma unroll
    for (int ks = 0; ks < 4; ks++) {
#pragma unroll
        for (int mt = 0; mt < 2; mt++) {
            uint32_t a[4];
            ldsm4t(a, abase + ks * 1024 + (sw ^ (mt * 32)));
            mma16816(cc[mt], a, bf[ks][0], bf[ks][1]);
        }
    }
    if (t == 0) { sts128f(red + vw * 256 + g * 16, cc[0]); sts128f(red + vw * 256 + 128 + g * 16, cc[1]); }
    __syncwarp();
    if (lane == 0) mbar_arrive(emptybar);
    bar_consumers();
    float s = 0.f;
    if (tid < 64) {
        const uint32_t ra = red + ((tid & 58) | ((tid & 1) << 2) | ((tid >> 2) & 1)) * 4;
#pragma unroll
        for (int w = 0; w < NCW; w++) s += ldsf(ra + w * 256);
    }
    return pack2(0.f, s);
}
__device__ __forceinline__ void publish_partials(unsigned* q, int t, const float (&cc)[4][4], unsigned tag) {
    float v[4];
#pragma unroll
    for (int i = 0; i < 4; i++) {
        const float lo = (t & 1) ? cc[1][i] : cc[0][i], hi = (t & 1) ? cc[3][i] : cc[2][i];
        v[i] = (t & 2) ? hi : lo;
    }
    stg_pkt(q, v[0], v[1], v[2], v[3], tag);
}
__device__ __forceinline__ void spin_cycles(unsigned n) {
    const unsigned c0 = clock();
    while ((unsigned)clock() - c0 < n) { }
}
__device__ __forceinline__ float reduce_unit(const unsigned* q, int lane, unsigned tag) {
    uint4 v[8];
#pragma unroll
    for (int i = 0; i < 8; i++) v[i] = ldg_pkt(q + i * 128);
    int it = 0;
    unsigned y[8];
    while (true) {
#pragma unroll
        for (int i = 0; i < 8; i++) y[i] = v[i].x ^ tag;
        const bool more = any_lane((((y[0] | y[1] | y[2]) | (y[3] | y[4] | y[5])) | (y[6] | y[7])) & 7u);
        if (!more || ++it >= SPIN_LIMIT) break;
#pragma unroll
        for (int i = 0; i < 8; i++) ldg_pkt_if(v[i], q + i * 128, y[i] & 7u);
    }
#define SUM8(e) (((e(0) + e(1)) + (e(2) + e(3))) + ((e(4) + e(5)) + (e(6) + e(7))))
#define EX(i) __uint_as_float(y[i])
#define EY(i) __uint_as_float(v[i].y)
#define EZ(i) __uint_as_float(v[i].z)
#define EW(i) __uint_as_float(v[i].w)
    const float s0 = SUM8(EX), s1 = SUM8(EY), s2 = SUM8(EZ), s3 = SUM8(EW);
    const bool h8 = lane & 2, bat = lane & 4;
    const float k0 = (h8 ? s2 : s0) + shx(h8 ? s0 : s2, 2);
    const float k1 = (h8 ? s3 : s1) + shx(h8 ? s1 : s3, 2);
    float k = (bat ? k1 : k0) + shx(bat ? k0 : k1, 4);
    k += shx(k, 8);
    k += shx(k, 16);
    return k;
}

__global__ void __launch_bounds__(NTHR, 1)
fused_block_kernel(const __grid_constant__ Maps maps, const __nv_bfloat16* __restrict__ xin,
                   const __nv_bfloat16* __restrict__ cin, const __nv_bfloat16* __restrict__ kcache,
                   __nv_bfloat16* __restrict__ out, unsigned* const scr) {
    extern __shared__ unsigned char smem_raw[];
    const int c = blockIdx.x;
    const int kvh = c >> 3, j = c & 7, bb = j & 1, sp = j >> 1;
    const bool wide = j >= 6;
    const int f0 = kvh * 288 + (wide ? 48 * j - 96 : 32 * j);
    const int kvrow0 = (bb * 16 + kvh) * 32768 + 28672 + sp * 64;
    const int kvstep = 256;
    if (threadIdx.x == 0)
        asm volatile("cp.async.bulk.prefetch.L2.global.L2::cache_hint [%0], %1, %2;"
                     ::"l"((const char*)kcache + (size_t)kvrow0 * 256), "r"(EARLY_PF), "l"(policy_stream()) : "memory");
    const uint32_t sb = (smem_u32(smem_raw) + 1023u) & ~1023u;
    const int warp = threadIdx.x >> 5, lane = threadIdx.x & 31;
    const uint32_t s_full = sb + OFF_BAR, s_empty = s_full + N_IT * 8;

    if (warp == NCW) {
        const uint32_t t0 = gtime32();
        const int first = (c < NMOD) ? 0 : 2;
        if (lane == 0) {
#pragma unroll
            for (int i = 0; i < 2; i++) mbar_init(s_full + (first + i) * 8, 1);
            asm volatile("fence.proxy.async.shared::cta;" ::: "memory");
#pragma unroll
            for (int i = 0; i < 2; i++) {
                const uint32_t bar = s_full + (first + i) * 8;
                mbar_expect_tx(bar, 18432);
                tma3d(sb + (first + i) * 18432, &maps.m[M_WMOD + (first >> 1)], c * 32, 0, i * 2, bar);
            }
        }
        __syncwarp();
        uint32_t w0[2], w1[2], w2[2];
#pragma unroll
        for (int h = 0; h < 2; h++) {
            const int i = lane + 32 * h;
            int off, map, dep = -1, x = 0, y = 0, z = 0, sz = 36, cum;
            if (i < IT_K) {
                off = i * 18432; map = M_WMOD + (i >> 1); x = c * 32; z = (i & 1) * 2; cum = 31104 + (i - 2) * 18432;
            } else if (i < IT_V) {
                const int k = i - IT_K;
                off = k_off(k); map = M_K; y = kvrow0 + k * kvstep; sz = 32; cum = 67968 + k * 16384;
                if (k == 8 && c < NMOD) dep = EM_WMOD;
                if (k == 10) dep = EM_WQ;
                if (k >= 12) dep = EM_K + k - 12;
            } else if (i < IT_WO) {
                const int k = i - IT_V;
                off = v_off(k); map = M_V; y = kvrow0 + k * kvstep; sz = 32; cum = 330112 + k * 16384;
                dep = EM_K + 3 + k + (k < 4);
            } else if (i < IT_GU) {
                const int k = i - IT_WO;
                off = k ? OFF_WO1 : OFF_WO0; map = M_WO; y = kvh * 256 + k * 128 + j * 16; dep = EM_V + 4 + 2 * k;
                cum = 592256 + k * 18432;
            } else if (i < IT_WD) {
                const int k = i - IT_GU;
                sz = wide ? 36 : 24;
                off = ((k & 1) ? OFF_U : OFF_G) + (k >> 1) * sz * 512; map = M_WG + (k & 1) + (wide ? 3 : 0);
                x = f0; y = (k >> 1) * 192; dep = EM_V + 5 + ((off + sz * 512 - 1) >> 14);
                cum = 629120 + k * 13824;
            } else {
                const int k = i - IT_WD;
                off = OFF_D + k * DSTR; map = wide ? M_WD48 : M_WD; y = f0; z = ((k + 2) % 3) * 3; sz = wide ? 36 : 24; dep = EM_V + (k ? 15 : 13);
                cum = 712064 + k * 13824;
            }
            const int stag = (i >= IT_K && i < IT_WO) ? (((kvh * 2 + bb) * 13) & 31) * 512 : ((c * 37) & 127) * 128;
            cum += EARLY_PF - min(max(cum - 67968, 0), EARLY_PF);
            const int due = (int)((float)max(cum + stag - PACE_LEAD, 0) * (128.0f / PACE_GBS));
            w0[h] = off | (map << 18) | ((dep + 1) << 22) | (z << 28);
            w1[h] = y | (sz << 24);
            w2[h] = x | (due << 13);
        }
        asm volatile("bar.sync 2, 384;" ::: "memory");
        uint32_t fb = s_full;
        asm volatile("" : "+r"(fb));
#pragma unroll 1
        for (int i = first + 2; i < N_IT; i++) {
            const bool hi = i >= 32;
            const uint32_t a = __shfl_sync(0xffffffffu, hi ? w0[1] : w0[0], i);
            const uint32_t b = __shfl_sync(0xffffffffu, hi ? w1[1] : w1[0], i);
            const uint32_t x = __shfl_sync(0xffffffffu, hi ? w2[1] : w2[0], i);
            if (lane == 0) {
                const uint32_t bar = fb + i * 8;
                const int win = (i >= IT_GU) ? WIN_TAIL : WIN_MAIN;
                const int dep = (a >> 22) & 63;
                const uint32_t due = t0 + (x >> 13);
                if (dep) mbar_wait(fb + (N_IT - 1 + dep) * 8);
                if (i - win >= first) mbar_wait(bar - win * 8);
                while ((int)(gtime32() - due) < 0) { }
                mbar_expect_tx(bar, (b >> 24) * 512);
                tma3d(fb - OFF_BAR + (a & 0x3ffff), &maps.m[(a >> 18) & 15], x & 0x1fff, b & 0xffffff, a >> 28, bar);
            }
            __syncwarp();
        }
        return;
    }

    const int g = lane >> 2, t = lane & 3, mi = lane >> 3, r = lane & 7;
    const int bat = g & 1;

    if (warp > NCW) {
        const bool first = warp == NCW + 1, active = first || c < 16;
        const int unit = first ? c : NCTA + c;
        const int rcol = (unit >> 2) * 16 + (unit & 3) * 2 + (lane & 1) + (lane & 2) * 4 + bat * DM;
        const unsigned ep = ldg_rlx1(scr + G_EPOCH);
        uint32_t xold = 0, ga = 0, gb = 0;
        if (active) xold = __ldg((const unsigned short*)xin + rcol);
        if (!first) asm volatile("bar.sync 2, 384;" ::: "memory");
        const unsigned tag = (ep + 1u) & 1u;
        unsigned side = 0;
        const int x1w = G_X1 + (unit >> 7) * 2048 + (unit & 127) * 8 + r + (lane & 8) * (HALF / 8) + (lane >> 4) * 4096;
        if (first) {
            unsigned* pr = scr + G_PROBE + c * 8;
            if (lane < 16) stg_rlx1(pr + r + (lane & 8) * (HALF / 8), 0u);
            __syncwarp();
            asm volatile("bar.arrive 2, 384;" ::: "memory");
            unsigned best0 = ~0u, best1 = ~0u, v = 0, cp = 0;
#pragma unroll 1
            for (int i = 0; i <= 2 * NPROBE; i++) {
                if (lane == 0) {
                    asm volatile("atom.relaxed.gpu.global.add.u32 %0, [%1], 1;" : "=r"(v) : "l"(pr + (i & 1) * HALF + (v >> 31)) : "memory");
                    const unsigned cn = clock(), d = cn - cp;
                    cp = cn;
                    if (i & 1) best0 = min(best0, d); else if (i) best1 = min(best1, d);
                    side = (best1 < best0) ^ (__popc(G_PROBE & 0x2C800) & 1);
                }
                if (i == 2 * NPROBE0) {
                    asm volatile("bar.sync 6, 64;" ::: "memory");
                    if (lane == 0) { sts32(sb + OFF_WMX + 116, side); mbar_arrive(s_empty + EM_SD * 8); }
                }
            }
            if (lane == 0) sts32(sb + OFF_WMX + 112, side);
            side = __shfl_sync(0xffffffffu, side, 0);
            mbar_wait(s_full + (IT_V + PH_V) * 8);
#pragma unroll 1
            for (int u = c; u < 144; u += NCTA) {
                unsigned* q = scr + G_PART + u * 2048 + near_half(G_PART + u * 2048, side) + lane * 4;
#pragma unroll
                for (int i = 0; i < 8; i++) stg_ph(q + i * 128);
#pragma unroll
                for (int i = 0; i < XREP; i += 2) stg_rlx1(scr + x1w + (u >> 7) * 2048 + i * 4096, 2u);
            }
            unsigned* o = scr + G_OP + kvh * 4096 + (j >> 2) * 2048 + (j & 3) * 256 + lane * 4;
            stg_ph(o); stg_ph(o + 128); stg_ph(o + HALF); stg_ph(o + HALF + 128);
            __threadfence();
            __syncwarp();
            if (lane < 8) stg_rlx1(scr + G_SIDE + c * 8 + lane, (side << 4) | tag);
            if (lane == 0) mbar_arrive(s_empty + EM_PH * 8);
        } else {
            asm volatile("bar.arrive 6, 64;" ::: "memory");
            if (lane < 8) asm volatile("prefetch.tensormap [%0];" ::"l"(&maps.m[lane + ((wide && lane >= M_WG) ? 3 : 0)]) : "memory");
            mbar_wait(s_empty + EM_PH * 8);
            side = __float_as_uint(ldsf(sb + OFF_WMX + 112));
        }
        if (active) {
            int it = 0;
            do {
                ga = ldg_rlx1(scr + dual_near(G_MOD, 2 * 1152 + unit * 8 + r, side));
                gb = ldg_rlx1(scr + dual_near(G_MOD, 5 * 1152 + unit * 8 + r, side));
            } while (any_lane(((ga ^ tag) | (gb ^ tag)) & 7u) && ++it < SPIN_LIMIT);
            ga >>= 16; gb >>= 16;
        }
        __syncwarp();
        if (first) {
            const int ow = G_OP + kvh * 4096 + (g >> 2) * 2048;
            const unsigned* q = scr + ow + near_half(ow, side) + (g & 3) * 256 + j * 32 + t * 8;
            mbar_wait(s_full + (IT_V + 15) * 8);
            uint4 lo, hi;
            int it = 0;
            do { lo = ldg_pkt(q); hi = ldg_pkt(q + 4); } while (any_lane(((lo.x ^ tag) | (hi.x ^ tag)) & 7u) && ++it < SPIN_LIMIT);
            float o[8] = {untagf(lo.x), __uint_as_float(lo.y), __uint_as_float(lo.z), __uint_as_float(lo.w),
                          untagf(hi.x), __uint_as_float(hi.y), __uint_as_float(hi.z), __uint_as_float(hi.w)};
            __syncwarp();
#pragma unroll
            for (int sft = 8; sft <= 16; sft <<= 1) {
#pragma unroll
                for (int i = 0; i < 8; i++) o[i] += shx(o[i], sft);
            }
            if (lane < 8)
                sts128(sb + OFF_FR + lane * 48, pack2(o[0], o[4]), pack2(o[2], o[6]), pack2(o[1], o[5]), pack2(o[3], o[7]));
        }
        asm volatile("bar.sync 3, 352;" ::: "memory");
        const unsigned* q = scr + G_PART + unit * 2048 + near_half(G_PART + unit * 2048, side) + lane * 4;
        if (!active) return;
#pragma unroll 1
        for (int ph = 0; ph < 2; ph++) {
            if (ph) asm volatile("bar.sync %0, 128;" ::"r"(first ? 5 : 7) : "memory");
            spin_cycles(ph ? DELAY_D : DELAY_B);
            const float k = reduce_unit(q, lane, tag | (ph * 4u));
            xold = badd2(xold, bmul2(ga, pack2(k, 0.f))) & 0xffffu;
            ga = gb;
            if (ph) {
                if (lane < 8) ((unsigned short*)out)[rcol] = (unsigned short)xold;
            } else {
#pragma unroll
                for (int i = 0; i < XREP; i += 2) stg_rlx1(scr + x1w + i * 4096, (xold << 16) | tag);
                if (first && lane == 0) mbar_arrive(s_empty + EM_X1 * 8);
            }
        }
        if (c == 0 && first && lane == 0) stg_rlx1(scr + G_EPOCH, ep + 1u);
        return;
    }

    const int vw = warp, tid = threadIdx.x;
    const int vecw = tid * 4 - (lane & 7) * 4 + t * 8 + bat * 4;
    unsigned* ppart = scr + G_PART + (vw * 16 + t * 4 + (g >> 1)) * 2048 + c * 8 + bat * 4;
    const unsigned* const pside = scr + G_SIDE + ((vw * 16 + t * 4 + (g >> 1)) & 127) * 8;
    const int qword = dual(G_Q, bat * 4096 + c * 32 + (tid >> 3) * 4 + t), mword = dual(G_MOD, c * 64 + (tid & 63));
    const uint32_t one2 = 0x3f803f80u;

    const unsigned ep = ldg_rlx1(scr + G_EPOCH);
    if (tid < 64) {
        if (c < NMOD) { stg_rlx1(scr + mword, 2u); stg_rlx1(scr + mword + HALF, 2u); }
        stg_rlx1(scr + qword, 2u); stg_rlx1(scr + qword + HALF, 2u);
    }
    uint32_t xw0, xw1, aw0, aw1;
    {
        const int col0 = bat * DM + (vw * 4 + mi) * 16 + 2 * t;
        const uint32_t cw0 = __ldg((const unsigned*)(cin + col0)), cw1 = __ldg((const unsigned*)(cin + col0 + 8));
        xw0 = __ldg((const unsigned*)(xin + col0)); xw1 = __ldg((const unsigned*)(xin + col0 + 8));
        if (lane == 0) {
            const int lo = (c < NMOD) ? 2 : 4;
#pragma unroll 1
            for (int i = vw; i < N_IT + N_EM; i += NCW) {
                const int e = i - N_IT;
                if (i >= lo) mbar_init(s_full + i * 8, (e < 0 || e >= EM_PH) ? 1 : (e < EM_K ? NCW : (e < EM_V ? 4 : 8)));
            }
            asm volatile("fence.proxy.async.shared::cta;" ::: "memory");
        }
        __syncwarp();
        asm volatile("bar.sync 2, 384;" ::: "memory");
        float cv[4] = {bflo(cw0), bfhi(cw0), bflo(cw1), bfhi(cw1)};
#pragma unroll
        for (int i = 0; i < 4; i++) cv[i] = cv[i] * rcp(1.0f + ex2(-1.4426950408889634f * cv[i]));
        aw0 = pack2(cv[0], cv[1]); aw1 = pack2(cv[2], cv[3]);
    }
    const unsigned tag = (ep + 1u) & 1u;
    const uint32_t st1 = sb + OFF_STAT + bat * 80, st2 = st1 + 160;
    ln_stage1(xw0, xw1, st1, vw, lane);

    if (c < NMOD) {
        const uint32_t m = gemv32(sb + OFF_WMOD, sb + OFF_RED, s_full + IT_WMOD * 8, s_empty + EM_WMOD * 8, aw0, aw1, tid);
        if (tid < 64) { stg_rlx1(scr + mword, m | tag); stg_rlx1(scr + mword + HALF, m | tag); }
    } else {
        bar_consumers();
    }
    mbar_wait(s_empty + EM_SD * 8);
    unsigned side = __float_as_uint(ldsf(sb + OFF_WMX + 116));
    {
        uint32_t y0, y1;
        ln_stage2(ln_load(st1), xw0, xw1, y0, y1);
        uint4 a, b;
        int it = 0;
        const unsigned *pa = scr + dual_near(G_MOD, vecw, side), *pb = scr + dual_near(G_MOD, 1152 + vecw, side);
        do { a = ldg_rlx4(pa); b = ldg_rlx4(pb); }
        while (any_lane((bad4(a, tag) | bad4(b, tag)) & 7u) && ++it < SPIN_LIMIT);
        __syncwarp();
        aw0 = badd2(bmul2(y0, badd2(one2, hi2(b.x, b.y))), hi2(a.x, a.y));
        aw1 = badd2(bmul2(y1, badd2(one2, hi2(b.z, b.w))), hi2(a.z, a.w));
        const uint32_t q = gemv32(sb + OFF_WQ, sb + OFF_RED + 2304, s_full + IT_WQ * 8, s_empty + EM_WQ * 8, aw0, aw1, tid);
        if (tid < 64) {
            stg_rlx1(scr + qword, q | tag); stg_rlx1(scr + qword + HALF, q | tag);
            uint4 v;
            int it = 0;
            const unsigned* pq = scr + dual_near(G_Q, bb * 4096 + kvh * 256 + tid * 4, side);
            do { v = ldg_rlx4(pq); } while (any_lane(bad4(v, tag) & 7u) && ++it < SPIN_LIMIT);
            sts64(sb + OFF_QS + (vw * 4 + t) * 80 + g * 8, hi2(v.x, v.y), hi2(v.z, v.w));
        }
        bar_consumers();
    }
    uint32_t sc0, sc1, sh0, sh1;
    {
        uint4 d, e;
        unsigned bad;
        int it = 0;
        do {
            d = ldg_rlx4(scr + dual_near(G_MOD, 3 * 1152 + vecw, side)); e = ldg_rlx4(scr + dual_near(G_MOD, 4 * 1152 + vecw, side));
            bad = bad4(d, tag) | bad4(e, tag);
        } while (any_lane(bad & 7u) && ++it < SPIN_LIMIT);
        __syncwarp();
        sh0 = hi2(d.x, d.y); sh1 = hi2(d.z, d.w);
        sc0 = badd2(one2, hi2(e.x, e.y)); sc1 = badd2(one2, hi2(e.z, e.w));
    }
    if (vw < 8) {
        uint4 qf[4];
#pragma unroll
        for (int i = 0; i < 4; i++) qf[i] = lds128(sb + OFF_QS + r * 80 + i * 16);
        const int mt = vw & 3;
        const uint32_t rowoff = (mt * 16 + r + 8 * (mi & 1)) * 128;
        const uint32_t sw = ((mi >> 1) ^ r) << 4;
        uint32_t mx = 0xff80ff80u;
#pragma unroll 1
        for (int i = (vw >> 2); i < 16; i += 2) {
            mbar_wait(s_full + (IT_K + i) * 8);
            const uint32_t base = sb + k_off(i) + rowoff;
            float c0[4] = {}, c1[4] = {};
            uint32_t a[4];
            ldsm4(a, base + sw);               mma16816(c0, a, qf[0].x, qf[0].y);
            ldsm4(a, base + 8192 + sw);        mma16816(c1, a, qf[2].x, qf[2].y);
            ldsm4(a, base + (sw ^ 32));        mma16816(c0, a, qf[0].z, qf[0].w);
            ldsm4(a, base + 8192 + (sw ^ 32)); mma16816(c1, a, qf[2].z, qf[2].w);
            ldsm4(a, base + (sw ^ 64));        mma16816(c0, a, qf[1].x, qf[1].y);
            ldsm4(a, base + 8192 + (sw ^ 64)); mma16816(c1, a, qf[3].x, qf[3].y);
            ldsm4(a, base + (sw ^ 96));        mma16816(c0, a, qf[1].z, qf[1].w);
            ldsm4(a, base + 8192 + (sw ^ 96)); mma16816(c1, a, qf[3].z, qf[3].w);
            __syncwarp();
            if (lane == 0) mbar_arrive(s_empty + (EM_K + i) * 8);
            const float scl = 0.08838834764831845f;
            uint32_t u0 = pack2(c0[0] + c1[0], c0[1] + c1[1]), u1 = pack2(c0[2] + c1[2], c0[3] + c1[3]);
            u0 = pack2(bflo(u0) * scl, bfhi(u0) * scl); u1 = pack2(bflo(u1) * scl, bfhi(u1) * scl);
            mx = bmax2(mx, bmax2(u0, u1));
            if (t == 0) {
                const uint32_t pa = sb + OFF_S + (i * 64 + 16 * (g >> 1) + 4 * mt + bat) * 4;
                sts32(pa, u0); sts32(pa + 8, u1);
            }
            if (i == PH_K && tid < 4) stg_ph(scr + G_ML + c * 8 + (tid & 1) * 4 + (tid & 2) * (HALF / 2));
        }
#pragma unroll
        for (int o = 4; o <= 16; o <<= 1) mx = bmax2(mx, __shfl_xor_sync(0xffffffffu, mx, o));
        if (lane == 0) sts32(sb + OFF_WMX + vw * 4, mx);
    }
    bar_consumers();
    {
        const float L2E = 1.4426950408889634f;
        uint4 sv = make_uint4(0, 0, 0, 0);
        float m0 = 0.f, m1 = 0.f;
        if (vw < 8) {
            uint4 ma = lds128(sb + OFF_WMX), mb = lds128(sb + OFF_WMX + 16);
            const uint32_t mx = bmax2(bmax2(bmax2(ma.x, ma.y), bmax2(ma.z, ma.w)), bmax2(bmax2(mb.x, mb.y), bmax2(mb.z, mb.w)));
            m0 = bflo(mx); m1 = bfhi(mx);
            sv = lds128(sb + OFF_S + tid * 16);
            float e0 = (ex2((bflo(sv.x) - m0) * L2E) + ex2((bflo(sv.y) - m0) * L2E)) + (ex2((bflo(sv.z) - m0) * L2E) + ex2((bflo(sv.w) - m0) * L2E));
            float e1 = (ex2((bfhi(sv.x) - m1) * L2E) + ex2((bfhi(sv.y) - m1) * L2E)) + (ex2((bfhi(sv.z) - m1) * L2E) + ex2((bfhi(sv.w) - m1) * L2E));
#pragma unroll
            for (int o = 16; o > 0; o >>= 1) { e0 += shx(e0, o); e1 += shx(e1, o); }
            if (lane == 0) sts64(sb + OFF_WMX + 32 + vw * 8, __float_as_uint(e0), __float_as_uint(e1));
        }
        bar_consumers();
        if (vw == 0) {
            float l0 = 0.f, l1 = 0.f;
#pragma unroll
            for (int w = 0; w < 4; w++) {
                uint4 s = lds128(sb + OFF_WMX + 32 + w * 16);
                l0 += __uint_as_float(s.x) + __uint_as_float(s.z); l1 += __uint_as_float(s.y) + __uint_as_float(s.w);
            }
            if (tid < 4) stg_pkt(scr + G_ML + c * 8 + (tid & 1) * 4 + (tid & 2) * (HALF / 2), m0, l0, m1, l1, tag);
            {
                const bool rd = lane < 4 && lane != sp;
                uint4 v = make_uint4(rd ? 2u : tag, 0, 0, 0);
                int it = 0;
                do { ldg_pkt_if(v, scr + G_ML + near_half(G_ML, side) + (kvh * 8 + (lane & 3) * 2 + bb) * 8, (v.x ^ tag) & 7u); }
                while (any_lane((v.x ^ tag) & 7u) && ++it < SPIN_LIMIT);
                if (rd) { m0 = untagf(v.x); l0 = __uint_as_float(v.y); m1 = __uint_as_float(v.z); l1 = __uint_as_float(v.w); }
            }
            float g0 = fmaxf(m0, shx(m0, 1)), g1 = fmaxf(m1, shx(m1, 1));
            g0 = fmaxf(g0, shx(g0, 2)); g1 = fmaxf(g1, shx(g1, 2));
            l0 *= ex2((m0 - g0) * L2E); l1 *= ex2((m1 - g1) * L2E);
            l0 += shx(l0, 1); l1 += shx(l1, 1);
            l0 += shx(l0, 2); l1 += shx(l1, 2);
            if (lane == 0)
                sts128(sb + OFF_WMX + 96, __float_as_uint(g0), __float_as_uint(g1), __float_as_uint(__frcp_rn(l0)), __float_as_uint(__frcp_rn(l1)));
        }
        bar_consumers();
        if (vw < 8) {
            const uint4 gs = lds128(sb + OFF_WMX + 96);
            const float g0 = __uint_as_float(gs.x), g1 = __uint_as_float(gs.y), i0 = __uint_as_float(gs.z), i1 = __uint_as_float(gs.w);
            const uint32_t a0 = pack2(ex2((bflo(sv.x) - g0) * L2E) * i0, ex2((bflo(sv.y) - g0) * L2E) * i0);
            const uint32_t a1 = pack2(ex2((bflo(sv.z) - g0) * L2E) * i0, ex2((bflo(sv.w) - g0) * L2E) * i0);
            const uint32_t b0 = pack2(ex2((bfhi(sv.x) - g1) * L2E) * i1, ex2((bfhi(sv.y) - g1) * L2E) * i1);
            const uint32_t b1 = pack2(ex2((bfhi(sv.z) - g1) * L2E) * i1, ex2((bfhi(sv.w) - g1) * L2E) * i1);
            sts64(sb + OFF_P + tid * 8, a0, a1); sts64(sb + OFF_P + PSTR + tid * 8, b0, b1);
        }
        bar_consumers();
    }
    const uint32_t rsw = ((mi & 1) ^ r) << 4;
    unsigned sidew = 2u;
    if (vw < 8) {
        float c0[4] = {}, c1[4] = {};
        const uint32_t vo = (vw >> 2) * 8192 + (r + 8 * (mi >> 1)) * 128 + ((((2 * vw + (mi & 1)) & 7) ^ r) << 4);
        const uint32_t pa = sb + OFF_P + bat * PSTR + t * 32;
#pragma unroll 1
        for (int i = 0; i < 16; i++) {
            uint4 pb0 = lds128(pa + i * 128), pb1 = lds128(pa + i * 128 + 16);
            mbar_wait(s_full + (IT_V + i) * 8);
            const uint32_t base = sb + v_off(i) + vo;
            uint32_t a0[4], a1[4], a2[4], a3[4];
            ldsm4t(a0, base); ldsm4t(a1, base + 2048); ldsm4t(a2, base + 4096); ldsm4t(a3, base + 6144);
            mma16816(c0, a0, pb0.x, pb0.y);
            mma16816(c1, a1, pb0.z, pb0.w);
            mma16816(c0, a2, pb1.x, pb1.y);
            mma16816(c1, a3, pb1.z, pb1.w);
            __syncwarp();
            if (lane == 0) mbar_arrive(s_empty + (EM_V + i) * 8);
            if (i == SIDE_V) { mbar_wait(s_empty + EM_PH * 8); sidew = ldg_rlx1(pside); }
        }
        if (t < 2)
            stg_pkt(scr + G_OP + kvh * 4096 + (j >> 2) * 2048 + t * HALF + (j & 3) * 256 + vw * 32 + g * 4,
                    c0[0] + c1[0], c0[1] + c1[1], c0[2] + c1[2], c0[3] + c1[3], tag);
    } else {
        mbar_wait(s_full + (IT_V + SIDE_V) * 8);
        mbar_wait(s_empty + EM_PH * 8);
    }
    {
        int it = 0;
        while (any_lane((sidew ^ tag) & 7u) && ++it < SPIN_LIMIT) sidew = ldg_rlx1(pside);
        ppart += near_half(G_PART + (vw * 16 + t * 4 + (g >> 1)) * 2048, sidew >> 4);
    }
    side = __float_as_uint(ldsf(sb + OFF_WMX + 112));
#pragma unroll 1
    for (int ph = 0; ph < 2; ph++) {
    if (ph) {
    uint32_t ag[4][6][4];
    const uint32_t gub = s_full + (IT_GU + 2 * (vw / 3)) * 8;
    const uint32_t gpitch = wide ? 96 : 64, gsw = wide ? 0 : (r >> 1) << 4;
    const uint32_t gbase = sb + ((mi & 1) ? OFF_U : OFF_G) + (vw * 64 + r + 8 * (mi >> 1)) * gpitch;
    auto load_gu = [&]() {
#pragma unroll
        for (int ks = 0; ks < 4; ks++)
#pragma unroll
            for (int q = 0; q < 4; q++) ldsm4t(ag[ks][q], gbase + ks * 16 * gpitch + ((q << 4) ^ gsw));
        if (wide) {
#pragma unroll
            for (int ks = 0; ks < 4; ks++)
#pragma unroll
                for (int q = 4; q < 6; q++) ldsm4t(ag[ks][q], gbase + ks * 1536 + q * 16);
        }
    };
    bool gpre;
    while (true) {
        gpre = __all_sync(0xffffffffu, mbar_test(gub) && mbar_test(gub + 8));
        if (gpre || __all_sync(0xffffffffu, mbar_test(s_empty + EM_X1 * 8))) break;
    }
    if (gpre) {
        load_gu();
        mbar_wait(s_empty + EM_X1 * 8);
    }
    {
        uint4 v;
        int it = 0;
        const int xw = G_X1 + (vw >> 3) * 2048 + (c & (XREP - 1)) * 4096;
        const unsigned* px = scr + xw + near_half(xw, side) + (vecw & 1023);
        do { v = ldg_rlx4(px); } while (any_lane(bad4(v, tag) & 7u) && ++it < SPIN_LIMIT);
        xw0 = hi2(v.x, v.y); xw1 = hi2(v.z, v.w);
        ln_stage1(xw0, xw1, st2, vw, lane);
        bar_consumers();
        uint32_t y0, y1;
        ln_stage2(ln_load(st2), xw0, xw1, y0, y1);
        aw0 = badd2(bmul2(y0, sc0), sh0); aw1 = badd2(bmul2(y1, sc1), sh1);
        uint32_t bf[4][2];
        make_bfrags(bf, aw0, aw1, r);
        if (!gpre) { mbar_wait(gub); mbar_wait(gub + 8); load_gu(); }
        float cc[6][4] = {};
#pragma unroll
        for (int ks = 0; ks < 4; ks++)
#pragma unroll
            for (int q = 0; q < 4; q++) mma16816(cc[q], ag[ks][q], bf[ks][0], bf[ks][1]);
        if (wide) {
#pragma unroll
            for (int ks = 0; ks < 4; ks++)
#pragma unroll
                for (int q = 4; q < 6; q++) mma16816(cc[q], ag[ks][q], bf[ks][0], bf[ks][1]);
        }
        if (t == 0) {
#pragma unroll
            for (int q = 0; q < 6; q++) sts128f(sb + OFF_RED + vw * 768 + q * 128 + g * 16, cc[q]);
        }
        bar_consumers();
        if (tid < 192) {
            float sv[NCW];
#pragma unroll
            for (int w = 0; w < NCW; w++) sv[w] = ldsf(sb + OFF_RED + w * 768 + tid * 4);
            const float s = ((sv[0] + sv[1]) + (sv[2] + sv[3])) + ((sv[4] + sv[5]) + (sv[6] + sv[7])) + sv[8];
            const uint32_t gu = pack2(s, __shfl_down_sync(0xffffffffu, s, 2));
            const float gt = bflo(gu);
            const uint32_t hh = pack2(((gt > 0.f) ? gt : gt * 0.0f) * bfhi(gu), 0.f);
            const int rr = tid >> 2;
            if ((tid & 2) == 0)
                sts16(sb + OFF_FR + ((tid & 1) * 4 + ((rr & 7) >> 1)) * 48 + (rr >> 3) * 4 + (rr & 1) * 2, hh);
        }
    }
    bar_consumers();
    }
    {
        const int di = (vw / 3 + 1) % 3;
        const uint32_t rrow = (r + 8 * (mi >> 1)) * 128;
        const uint32_t b0 = sb + rrow + (ph ? OFF_D + di * DSTR + (vw % 3) * (wide ? 6144 : 4096) : OFF_WO0 + vw * 2048);
        const uint32_t b1 = ph ? b0 + 2048 : sb + rrow + OFF_WO1 + vw * 2048;
        const uint32_t fb0 = s_full + (ph ? IT_WD + di : IT_WO) * 8;
        const bool k3 = ph && wide;
        uint32_t ad[3][4][4];
        mbar_wait(fb0);
#pragma unroll
        for (int mt = 0; mt < 4; mt++) ldsm4t(ad[0][mt], b0 + (rsw ^ (mt * 32)));
        if (!ph) mbar_wait(fb0 + 8);
#pragma unroll
        for (int mt = 0; mt < 4; mt++) ldsm4t(ad[1][mt], b1 + (rsw ^ (mt * 32)));
        if (k3) {
#pragma unroll
            for (int mt = 0; mt < 4; mt++) ldsm4t(ad[2][mt], b0 + 4096 + (rsw ^ (mt * 32)));
        }
        if (!ph) asm volatile("bar.sync 3, 352;" ::: "memory");
        const uint4 fr = lds128(sb + OFF_FR + r * 48);
        const uint2 f2 = lds64(sb + OFF_FR + r * 48 + 16);
        float cc[4][4] = {};
#pragma unroll
        for (int mt = 0; mt < 4; mt++) mma16816(cc[mt], ad[0][mt], fr.x, fr.y);
#pragma unroll
        for (int mt = 0; mt < 4; mt++) mma16816(cc[mt], ad[1][mt], fr.z, fr.w);
        if (k3) {
#pragma unroll
            for (int mt = 0; mt < 4; mt++) mma16816(cc[mt], ad[2][mt], f2.x, f2.y);
        }
        publish_partials(ppart, t, cc, tag | (ph * 4u));
    }
    }
    if (vw / 3 == c / 48) asm volatile("bar.arrive 5, 128;" ::: "memory");
    if (vw >= 6 && c < 16) asm volatile("bar.arrive 7, 128;" ::: "memory");
}

typedef CUresult (*EncodeFn)(CUtensorMap*, CUtensorMapDataType, cuuint32_t, void*, const cuuint64_t*, const cuuint64_t*,
                             const cuuint32_t*, const cuuint32_t*, CUtensorMapInterleave, CUtensorMapSwizzle,
                             CUtensorMapL2promotion, CUtensorMapFloatOOBfill);

void make_map(EncodeFn enc, CUtensorMap* m, const void* p, cuuint64_t d0, cuuint64_t d1, cuuint64_t d2,
              cuuint64_t s1, cuuint64_t s2, cuuint32_t b0, cuuint32_t b1, cuuint32_t b2, CUtensorMapSwizzle sw,
              CUtensorMapL2promotion pr = CU_TENSOR_MAP_L2_PROMOTION_L2_128B) {
    cuuint64_t dims[3] = {d0, d1, d2};
    cuuint64_t str[2] = {s1, s2};
    cuuint32_t box[3] = {b0, b1, b2};
    cuuint32_t es[3] = {1, 1, 1};
    enc(m, CU_TENSOR_MAP_DATA_TYPE_BFLOAT16, 3, const_cast<void*>(p), dims, str, box, es,
        CU_TENSOR_MAP_INTERLEAVE_NONE, sw, pr, CU_TENSOR_MAP_FLOAT_OOB_FILL_NONE);
}

}

extern "C" void kernel_launch(void* const* d_in, const int* in_sizes, int n_in, void* d_out, int out_size) {
    (void)in_sizes; (void)n_in; (void)out_size;
    void* fn = nullptr;
    cudaDriverEntryPointQueryResult qr;
    cudaGetDriverEntryPoint("cuTensorMapEncodeTiled", &fn, cudaEnableDefault, &qr);
    EncodeFn enc = (EncodeFn)fn;
    cudaFuncSetAttribute(fused_block_kernel, cudaFuncAttributeMaxDynamicSharedMemorySize, SMEM_BYTES);

    const void *x = d_in[0], *kc = d_in[1], *vc = d_in[2], *wq = d_in[3], *wo = d_in[4];
    const void *wg = d_in[6], *wu = d_in[7], *wd = d_in[8], *cc = d_in[9], *wmod = d_in[10];
    const CUtensorMapSwizzle S128 = CU_TENSOR_MAP_SWIZZLE_128B, S64 = CU_TENSOR_MAP_SWIZZLE_64B, S0 = CU_TENSOR_MAP_SWIZZLE_NONE;
    void* raw = nullptr;
    cudaGetSymbolAddress(&raw, g_raw);
    unsigned* scr = (unsigned*)(((uintptr_t)raw + 0x1fffff) & ~(uintptr_t)0x1fffff);
    Maps m;
    make_map(enc, &m.m[M_K], kc, 64, 32ull * 32768, 2, 256, 128, 64, 64, 2, S128, CU_TENSOR_MAP_L2_PROMOTION_L2_256B);
    make_map(enc, &m.m[M_V], vc, 64, 32ull * 32768, 2, 256, 128, 64, 64, 2, S128, CU_TENSOR_MAP_L2_PROMOTION_L2_256B);
    make_map(enc, &m.m[M_WMOD], wmod, 3456, 144, 4, 3456 * 2, 3456 * 2 * 144, 32, 144, 2, S64);
    make_map(enc, &m.m[M_WQ], wq, 4096, 144, 4, 4096 * 2, 4096 * 2 * 144, 32, 144, 2, S64);
    make_map(enc, &m.m[M_WG], wg, 4608, 576, 1, 4608 * 2, 4608 * 2 * 576, 32, 192, 1, S64);
    make_map(enc, &m.m[M_WU], wu, 4608, 576, 1, 4608 * 2, 4608 * 2 * 576, 32, 192, 1, S64);
    make_map(enc, &m.m[M_WG48], wg, 4608, 576, 1, 4608 * 2, 4608 * 2 * 576, 48, 192, 1, S0);
    make_map(enc, &m.m[M_WU48], wu, 4608, 576, 1, 4608 * 2, 4608 * 2 * 576, 48, 192, 1, S0);
    make_map(enc, &m.m[M_WO], wo, 64, 4096, 9, 1152, 128, 64, 16, 9, S128);
    make_map(enc, &m.m[M_WD], wd, 64, 4608, 9, 1152, 128, 64, 32, 3, S128);
    make_map(enc, &m.m[M_WD48], wd, 64, 4608, 9, 1152, 128, 64, 48, 3, S128);
    fused_block_kernel<<<NCTA, NTHR, SMEM_BYTES>>>(m, (const __nv_bfloat16*)x, (const __nv_bfloat16*)cc,
                                                   (const __nv_bfloat16*)kc, (__nv_bfloat16*)d_out, scr);
}
```

```cpp
#include <cuda_runtime.h>
#include <cuda.h>
#include <cuda_bf16.h>
#include <stdint.h>

namespace {

constexpr int DM = 576;
constexpr int NCTA = 128;
constexpr int NCW = 9;
constexpr int NTHR = (NCW + 3) * 32;
constexpr int NMOD = 108;

constexpr int WIN_MAIN = 4;
constexpr int WIN_TAIL = 3;
constexpr int PACE_GBS = 3185;
constexpr int PACE_LEAD = 19456;
constexpr int EARLY_PF = 8192;
constexpr int DELAY_B = 300;
constexpr int XREP = 2;
constexpr int PH_K = 0;
constexpr int PH_V = 0;
constexpr int SIDE_V = 6;
constexpr int NPROBE0 = 3, NPROBE = 10;

constexpr int IT_WMOD = 0, IT_WQ = 2, IT_K = 4, IT_V = 20, IT_WO = 36, IT_GU = 38, IT_WD = 44, N_IT = 47;
constexpr int EM_WMOD = 0, EM_WQ = 1, EM_K = 2, EM_V = 18, EM_PH = 34, EM_X1 = 35, EM_SD = 36, N_EM = 37;

constexpr int RING = 13 * 16384;
constexpr int OFF_WMOD = 0, OFF_WQ = 36864, OFF_K0 = 73728;
constexpr int OFF_WO0 = 194560, OFF_WO1 = 0, OFF_G = 18432, OFF_U = 73728;
constexpr int OFF_D = 129024, DSTR = 18432;
constexpr int PSTR = 2064;
constexpr int OFF_P = RING;
constexpr int OFF_S = OFF_P + 4160;
constexpr int OFF_RED = OFF_S + 4096;
constexpr int OFF_QS = OFF_RED + 6912;
constexpr int OFF_FR = OFF_QS + 640;
constexpr int OFF_STAT = OFF_FR + 384;
constexpr int OFF_WMX = OFF_STAT + 320;
constexpr int OFF_BAR = OFF_WMX + 128;
constexpr int SMEM_USED = OFF_BAR + (N_IT + N_EM) * 8;
constexpr int SMEM_BYTES = SMEM_USED + 1024;
static_assert(SMEM_BYTES <= 232448, "smem");

struct Maps { CUtensorMap m[11]; };
enum { M_K, M_V, M_WMOD, M_WQ, M_WO, M_WG, M_WU, M_WD, M_WG48, M_WU48, M_WD48 };

constexpr int HALF = 1024;
constexpr int G_PART = 0;
constexpr int G_OP = G_PART + 144 * 2048;
constexpr int G_X1 = G_OP + 16 * 4096;
constexpr int G_PROBE = G_X1 + XREP * 4096;
constexpr int G_SIDE = G_PROBE + 2048;
constexpr int G_EPOCH = G_SIDE + 1024;
constexpr int G_MOD = G_EPOCH + 1024;
constexpr int G_Q = G_MOD + 7 * 2048;
constexpr int G_ML = G_Q + 8 * 2048;
constexpr int G_WORDS = G_ML + 2048;
static_assert(G_MOD % 2048 == 0 && G_OP % 2048 == 0 && G_X1 % 2048 == 0 && G_PROBE % 2048 == 0, "halves");
static_assert(G_WORDS * 4 <= (2 << 20), "scratch must fit one 2 MB page");
__device__ __align__(128) unsigned g_raw[(2 << 20) / 4 + G_WORDS];
__device__ __forceinline__ int near_half(int w, unsigned side) { return ((__popc(w & 0x2C800) ^ side) & 1) << 10; }
__device__ __forceinline__ int dual(int base, int i) { return base + i + (i & ~1023); }
__device__ __forceinline__ int dual_near(int base, int i, unsigned side) { const int w = dual(base, i); return w + near_half(w, side); }

constexpr int SPIN_LIMIT = 1 << 20;

__device__ __forceinline__ uint32_t smem_u32(const void* p) { return (uint32_t)__cvta_generic_to_shared(p); }
__device__ __forceinline__ void mbar_init(uint32_t bar, int cnt) {
    asm volatile("mbarrier.init.shared::cta.b64 [%0], %1;" ::"r"(bar), "r"(cnt) : "memory");
}
__device__ __forceinline__ void mbar_expect_tx(uint32_t bar, uint32_t bytes) {
    asm volatile("mbarrier.arrive.expect_tx.shared::cta.b64 _, [%0], %1;" ::"r"(bar), "r"(bytes) : "memory");
}
__device__ __forceinline__ void mbar_arrive(uint32_t bar) {
    asm volatile("mbarrier.arrive.shared::cta.b64 _, [%0];" ::"r"(bar) : "memory");
}
__device__ __forceinline__ void mbar_wait(uint32_t bar) {
    asm volatile("{\n.reg .pred p;\nW_%=:\nmbarrier.try_wait.parity.shared::cta.b64 p, [%0], 0;\n@!p bra W_%=;\n}"
                 ::"r"(bar) : "memory");
}
__device__ __forceinline__ uint32_t gtime32() { uint32_t t; asm volatile("mov.u32 %0, %%globaltimer_lo;" : "=r"(t)); return t; }
__device__ __forceinline__ uint64_t policy_stream() {
    uint64_t p; asm("createpolicy.fractional.L2::evict_first.b64 %0, 1.0;" : "=l"(p)); return p;
}
__device__ __forceinline__ void tma3d(uint32_t dst, const CUtensorMap* m, int x, int y, int z, uint32_t bar) {
    asm volatile("cp.async.bulk.tensor.3d.shared::cluster.global.mbarrier::complete_tx::bytes.L2::cache_hint [%0], [%1, {%3, %4, %5}], [%2], %6;"
                 ::"r"(dst), "l"(m), "r"(bar), "r"(x), "r"(y), "r"(z), "l"(policy_stream()) : "memory");
}
__device__ __forceinline__ void bar_consumers() { asm volatile("bar.sync 1, 288;" ::: "memory"); }

__device__ __forceinline__ void ldsm4(uint32_t (&a)[4], uint32_t addr) {
    asm volatile("ldmatrix.sync.aligned.m8n8.x4.shared.b16 {%0,%1,%2,%3}, [%4];"
                 : "=r"(a[0]), "=r"(a[1]), "=r"(a[2]), "=r"(a[3]) : "r"(addr) : "memory");
}
__device__ __forceinline__ void ldsm4t(uint32_t (&a)[4], uint32_t addr) {
    asm volatile("ldmatrix.sync.aligned.m8n8.x4.trans.shared.b16 {%0,%1,%2,%3}, [%4];"
                 : "=r"(a[0]), "=r"(a[1]), "=r"(a[2]), "=r"(a[3]) : "r"(addr) : "memory");
}
__device__ __forceinline__ void mma16816(float (&c)[4], const uint32_t (&a)[4], uint32_t b0, uint32_t b1) {
    asm volatile("mma.sync.aligned.m16n8k16.row.col.f32.bf16.bf16.f32 {%0,%1,%2,%3}, {%4,%5,%6,%7}, {%8,%9}, {%0,%1,%2,%3};"
                 : "+f"(c[0]), "+f"(c[1]), "+f"(c[2]), "+f"(c[3])
                 : "r"(a[0]), "r"(a[1]), "r"(a[2]), "r"(a[3]), "r"(b0), "r"(b1));
}
__device__ __forceinline__ float ldsf(uint32_t a) { float v; asm volatile("ld.shared.f32 %0, [%1];" : "=f"(v) : "r"(a) : "memory"); return v; }
__device__ __forceinline__ uint2 lds64(uint32_t a) {
    uint2 v; asm volatile("ld.shared.v2.u32 {%0,%1}, [%2];" : "=r"(v.x), "=r"(v.y) : "r"(a) : "memory"); return v;
}
__device__ __forceinline__ uint4 lds128(uint32_t a) {
    uint4 v; asm volatile("ld.shared.v4.u32 {%0,%1,%2,%3}, [%4];" : "=r"(v.x), "=r"(v.y), "=r"(v.z), "=r"(v.w) : "r"(a) : "memory"); return v;
}
__device__ __forceinline__ void sts16(uint32_t a, uint32_t v) { asm volatile("st.shared.u16 [%0], %1;" ::"r"(a), "h"((unsigned short)v) : "memory"); }
__device__ __forceinline__ void sts32(uint32_t a, uint32_t v) { asm volatile("st.shared.u32 [%0], %1;" ::"r"(a), "r"(v) : "memory"); }
__device__ __forceinline__ void sts64(uint32_t a, uint32_t x, uint32_t y) { asm volatile("st.shared.v2.u32 [%0], {%1,%2};" ::"r"(a), "r"(x), "r"(y) : "memory"); }
__device__ __forceinline__ void sts128(uint32_t a, uint32_t x, uint32_t y, uint32_t z, uint32_t w) {
    asm volatile("st.shared.v4.u32 [%0], {%1,%2,%3,%4};" ::"r"(a), "r"(x), "r"(y), "r"(z), "r"(w) : "memory");
}
__device__ __forceinline__ void sts128f(uint32_t a, const float (&c)[4]) {
    asm volatile("st.shared.v4.f32 [%0], {%1,%2,%3,%4};" ::"r"(a), "f"(c[0]), "f"(c[1]), "f"(c[2]), "f"(c[3]) : "memory");
}
__device__ __forceinline__ unsigned ldg_rlx1(const unsigned* p) {
    unsigned v; asm volatile("ld.relaxed.gpu.global.u32 %0, [%1];" : "=r"(v) : "l"(p) : "memory"); return v;
}
__device__ __forceinline__ uint4 ldg_rlx4(const unsigned* p) {
    uint4 v; asm volatile("ld.relaxed.gpu.global.v4.u32 {%0,%1,%2,%3}, [%4];" : "=r"(v.x), "=r"(v.y), "=r"(v.z), "=r"(v.w) : "l"(p) : "memory"); return v;
}
__device__ __forceinline__ uint4 ldg_pkt(const unsigned* p) {
    uint4 v;
    asm volatile("{\n.reg .b128 t;\n.reg .b64 lo, hi;\nld.relaxed.gpu.global.b128 t, [%4];\nmov.b128 {lo, hi}, t;\n"
                 "mov.b64 {%0,%1}, lo;\nmov.b64 {%2,%3}, hi;\n}"
                 : "=r"(v.x), "=r"(v.y), "=r"(v.z), "=r"(v.w) : "l"(p) : "memory");
    return v;
}
__device__ __forceinline__ void ldg_pkt_if(uint4& v, const unsigned* a, unsigned p) {
    asm volatile("{\n.reg .pred q;\n.reg .b128 t;\n.reg .b64 lo, hi;\nsetp.ne.u32 q, %5, 0;\n"
                 "mov.b64 lo, {%0,%1};\nmov.b64 hi, {%2,%3};\nmov.b128 t, {lo, hi};\n"
                 "@q ld.relaxed.gpu.global.b128 t, [%4];\nmov.b128 {lo, hi}, t;\n"
                 "mov.b64 {%0,%1}, lo;\nmov.b64 {%2,%3}, hi;\n}"
                 : "+r"(v.x), "+r"(v.y), "+r"(v.z), "+r"(v.w) : "l"(a), "r"(p) : "memory");
}
__device__ __forceinline__ bool any_lane(unsigned x) { return __any_sync(0xffffffffu, x != 0); }
__device__ __forceinline__ void stg_pkt(unsigned* p, float a, float b, float c, float d, unsigned tag) {
    unsigned x = (__float_as_uint(a) & ~7u) | tag;
    asm volatile("{\n.reg .b128 t;\n.reg .b64 lo, hi;\nmov.b64 lo, {%1,%2};\nmov.b64 hi, {%3,%4};\nmov.b128 t, {lo, hi};\n"
                 "st.relaxed.gpu.global.b128 [%0], t;\n}"
                 ::"l"(p), "r"(x), "r"(__float_as_uint(b)), "r"(__float_as_uint(c)), "r"(__float_as_uint(d)) : "memory");
}
__device__ __forceinline__ void stg_rlx1(unsigned* p, unsigned x) { asm volatile("st.relaxed.gpu.global.u32 [%0], %1;" ::"l"(p), "r"(x) : "memory"); }
__device__ __forceinline__ unsigned bad4(const uint4& v, unsigned tag) {
    return ((v.x ^ tag) | (v.y ^ tag)) | ((v.z ^ tag) | (v.w ^ tag));
}
__device__ __forceinline__ float untagf(unsigned w) { return __uint_as_float(w & ~7u); }
__device__ __forceinline__ uint32_t pack2(float lo, float hi) {
    uint32_t r; asm("cvt.rn.bf16x2.f32 %0, %1, %2;" : "=r"(r) : "f"(hi), "f"(lo)); return r;
}
__device__ __forceinline__ float bflo(uint32_t w) { return __uint_as_float(w << 16); }
__device__ __forceinline__ float bfhi(uint32_t w) { return __uint_as_float(w & 0xffff0000u); }
__device__ __forceinline__ uint32_t hi2(uint32_t a, uint32_t b) { return __byte_perm(a, b, 0x7632); }
__device__ __forceinline__ uint32_t badd2(uint32_t a, uint32_t b) { uint32_t r; asm("add.rn.bf16x2 %0, %1, %2;" : "=r"(r) : "r"(a), "r"(b)); return r; }
__device__ __forceinline__ uint32_t bsub2(uint32_t a, uint32_t b) { uint32_t r; asm("sub.rn.bf16x2 %0, %1, %2;" : "=r"(r) : "r"(a), "r"(b)); return r; }
__device__ __forceinline__ uint32_t bmul2(uint32_t a, uint32_t b) { uint32_t r; asm("mul.rn.bf16x2 %0, %1, %2;" : "=r"(r) : "r"(a), "r"(b)); return r; }
__device__ __forceinline__ uint32_t bmax2(uint32_t a, uint32_t b) { uint32_t r; asm("max.bf16x2 %0, %1, %2;" : "=r"(r) : "r"(a), "r"(b)); return r; }
__device__ __forceinline__ float ex2(float x) { float r; asm("ex2.approx.ftz.f32 %0, %1;" : "=f"(r) : "f"(x)); return r; }
__device__ __forceinline__ float rcp(float x) { float r; asm("rcp.approx.ftz.f32 %0, %1;" : "=f"(r) : "f"(x)); return r; }
__device__ __forceinline__ float fsqrt(float x) { float r; asm("sqrt.approx.ftz.f32 %0, %1;" : "=f"(r) : "f"(x)); return r; }
__device__ __forceinline__ float shx(float v, int m) { return __shfl_xor_sync(0xffffffffu, v, m); }

__device__ __forceinline__ uint32_t k_off(int i) { return i < 8 ? OFF_K0 + i * 16384 : (i - 8) * 16384; }
__device__ __forceinline__ uint32_t v_off(int i) { return i < 5 ? (8 + i) * 16384 : (i - 5) * 16384; }

__device__ __forceinline__ void stg_ph(unsigned* p) { stg_pkt(p, 0.f, 0.f, 0.f, 0.f, 2u); }

__device__ __forceinline__ void ln_stage1(uint32_t xw0, uint32_t xw1, uint32_t st, int vw, int lane) {
    const float piv = __shfl_sync(0xffffffffu, bflo(xw0), lane & 4);
    const float d0 = bflo(xw0) - piv, d1 = bfhi(xw0) - piv, d2 = bflo(xw1) - piv, d3 = bfhi(xw1) - piv;
    float s1 = (d0 + d1) + (d2 + d3), s2 = (d0 * d0 + d1 * d1) + (d2 * d2 + d3 * d3);
    s1 += shx(s1, 1); s2 += shx(s2, 1);
    s1 += shx(s1, 2); s2 += shx(s2, 2);
    s1 += shx(s1, 8); s2 += shx(s2, 8);
    s1 += shx(s1, 16); s2 += shx(s2, 16);
    if ((lane & 27) == 0)
        sts64(st + vw * 8, __float_as_uint(piv + s1 * (1.0f / 64.0f)), __float_as_uint(s2 - s1 * s1 * (1.0f / 64.0f)));
}
struct LnStat { uint4 a, b, c, d; uint2 e; };
__device__ __forceinline__ LnStat ln_load(uint32_t st) {
    LnStat s; s.a = lds128(st); s.b = lds128(st + 16); s.c = lds128(st + 32); s.d = lds128(st + 48); s.e = lds64(st + 64);
    return s;
}
__device__ __forceinline__ void ln_stage2(const LnStat& s, uint32_t xw0, uint32_t xw1, uint32_t& y0, uint32_t& y1) {
    const float m[9] = {__uint_as_float(s.a.x), __uint_as_float(s.a.z), __uint_as_float(s.b.x), __uint_as_float(s.b.z),
                        __uint_as_float(s.c.x), __uint_as_float(s.c.z), __uint_as_float(s.d.x), __uint_as_float(s.d.z), __uint_as_float(s.e.x)};
    const float mean = (((m[0] + m[1]) + (m[2] + m[3])) + ((m[4] + m[5]) + (m[6] + m[7])) + m[8]) * (1.0f / NCW);
    const float m2 = ((__uint_as_float(s.a.y) + __uint_as_float(s.a.w)) + (__uint_as_float(s.b.y) + __uint_as_float(s.b.w))) +
                     ((__uint_as_float(s.c.y) + __uint_as_float(s.c.w)) + (__uint_as_float(s.d.y) + __uint_as_float(s.d.w))) + __uint_as_float(s.e.y);
    float d[9];
#pragma unroll
    for (int w = 0; w < 9; w++) d[w] = m[w] - mean;
    const float acc = (d[0] * d[0] + d[1] * d[1] + d[2] * d[2]) + (d[3] * d[3] + d[4] * d[4] + d[5] * d[5]) + (d[6] * d[6] + d[7] * d[7] + d[8] * d[8]);
    const float var = (m2 + 64.0f * acc) * (1.0f / DM);
    const uint32_t mv = pack2(mean, var);
    const float ve = bflo(pack2(bfhi(mv) + 1e-5f, 0.f));
    const float rinv = rcp(bflo(pack2(fsqrt(ve), 0.f)));
    const uint32_t mm = __byte_perm(mv, mv, 0x1010);
    const uint32_t e0 = bsub2(xw0, mm), e1 = bsub2(xw1, mm);
    y0 = pack2(bflo(e0) * rinv, bfhi(e0) * rinv); y1 = pack2(bflo(e1) * rinv, bfhi(e1) * rinv);
}
__device__ __forceinline__ void make_bfrags(uint32_t (&bf)[4][2], uint32_t aw0, uint32_t aw1, int r) {
#pragma unroll
    for (int ks = 0; ks < 4; ks++) {
        bf[ks][0] = __shfl_sync(0xffffffffu, aw0, ks * 8 + r);
        bf[ks][1] = __shfl_sync(0xffffffffu, aw1, ks * 8 + r);
    }
}
__device__ __forceinline__ uint32_t gemv32(uint32_t s_w, uint32_t red, uint32_t fullbar, uint32_t emptybar,
                                           uint32_t aw0, uint32_t aw1, int tid) {
    const int vw = tid >> 5, lane = tid & 31, g = lane >> 2, t = lane & 3, mi = lane >> 3, r = lane & 7;
    uint32_t bf[4][2];
    make_bfrags(bf, aw0, aw1, r);
    if (vw <= 4) mbar_wait(fullbar);
    if (vw >= 4) mbar_wait(fullbar + 8);
    float cc[2][4] = {};
    const uint32_t abase = s_w + (vw * 64 + r + 8 * (mi >> 1)) * 64;
    const uint32_t sw = ((mi & 1) ^ (r >> 1)) << 4;
#pragma unroll
    for (int ks = 0; ks < 4; ks++) {
#pragma unroll
        for (int mt = 0; mt < 2; mt++) {
            uint32_t a[4];
            ldsm4t(a, abase + ks * 1024 + (sw ^ (mt * 32)));
            mma16816(cc[mt], a, bf[ks][0], bf[ks][1]);
        }
    }
    if (t == 0) { sts128f(red + vw * 256 + g * 16, cc[0]); sts128f(red + vw * 256 + 128 + g * 16, cc[1]); }
    __syncwarp();
    if (lane == 0) mbar_arrive(emptybar);
    bar_consumers();
    float s = 0.f;
    if (tid < 64) {
        const uint32_t ra = red + ((tid & 58) | ((tid & 1) << 2) | ((tid >> 2) & 1)) * 4;
#pragma unroll
        for (int w = 0; w < NCW; w++) s += ldsf(ra + w * 256);
    }
    return pack2(0.f, s);
}
__device__ __forceinline__ void publish_partials(unsigned* q, int t, const float (&cc)[4][4], unsigned tag) {
    float v[4];
#pragma unroll
    for (int i = 0; i < 4; i++) {
        const float lo = (t & 1) ? cc[1][i] : cc[0][i], hi = (t & 1) ? cc[3][i] : cc[2][i];
        v[i] = (t & 2) ? hi : lo;
    }
    stg_pkt(q, v[0], v[1], v[2], v[3], tag);
}
__device__ __forceinline__ void spin_cycles(unsigned n) {
    const unsigned c0 = clock();
    while ((unsigned)clock() - c0 < n) { }
}
__device__ __forceinline__ float reduce_unit(const unsigned* q, int lane, unsigned tag) {
    uint4 v[8];
#pragma unroll
    for (int i = 0; i < 8; i++) v[i] = ldg_pkt(q + i * 128);
    int it = 0;
    unsigned y[8];
    while (true) {
#pragma unroll
        for (int i = 0; i < 8; i++) y[i] = v[i].x ^ tag;
        const bool more = any_lane((((y[0] | y[1] | y[2]) | (y[3] | y[4] | y[5])) | (y[6] | y[7])) & 7u);
        if (!more || ++it >= SPIN_LIMIT) break;
#pragma unroll
        for (int i = 0; i < 8; i++) ldg_pkt_if(v[i], q + i * 128, y[i] & 7u);
    }
#define SUM8(e) (((e(0) + e(1)) + (e(2) + e(3))) + ((e(4) + e(5)) + (e(6) + e(7))))
#define EX(i) __uint_as_float(y[i])
#define EY(i) __uint_as_float(v[i].y)
#define EZ(i) __uint_as_float(v[i].z)
#define EW(i) __uint_as_float(v[i].w)
    const float s0 = SUM8(EX), s1 = SUM8(EY), s2 = SUM8(EZ), s3 = SUM8(EW);
    const bool h8 = lane & 2, bat = lane & 4;
    const float k0 = (h8 ? s2 : s0) + shx(h8 ? s0 : s2, 2);
    const float k1 = (h8 ? s3 : s1) + shx(h8 ? s1 : s3, 2);
    float k = (bat ? k1 : k0) + shx(bat ? k0 : k1, 4);
    k += shx(k, 8);
    k += shx(k, 16);
    return k;
}

__global__ void __launch_bounds__(NTHR, 1)
fused_block_kernel(const __grid_constant__ Maps maps, const __nv_bfloat16* __restrict__ xin,
                   const __nv_bfloat16* __restrict__ cin, const __nv_bfloat16* __restrict__ kcache,
                   __nv_bfloat16* __restrict__ out, unsigned* const scr) {
    extern __shared__ unsigned char smem_raw[];
    const int c = blockIdx.x;
    const int kvh = c >> 3, j = c & 7, bb = j & 1, sp = j >> 1;
    const bool wide = j >= 6;
    const int f0 = kvh * 288 + (wide ? 48 * j - 96 : 32 * j);
    const int kvrow0 = (bb * 16 + kvh) * 32768 + 28672 + sp * 64;
    const int kvstep = 256;
    if (threadIdx.x == 0)
        asm volatile("cp.async.bulk.prefetch.L2.global.L2::cache_hint [%0], %1, %2;"
                     ::"l"((const char*)kcache + (size_t)kvrow0 * 256), "r"(EARLY_PF), "l"(policy_stream()) : "memory");
    const uint32_t sb = (smem_u32(smem_raw) + 1023u) & ~1023u;
    const int warp = threadIdx.x >> 5, lane = threadIdx.x & 31;
    const uint32_t s_full = sb + OFF_BAR, s_empty = s_full + N_IT * 8;

    if (warp == NCW) {
        const uint32_t t0 = gtime32();
        const int first = (c < NMOD) ? 0 : 2;
        if (lane == 0) {
#pragma unroll
            for (int i = 0; i < 2; i++) mbar_init(s_full + (first + i) * 8, 1);
            asm volatile("fence.proxy.async.shared::cta;" ::: "memory");
#pragma unroll
            for (int i = 0; i < 2; i++) {
                const uint32_t bar = s_full + (first + i) * 8;
                mbar_expect_tx(bar, 18432);
                tma3d(sb + (first + i) * 18432, &maps.m[M_WMOD + (first >> 1)], c * 32, 0, i * 2, bar);
            }
        }
        __syncwarp();
        uint32_t w0[2], w1[2], w2[2];
#pragma unroll
        for (int h = 0; h < 2; h++) {
            const int i = lane + 32 * h;
            int off, map, dep = -1, x = 0, y = 0, z = 0, sz = 36, cum;
            if (i < IT_K) {
                off = i * 18432; map = M_WMOD + (i >> 1); x = c * 32; z = (i & 1) * 2; cum = 31104 + (i - 2) * 18432;
            } else if (i < IT_V) {
                const int k = i - IT_K;
                off = k_off(k); map = M_K; y = kvrow0 + k * kvstep; sz = 32; cum = 67968 + k * 16384;
                if (k == 8 && c < NMOD) dep = EM_WMOD;
                if (k == 10) dep = EM_WQ;
                if (k >= 12) dep = EM_K + k - 12;
            } else if (i < IT_WO) {
                const int k = i - IT_V;
                off = v_off(k); map = M_V; y = kvrow0 + k * kvstep; sz = 32; cum = 330112 + k * 16384;
                dep = EM_K + 3 + k + (k < 4);
            } else if (i < IT_GU) {
                const int k = i - IT_WO;
                off = k ? OFF_WO1 : OFF_WO0; map = M_WO; y = kvh * 256 + k * 128 + j * 16; dep = EM_V + 4 + 2 * k;
                cum = 592256 + k * 18432;
            } else if (i < IT_WD) {
                const int k = i - IT_GU;
                sz = wide ? 36 : 24;
                off = ((k & 1) ? OFF_U : OFF_G) + (k >> 1) * sz * 512; map = M_WG + (k & 1) + (wide ? 3 : 0);
                x = f0; y = (k >> 1) * 192; dep = EM_V + 5 + ((off + sz * 512 - 1) >> 14);
                cum = 629120 + k * 13824;
            } else {
                const int k = i - IT_WD;
                off = OFF_D + k * DSTR; map = wide ? M_WD48 : M_WD; y = f0; z = ((k + 2) % 3) * 3; sz = wide ? 36 : 24; dep = EM_V + (k ? 15 : 13);
                cum = 712064 + k * 13824;
            }
            const int stag = (i >= IT_K && i < IT_WO) ? (((kvh * 2 + bb) * 13) & 31) * 512
                           : i < IT_GU ? ((c * 37) & 127) * 128
                           : wide ? (((kvh * 2 + j) * 13) & 31) * 144 : 4608 + (((kvh * 6 + j) * 37) % 96) * 96;
            cum += EARLY_PF - min(max(cum - 67968, 0), EARLY_PF);
            const int due = (int)((float)max(cum + stag - PACE_LEAD, 0) * (128.0f / PACE_GBS));
            w0[h] = off | (map << 18) | ((dep + 1) << 22) | (z << 28);
            w1[h] = y | (sz << 24);
            w2[h] = x | (due << 13);
        }
        asm volatile("bar.sync 2, 384;" ::: "memory");
        uint32_t fb = s_full;
        asm volatile("" : "+r"(fb));
#pragma unroll 1
        for (int i = first + 2; i < N_IT; i++) {
            const bool hi = i >= 32;
            const uint32_t a = __shfl_sync(0xffffffffu, hi ? w0[1] : w0[0], i);
            const uint32_t b = __shfl_sync(0xffffffffu, hi ? w1[1] : w1[0], i);
            const uint32_t x = __shfl_sync(0xffffffffu, hi ? w2[1] : w2[0], i);
            if (lane == 0) {
                const uint32_t bar = fb + i * 8;
                const int win = (i >= IT_GU) ? WIN_TAIL : WIN_MAIN;
                const int dep = (a >> 22) & 63;
                const uint32_t due = t0 + (x >> 13);
                if (dep) mbar_wait(fb + (N_IT - 1 + dep) * 8);
                if (i - win >= first) mbar_wait(bar - win * 8);
                while ((int)(gtime32() - due) < 0) { }
                mbar_expect_tx(bar, (b >> 24) * 512);
                tma3d(fb - OFF_BAR + (a & 0x3ffff), &maps.m[(a >> 18) & 15], x & 0x1fff, b & 0xffffff, a >> 28, bar);
            }
            __syncwarp();
        }
        return;
    }

    const int g = lane >> 2, t = lane & 3, mi = lane >> 3, r = lane & 7;
    const int bat = g & 1;

    if (warp > NCW) {
        const bool first = warp == NCW + 1, active = first || c < 16;
        const int unit = first ? c : NCTA + c;
        const int rcol = (unit >> 2) * 16 + (unit & 3) * 2 + (lane & 1) + (lane & 2) * 4 + bat * DM;
        const unsigned ep = ldg_rlx1(scr + G_EPOCH);
        uint32_t xold = 0, ga = 0, gb = 0;
        if (active) xold = __ldg((const unsigned short*)xin + rcol);
        if (!first) asm volatile("bar.sync 2, 384;" ::: "memory");
        const unsigned tag = (ep + 1u) & 1u;
        unsigned side = 0;
        const int x1w = G_X1 + (unit >> 7) * 2048 + (unit & 127) * 8 + r + (lane & 8) * (HALF / 8) + (lane >> 4) * 4096;
        if (first) {
            unsigned* pr = scr + G_PROBE + c * 8;
            if (lane < 16) stg_rlx1(pr + r + (lane & 8) * (HALF / 8), 0u);
            __syncwarp();
            asm volatile("bar.arrive 2, 384;" ::: "memory");
            unsigned best0 = ~0u, best1 = ~0u, v = 0, cp = 0;
#pragma unroll 1
            for (int i = 0; i <= 2 * NPROBE; i++) {
                if (lane == 0) {
                    asm volatile("atom.relaxed.gpu.global.add.u32 %0, [%1], 1;" : "=r"(v) : "l"(pr + (i & 1) * HALF + (v >> 31)) : "memory");
                    const unsigned cn = clock(), d = cn - cp;
                    cp = cn;
                    if (i & 1) best0 = min(best0, d); else if (i) best1 = min(best1, d);
                    side = (best1 < best0) ^ (__popc(G_PROBE & 0x2C800) & 1);
                }
                if (i == 2 * NPROBE0) {
                    asm volatile("bar.sync 6, 64;" ::: "memory");
                    if (lane == 0) { sts32(sb + OFF_WMX + 116, side); mbar_arrive(s_empty + EM_SD * 8); }
                }
            }
            if (lane == 0) sts32(sb + OFF_WMX + 112, side);
            side = __shfl_sync(0xffffffffu, side, 0);
            mbar_wait(s_full + (IT_V + PH_V) * 8);
#pragma unroll 1
            for (int u = c; u < 144; u += NCTA) {
                unsigned* q = scr + G_PART + u * 2048 + near_half(G_PART + u * 2048, side) + lane * 4;
#pragma unroll
                for (int i = 0; i < 8; i++) stg_ph(q + i * 128);
#pragma unroll
                for (int i = 0; i < XREP; i += 2) stg_rlx1(scr + x1w + (u >> 7) * 2048 + i * 4096, 2u);
            }
            unsigned* o = scr + G_OP + kvh * 4096 + (j >> 2) * 2048 + (j & 3) * 256 + lane * 4;
            stg_ph(o); stg_ph(o + 128); stg_ph(o + HALF); stg_ph(o + HALF + 128);
            __threadfence();
            __syncwarp();
            if (lane < 8) stg_rlx1(scr + G_SIDE + c * 8 + lane, (side << 4) | tag);
            if (lane == 0) mbar_arrive(s_empty + EM_PH * 8);
        } else {
            asm volatile("bar.arrive 6, 64;" ::: "memory");
            if (lane < 8) asm volatile("prefetch.tensormap [%0];" ::"l"(&maps.m[lane + ((wide && lane >= M_WG) ? 3 : 0)]) : "memory");
            mbar_wait(s_empty + EM_PH * 8);
            side = __float_as_uint(ldsf(sb + OFF_WMX + 112));
        }
        if (active) {
            int it = 0;
            do {
                ga = ldg_rlx1(scr + dual_near(G_MOD, 2 * 1152 + unit * 8 + r, side));
                gb = ldg_rlx1(scr + dual_near(G_MOD, 5 * 1152 + unit * 8 + r, side));
            } while (any_lane(((ga ^ tag) | (gb ^ tag)) & 7u) && ++it < SPIN_LIMIT);
            ga >>= 16; gb >>= 16;
        }
        __syncwarp();
        if (first) {
            const int ow = G_OP + kvh * 4096 + (g >> 2) * 2048;
            const unsigned* q = scr + ow + near_half(ow, side) + (g & 3) * 256 + j * 32 + t * 8;
            mbar_wait(s_full + (IT_V + 15) * 8);
            uint4 lo, hi;
            int it = 0;
            do { lo = ldg_pkt(q); hi = ldg_pkt(q + 4); } while (any_lane(((lo.x ^ tag) | (hi.x ^ tag)) & 7u) && ++it < SPIN_LIMIT);
            float o[8] = {untagf(lo.x), __uint_as_float(lo.y), __uint_as_float(lo.z), __uint_as_float(lo.w),
                          untagf(hi.x), __uint_as_float(hi.y), __uint_as_float(hi.z), __uint_as_float(hi.w)};
            __syncwarp();
#pragma unroll
            for (int sft = 8; sft <= 16; sft <<= 1) {
#pragma unroll
                for (int i = 0; i < 8; i++) o[i] += shx(o[i], sft);
            }
            if (lane < 8)
                sts128(sb + OFF_FR + lane * 48, pack2(o[0], o[4]), pack2(o[2], o[6]), pack2(o[1], o[5]), pack2(o[3], o[7]));
        }
        asm volatile("bar.sync 3, 352;" ::: "memory");
        const unsigned* q = scr + G_PART + unit * 2048 + near_half(G_PART + unit * 2048, side) + lane * 4;
        if (!active) return;
#pragma unroll 1
        for (int ph = 0; ph < 2; ph++) {
            if (ph) asm volatile("bar.sync %0, 128;" ::"r"(first ? 5 : 7) : "memory");
            else spin_cycles(DELAY_B);
            const float k = reduce_unit(q, lane, tag | (ph * 4u));
            xold = badd2(xold, bmul2(ga, pack2(k, 0.f))) & 0xffffu;
            ga = gb;
            if (ph) {
                if (lane < 8) ((unsigned short*)out)[rcol] = (unsigned short)xold;
            } else {
#pragma unroll
                for (int i = 0; i < XREP; i += 2) stg_rlx1(scr + x1w + i * 4096, (xold << 16) | tag);
                if (first && lane == 0) mbar_arrive(s_empty + EM_X1 * 8);
            }
        }
        if (c == 0 && first && lane == 0) stg_rlx1(scr + G_EPOCH, ep + 1u);
        return;
    }

    const int vw = warp, tid = threadIdx.x;
    const int vecw = tid * 4 - (lane & 7) * 4 + t * 8 + bat * 4;
    unsigned* ppart = scr + G_PART + (vw * 16 + t * 4 + (g >> 1)) * 2048 + c * 8 + bat * 4;
    const unsigned* const pside = scr + G_SIDE + ((vw * 16 + t * 4 + (g >> 1)) & 127) * 8;
    const int qword = dual(G_Q, bat * 4096 + c * 32 + (tid >> 3) * 4 + t), mword = dual(G_MOD, c * 64 + (tid & 63));
    const uint32_t one2 = 0x3f803f80u;

    const unsigned ep = ldg_rlx1(scr + G_EPOCH);
    if (tid < 64) {
        if (c < NMOD) { stg_rlx1(scr + mword, 2u); stg_rlx1(scr + mword + HALF, 2u); }
        stg_rlx1(scr + qword, 2u); stg_rlx1(scr + qword + HALF, 2u);
    }
    uint32_t xw0, xw1, aw0, aw1;
    {
        const int col0 = bat * DM + (vw * 4 + mi) * 16 + 2 * t;
        const uint32_t cw0 = __ldg((const unsigned*)(cin + col0)), cw1 = __ldg((const unsigned*)(cin + col0 + 8));
        xw0 = __ldg((const unsigned*)(xin + col0)); xw1 = __ldg((const unsigned*)(xin + col0 + 8));
        if (lane == 0) {
            const int lo = (c < NMOD) ? 2 : 4;
#pragma unroll 1
            for (int i = vw; i < N_IT + N_EM; i += NCW) {
                const int e = i - N_IT;
                if (i >= lo) mbar_init(s_full + i * 8, (e < 0 || e >= EM_PH) ? 1 : (e < EM_K ? NCW : (e < EM_V ? 4 : 8)));
            }
            asm volatile("fence.proxy.async.shared::cta;" ::: "memory");
        }
        __syncwarp();
        asm volatile("bar.sync 2, 384;" ::: "memory");
        float cv[4] = {bflo(cw0), bfhi(cw0), bflo(cw1), bfhi(cw1)};
#pragma unroll
        for (int i = 0; i < 4; i++) cv[i] = cv[i] * rcp(1.0f + ex2(-1.4426950408889634f * cv[i]));
        aw0 = pack2(cv[0], cv[1]); aw1 = pack2(cv[2], cv[3]);
    }
    const unsigned tag = (ep + 1u) & 1u;
    const uint32_t st1 = sb + OFF_STAT + bat * 80, st2 = st1 + 160;
    ln_stage1(xw0, xw1, st1, vw, lane);

    if (c < NMOD) {
        const uint32_t m = gemv32(sb + OFF_WMOD, sb + OFF_RED, s_full + IT_WMOD * 8, s_empty + EM_WMOD * 8, aw0, aw1, tid);
        if (tid < 64) { stg_rlx1(scr + mword, m | tag); stg_rlx1(scr + mword + HALF, m | tag); }
    } else {
        bar_consumers();
    }
    mbar_wait(s_empty + EM_SD * 8);
    unsigned side = __float_as_uint(ldsf(sb + OFF_WMX + 116));
    {
        uint32_t y0, y1;
        ln_stage2(ln_load(st1), xw0, xw1, y0, y1);
        uint4 a, b;
        int it = 0;
        const unsigned *pa = scr + dual_near(G_MOD, vecw, side), *pb = scr + dual_near(G_MOD, 1152 + vecw, side);
        do { a = ldg_rlx4(pa); b = ldg_rlx4(pb); }
        while (any_lane((bad4(a, tag) | bad4(b, tag)) & 7u) && ++it < SPIN_LIMIT);
        __syncwarp();
        aw0 = badd2(bmul2(y0, badd2(one2, hi2(b.x, b.y))), hi2(a.x, a.y));
        aw1 = badd2(bmul2(y1, badd2(one2, hi2(b.z, b.w))), hi2(a.z, a.w));
        const uint32_t q = gemv32(sb + OFF_WQ, sb + OFF_RED + 2304, s_full + IT_WQ * 8, s_empty + EM_WQ * 8, aw0, aw1, tid);
        if (tid < 64) {
            stg_rlx1(scr + qword, q | tag); stg_rlx1(scr + qword + HALF, q | tag);
            uint4 v;
            int it = 0;
            const unsigned* pq = scr + dual_near(G_Q, bb * 4096 + kvh * 256 + tid * 4, side);
            do { v = ldg_rlx4(pq); } while (any_lane(bad4(v, tag) & 7u) && ++it < SPIN_LIMIT);
            sts64(sb + OFF_QS + (vw * 4 + t) * 80 + g * 8, hi2(v.x, v.y), hi2(v.z, v.w));
        }
        bar_consumers();
    }
    uint32_t sc0, sc1, sh0, sh1;
    {
        uint4 d, e;
        unsigned bad;
        int it = 0;
        do {
            d = ldg_rlx4(scr + dual_near(G_MOD, 3 * 1152 + vecw, side)); e = ldg_rlx4(scr + dual_near(G_MOD, 4 * 1152 + vecw, side));
            bad = bad4(d, tag) | bad4(e, tag);
        } while (any_lane(bad & 7u) && ++it < SPIN_LIMIT);
        __syncwarp();
        sh0 = hi2(d.x, d.y); sh1 = hi2(d.z, d.w);
        sc0 = badd2(one2, hi2(e.x, e.y)); sc1 = badd2(one2, hi2(e.z, e.w));
    }
    if (vw < 8) {
        uint4 qf[4];
#pragma unroll
        for (int i = 0; i < 4; i++) qf[i] = lds128(sb + OFF_QS + r * 80 + i * 16);
        const int mt = vw & 3;
        const uint32_t rowoff = (mt * 16 + r + 8 * (mi & 1)) * 128;
        const uint32_t sw = ((mi >> 1) ^ r) << 4;
        uint32_t mx = 0xff80ff80u;
#pragma unroll 1
        for (int i = (vw >> 2); i < 16; i += 2) {
            mbar_wait(s_full + (IT_K + i) * 8);
            const uint32_t base = sb + k_off(i) + rowoff;
            float c0[4] = {}, c1[4] = {};
            uint32_t a[4];
            ldsm4(a, base + sw);               mma16816(c0, a, qf[0].x, qf[0].y);
            ldsm4(a, base + 8192 + sw);        mma16816(c1, a, qf[2].x, qf[2].y);
            ldsm4(a, base + (sw ^ 32));        mma16816(c0, a, qf[0].z, qf[0].w);
            ldsm4(a, base + 8192 + (sw ^ 32)); mma16816(c1, a, qf[2].z, qf[2].w);
            ldsm4(a, base + (sw ^ 64));        mma16816(c0, a, qf[1].x, qf[1].y);
            ldsm4(a, base + 8192 + (sw ^ 64)); mma16816(c1, a, qf[3].x, qf[3].y);
            ldsm4(a, base + (sw ^ 96));        mma16816(c0, a, qf[1].z, qf[1].w);
            ldsm4(a, base + 8192 + (sw ^ 96)); mma16816(c1, a, qf[3].z, qf[3].w);
            __syncwarp();
            if (lane == 0) mbar_arrive(s_empty + (EM_K + i) * 8);
            const float scl = 0.08838834764831845f;
            uint32_t u0 = pack2(c0[0] + c1[0], c0[1] + c1[1]), u1 = pack2(c0[2] + c1[2], c0[3] + c1[3]);
            u0 = pack2(bflo(u0) * scl, bfhi(u0) * scl); u1 = pack2(bflo(u1) * scl, bfhi(u1) * scl);
            mx = bmax2(mx, bmax2(u0, u1));
            if (t == 0) {
                const uint32_t pa = sb + OFF_S + (i * 64 + 16 * (g >> 1) + 4 * mt + bat) * 4;
                sts32(pa, u0); sts32(pa + 8, u1);
            }
            if (i == PH_K && tid < 4) stg_ph(scr + G_ML + c * 8 + (tid & 1) * 4 + (tid & 2) * (HALF / 2));
        }
#pragma unroll
        for (int o = 4; o <= 16; o <<= 1) mx = bmax2(mx, __shfl_xor_sync(0xffffffffu, mx, o));
        if (lane == 0) sts32(sb + OFF_WMX + vw * 4, mx);
    }
    bar_consumers();
    {
        const float L2E = 1.4426950408889634f;
        uint4 sv = make_uint4(0, 0, 0, 0);
        float m0 = 0.f, m1 = 0.f;
        if (vw < 8) {
            uint4 ma = lds128(sb + OFF_WMX), mb = lds128(sb + OFF_WMX + 16);
            const uint32_t mx = bmax2(bmax2(bmax2(ma.x, ma.y), bmax2(ma.z, ma.w)), bmax2(bmax2(mb.x, mb.y), bmax2(mb.z, mb.w)));
            m0 = bflo(mx); m1 = bfhi(mx);
            sv = lds128(sb + OFF_S + tid * 16);
            float e0 = (ex2((bflo(sv.x) - m0) * L2E) + ex2((bflo(sv.y) - m0) * L2E)) + (ex2((bflo(sv.z) - m0) * L2E) + ex2((bflo(sv.w) - m0) * L2E));
            float e1 = (ex2((bfhi(sv.x) - m1) * L2E) + ex2((bfhi(sv.y) - m1) * L2E)) + (ex2((bfhi(sv.z) - m1) * L2E) + ex2((bfhi(sv.w) - m1) * L2E));
#pragma unroll
            for (int o = 16; o > 0; o >>= 1) { e0 += shx(e0, o); e1 += shx(e1, o); }
            if (lane == 0) sts64(sb + OFF_WMX + 32 + vw * 8, __float_as_uint(e0), __float_as_uint(e1));
        }
        bar_consumers();
        if (vw == 0) {
            float l0 = 0.f, l1 = 0.f;
#pragma unroll
            for (int w = 0; w < 4; w++) {
                uint4 s = lds128(sb + OFF_WMX + 32 + w * 16);
                l0 += __uint_as_float(s.x) + __uint_as_float(s.z); l1 += __uint_as_float(s.y) + __uint_as_float(s.w);
            }
            if (tid < 4) stg_pkt(scr + G_ML + c * 8 + (tid & 1) * 4 + (tid & 2) * (HALF / 2), m0, l0, m1, l1, tag);
            {
                const bool rd = lane < 4 && lane != sp;
                uint4 v = make_uint4(rd ? 2u : tag, 0, 0, 0);
                int it = 0;
                do { ldg_pkt_if(v, scr + G_ML + near_half(G_ML, side) + (kvh * 8 + (lane & 3) * 2 + bb) * 8, (v.x ^ tag) & 7u); }
                while (any_lane((v.x ^ tag) & 7u) && ++it < SPIN_LIMIT);
                if (rd) { m0 = untagf(v.x); l0 = __uint_as_float(v.y); m1 = __uint_as_float(v.z); l1 = __uint_as_float(v.w); }
            }
            float g0 = fmaxf(m0, shx(m0, 1)), g1 = fmaxf(m1, shx(m1, 1));
            g0 = fmaxf(g0, shx(g0, 2)); g1 = fmaxf(g1, shx(g1, 2));
            l0 *= ex2((m0 - g0) * L2E); l1 *= ex2((m1 - g1) * L2E);
            l0 += shx(l0, 1); l1 += shx(l1, 1);
            l0 += shx(l0, 2); l1 += shx(l1, 2);
            if (lane == 0)
                sts128(sb + OFF_WMX + 96, __float_as_uint(g0), __float_as_uint(g1), __float_as_uint(__frcp_rn(l0)), __float_as_uint(__frcp_rn(l1)));
        }
        bar_consumers();
        if (vw < 8) {
            const uint4 gs = lds128(sb + OFF_WMX + 96);
            const float g0 = __uint_as_float(gs.x), g1 = __uint_as_float(gs.y), i0 = __uint_as_float(gs.z), i1 = __uint_as_float(gs.w);
            const uint32_t a0 = pack2(ex2((bflo(sv.x) - g0) * L2E) * i0, ex2((bflo(sv.y) - g0) * L2E) * i0);
            const uint32_t a1 = pack2(ex2((bflo(sv.z) - g0) * L2E) * i0, ex2((bflo(sv.w) - g0) * L2E) * i0);
            const uint32_t b0 = pack2(ex2((bfhi(sv.x) - g1) * L2E) * i1, ex2((bfhi(sv.y) - g1) * L2E) * i1);
            const uint32_t b1 = pack2(ex2((bfhi(sv.z) - g1) * L2E) * i1, ex2((bfhi(sv.w) - g1) * L2E) * i1);
            sts64(sb + OFF_P + tid * 8, a0, a1); sts64(sb + OFF_P + PSTR + tid * 8, b0, b1);
        }
        bar_consumers();
    }
    const uint32_t rsw = ((mi & 1) ^ r) << 4;
    unsigned sidew = 2u;
    if (vw < 8) {
        float c0[4] = {}, c1[4] = {};
        const uint32_t vo = (vw >> 2) * 8192 + (r + 8 * (mi >> 1)) * 128 + ((((2 * vw + (mi & 1)) & 7) ^ r) << 4);
        const uint32_t pa = sb + OFF_P + bat * PSTR + t * 32;
#pragma unroll 1
        for (int i = 0; i < 16; i++) {
            uint4 pb0 = lds128(pa + i * 128), pb1 = lds128(pa + i * 128 + 16);
            mbar_wait(s_full + (IT_V + i) * 8);
            const uint32_t base = sb + v_off(i) + vo;
            uint32_t a0[4], a1[4], a2[4], a3[4];
            ldsm4t(a0, base); ldsm4t(a1, base + 2048); ldsm4t(a2, base + 4096); ldsm4t(a3, base + 6144);
            mma16816(c0, a0, pb0.x, pb0.y);
            mma16816(c1, a1, pb0.z, pb0.w);
            mma16816(c0, a2, pb1.x, pb1.y);
            mma16816(c1, a3, pb1.z, pb1.w);
            __syncwarp();
            if (lane == 0) mbar_arrive(s_empty + (EM_V + i) * 8);
            if (i == SIDE_V) { mbar_wait(s_empty + EM_PH * 8); sidew = ldg_rlx1(pside); }
        }
        if (t < 2)
            stg_pkt(scr + G_OP + kvh * 4096 + (j >> 2) * 2048 + t * HALF + (j & 3) * 256 + vw * 32 + g * 4,
                    c0[0] + c1[0], c0[1] + c1[1], c0[2] + c1[2], c0[3] + c1[3], tag);
    } else {
        mbar_wait(s_full + (IT_V + SIDE_V) * 8);
        mbar_wait(s_empty + EM_PH * 8);
    }
    {
        int it = 0;
        while (any_lane((sidew ^ tag) & 7u) && ++it < SPIN_LIMIT) sidew = ldg_rlx1(pside);
        ppart += near_half(G_PART + (vw * 16 + t * 4 + (g >> 1)) * 2048, sidew >> 4);
    }
    side = __float_as_uint(ldsf(sb + OFF_WMX + 112));
#pragma unroll 1
    for (int ph = 0; ph < 2; ph++) {
        if (ph) {
            mbar_wait(s_empty + EM_X1 * 8);
            {
                uint4 v;
                int it = 0;
                const int xw = G_X1 + (vw >> 3) * 2048 + (c & (XREP - 1)) * 4096;
                const unsigned* px = scr + xw + near_half(xw, side) + (vecw & 1023);
                do { v = ldg_rlx4(px); } while (any_lane(bad4(v, tag) & 7u) && ++it < SPIN_LIMIT);
                xw0 = hi2(v.x, v.y); xw1 = hi2(v.z, v.w);
                ln_stage1(xw0, xw1, st2, vw, lane);
                bar_consumers();
                uint32_t y0, y1;
                ln_stage2(ln_load(st2), xw0, xw1, y0, y1);
                aw0 = badd2(bmul2(y0, sc0), sh0); aw1 = badd2(bmul2(y1, sc1), sh1);
                uint32_t bf[4][2];
                make_bfrags(bf, aw0, aw1, r);
                const uint32_t gub = s_full + (IT_GU + 2 * (vw / 3)) * 8;
                const uint32_t gpitch = wide ? 96 : 64, gsw = wide ? 0 : (r >> 1) << 4;
                const uint32_t gbase = sb + ((mi & 1) ? OFF_U : OFF_G) + (vw * 64 + r + 8 * (mi >> 1)) * gpitch;
                mbar_wait(gub); mbar_wait(gub + 8);
                float cc[6][4] = {};
#pragma unroll
                for (int ks = 0; ks < 4; ks++)
#pragma unroll
                    for (int q = 0; q < 4; q++) {
                        uint32_t a[4];
                        ldsm4t(a, gbase + ks * 16 * gpitch + ((q << 4) ^ gsw));
                        mma16816(cc[q], a, bf[ks][0], bf[ks][1]);
                    }
                if (wide) {
#pragma unroll
                    for (int ks = 0; ks < 4; ks++)
#pragma unroll
                        for (int q = 4; q < 6; q++) {
                            uint32_t a[4];
                            ldsm4t(a, gbase + ks * 1536 + q * 16);
                            mma16816(cc[q], a, bf[ks][0], bf[ks][1]);
                        }
                }
                if (t == 0) {
#pragma unroll
                    for (int q = 0; q < 6; q++) sts128f(sb + OFF_RED + vw * 768 + q * 128 + g * 16, cc[q]);
                }
                bar_consumers();
                if (tid < 192) {
                    float sv[NCW];
#pragma unroll
                    for (int w = 0; w < NCW; w++) sv[w] = ldsf(sb + OFF_RED + w * 768 + tid * 4);
                    const float s = ((sv[0] + sv[1]) + (sv[2] + sv[3])) + ((sv[4] + sv[5]) + (sv[6] + sv[7])) + sv[8];
                    const uint32_t gu = pack2(s, __shfl_down_sync(0xffffffffu, s, 2));
                    const float gt = bflo(gu);
                    const uint32_t hh = pack2(((gt > 0.f) ? gt : gt * 0.0f) * bfhi(gu), 0.f);
                    const int rr = tid >> 2;
                    if ((tid & 2) == 0)
                        sts16(sb + OFF_FR + ((tid & 1) * 4 + ((rr & 7) >> 1)) * 48 + (rr >> 3) * 4 + (rr & 1) * 2, hh);
                }
            }
            bar_consumers();
        }
        {
            const int di = (vw / 3 + 1) % 3;
            const uint32_t rrow = (r + 8 * (mi >> 1)) * 128;
            const uint32_t b0 = sb + rrow + (ph ? OFF_D + di * DSTR + (vw % 3) * (wide ? 6144 : 4096) : OFF_WO0 + vw * 2048);
            const uint32_t b1 = ph ? b0 + 2048 : sb + rrow + OFF_WO1 + vw * 2048;
            const uint32_t fb0 = s_full + (ph ? IT_WD + di : IT_WO) * 8;
            const bool k3 = ph && wide;
            uint32_t ad[3][4][4];
            uint4 fr = lds128(sb + OFF_FR + r * 48);
            const uint2 f2 = lds64(sb + OFF_FR + r * 48 + 16);
            mbar_wait(fb0);
#pragma unroll
            for (int mt = 0; mt < 4; mt++) ldsm4t(ad[0][mt], b0 + (rsw ^ (mt * 32)));
            if (!ph) mbar_wait(fb0 + 8);
#pragma unroll
            for (int mt = 0; mt < 4; mt++) ldsm4t(ad[1][mt], b1 + (rsw ^ (mt * 32)));
            if (k3) {
#pragma unroll
                for (int mt = 0; mt < 4; mt++) ldsm4t(ad[2][mt], b0 + 4096 + (rsw ^ (mt * 32)));
            }
            if (!ph) {
                asm volatile("bar.sync 3, 352;" ::: "memory");
                fr = lds128(sb + OFF_FR + r * 48);
            }
            float cc[4][4] = {};
#pragma unroll
            for (int mt = 0; mt < 4; mt++) mma16816(cc[mt], ad[0][mt], fr.x, fr.y);
#pragma unroll
            for (int mt = 0; mt < 4; mt++) mma16816(cc[mt], ad[1][mt], fr.z, fr.w);
            if (k3) {
#pragma unroll
                for (int mt = 0; mt < 4; mt++) mma16816(cc[mt], ad[2][mt], f2.x, f2.y);
            }
            publish_partials(ppart, t, cc, tag | (ph * 4u));
        }
    }
    if (vw / 3 == c / 48) asm volatile("bar.arrive 5, 128;" ::: "memory");
    if (vw >= 6 && c < 16) asm volatile("bar.arrive 7, 128;" ::: "memory");
}

typedef CUresult (*EncodeFn)(CUtensorMap*, CUtensorMapDataType, cuuint32_t, void*, const cuuint64_t*, const cuuint64_t*,
                             const cuuint32_t*, const cuuint32_t*, CUtensorMapInterleave, CUtensorMapSwizzle,
                             CUtensorMapL2promotion, CUtensorMapFloatOOBfill);

void make_map(EncodeFn enc, CUtensorMap* m, const void* p, cuuint64_t d0, cuuint64_t d1, cuuint64_t d2,
              cuuint64_t s1, cuuint64_t s2, cuuint32_t b0, cuuint32_t b1, cuuint32_t b2, CUtensorMapSwizzle sw,
              CUtensorMapL2promotion pr = CU_TENSOR_MAP_L2_PROMOTION_L2_128B) {
    cuuint64_t dims[3] = {d0, d1, d2};
    cuuint64_t str[2] = {s1, s2};
    cuuint32_t box[3] = {b0, b1, b2};
    cuuint32_t es[3] = {1, 1, 1};
    enc(m, CU_TENSOR_MAP_DATA_TYPE_BFLOAT16, 3, const_cast<void*>(p), dims, str, box, es,
        CU_TENSOR_MAP_INTERLEAVE_NONE, sw, pr, CU_TENSOR_MAP_FLOAT_OOB_FILL_NONE);
}

}

extern "C" void kernel_launch(void* const* d_in, const int* in_sizes, int n_in, void* d_out, int out_size) {
    (void)in_sizes; (void)n_in; (void)out_size;
    void* fn = nullptr;
    cudaDriverEntryPointQueryResult qr;
    cudaGetDriverEntryPoint("cuTensorMapEncodeTiled", &fn, cudaEnableDefault, &qr);
    EncodeFn enc = (EncodeFn)fn;
    cudaFuncSetAttribute(fused_block_kernel, cudaFuncAttributeMaxDynamicSharedMemorySize, SMEM_BYTES);

    const void *x = d_in[0], *kc = d_in[1], *vc = d_in[2], *wq = d_in[3], *wo = d_in[4];
    const void *wg = d_in[6], *wu = d_in[7], *wd = d_in[8], *cc = d_in[9], *wmod = d_in[10];
    const CUtensorMapSwizzle S128 = CU_TENSOR_MAP_SWIZZLE_128B, S64 = CU_TENSOR_MAP_SWIZZLE_64B, S0 = CU_TENSOR_MAP_SWIZZLE_NONE;
    void* raw = nullptr;
    cudaGetSymbolAddress(&raw, g_raw);
    unsigned* scr = (unsigned*)(((uintptr_t)raw + 0x1fffff) & ~(uintptr_t)0x1fffff);
    Maps m;
    make_map(enc, &m.m[M_K], kc, 64, 32ull * 32768, 2, 256, 128, 64, 64, 2, S128, CU_TENSOR_MAP_L2_PROMOTION_L2_256B);
    make_map(enc, &m.m[M_V], vc, 64, 32ull * 32768, 2, 256, 128, 64, 64, 2, S128, CU_TENSOR_MAP_L2_PROMOTION_L2_256B);
    make_map(enc, &m.m[M_WMOD], wmod, 3456, 144, 4, 3456 * 2, 3456 * 2 * 144, 32, 144, 2, S64);
    make_map(enc, &m.m[M_WQ], wq, 4096, 144, 4, 4096 * 2, 4096 * 2 * 144, 32, 144, 2, S64);
    make_map(enc, &m.m[M_WG], wg, 4608, 576, 1, 4608 * 2, 4608 * 2 * 576, 32, 192, 1, S64);
    make_map(enc, &m.m[M_WU], wu, 4608, 576, 1, 4608 * 2, 4608 * 2 * 576, 32, 192, 1, S64);
    make_map(enc, &m.m[M_WG48], wg, 4608, 576, 1, 4608 * 2, 4608 * 2 * 576, 48, 192, 1, S0);
    make_map(enc, &m.m[M_WU48], wu, 4608, 576, 1, 4608 * 2, 4608 * 2 * 576, 48, 192, 1, S0);
    make_map(enc, &m.m[M_WO], wo, 64, 4096, 9, 1152, 128, 64, 16, 9, S128);
    make_map(enc, &m.m[M_WD], wd, 64, 4608, 9, 1152, 128, 64, 32, 3, S128);
    make_map(enc, &m.m[M_WD48], wd, 64, 4608, 9, 1152, 128, 64, 48, 3, S128);
    fused_block_kernel<<<NCTA, NTHR, SMEM_BYTES>>>(m, (const __nv_bfloat16*)x, (const __nv_bfloat16*)cc,
                                                   (const __nv_bfloat16*)kc, (__nv_bfloat16*)d_out, scr);
}
```

```cpp
#include <cuda_runtime.h>
#include <cuda.h>
#include <cuda_bf16.h>
#include <stdint.h>

namespace {

constexpr int DM = 576;
constexpr int NCTA = 128;
constexpr int NCW = 9;
constexpr int NTHR = (NCW + 3) * 32;
constexpr int NMOD = 108;

constexpr int WIN_MAIN = 4;
constexpr int WIN_TAIL = 3;
constexpr int PACE_GBS = 3210;
constexpr int PACE_LEAD = 15360;
constexpr int EARLY_PF = 8192;
constexpr int DELAY_B = 300;
constexpr int XREP = 2;
constexpr int PH_K = 0;
constexpr int PH_V = 0;
constexpr int SIDE_V = 6;
constexpr int NPROBE0 = 3, NPROBE = 10;

constexpr int IT_WMOD = 0, IT_WQ = 2, IT_K = 4, IT_V = 20, IT_WO = 36, IT_GU = 38, IT_WD = 44, N_IT = 47;
constexpr int EM_WMOD = 0, EM_WQ = 1, EM_K = 2, EM_V = 18, EM_PH = 34, EM_X1 = 35, EM_SD = 36, N_EM = 37;

constexpr int RING = 13 * 16384;
constexpr int OFF_WMOD = 0, OFF_WQ = 36864, OFF_K0 = 73728;
constexpr int OFF_WO0 = 194560, OFF_WO1 = 0, OFF_G = 18432, OFF_U = 73728;
constexpr int OFF_D = 129024, DSTR = 18432;
constexpr int PSTR = 2064;
constexpr int OFF_P = RING;
constexpr int OFF_S = OFF_P + 4160;
constexpr int OFF_RED = OFF_S + 4096;
constexpr int OFF_QS = OFF_RED + 6912;
constexpr int OFF_FR = OFF_QS + 640;
constexpr int OFF_STAT = OFF_FR + 384;
constexpr int OFF_WMX = OFF_STAT + 320;
constexpr int OFF_BAR = OFF_WMX + 128;
constexpr int SMEM_USED = OFF_BAR + (N_IT + N_EM) * 8;
constexpr int SMEM_BYTES = SMEM_USED + 1024;
static_assert(SMEM_BYTES <= 232448, "smem");

struct Maps { CUtensorMap m[11]; };
enum { M_K, M_V, M_WMOD, M_WQ, M_WO, M_WG, M_WU, M_WD, M_WG48, M_WU48, M_WD48 };

constexpr int HALF = 1024;
constexpr int G_PART = 0;
constexpr int G_OP = G_PART + 144 * 2048;
constexpr int G_X1 = G_OP + 16 * 4096;
constexpr int G_PROBE = G_X1 + XREP * 4096;
constexpr int G_SIDE = G_PROBE + 2048;
constexpr int G_EPOCH = G_SIDE + 1024;
constexpr int G_MOD = G_EPOCH + 1024;
constexpr int G_Q = G_MOD + 7 * 2048;
constexpr int G_ML = G_Q + 8 * 2048;
constexpr int G_WORDS = G_ML + 2048;
static_assert(G_MOD % 2048 == 0 && G_OP % 2048 == 0 && G_X1 % 2048 == 0 && G_PROBE % 2048 == 0, "halves");
static_assert(G_WORDS * 4 <= (2 << 20), "scratch must fit one 2 MB page");
__device__ __align__(128) unsigned g_raw[(2 << 20) / 4 + G_WORDS];
__device__ __forceinline__ int near_half(int w, unsigned side) { return ((__popc(w & 0x2C800) ^ side) & 1) << 10; }
__device__ __forceinline__ int dual(int base, int i) { return base + i + (i & ~1023); }
__device__ __forceinline__ int dual_near(int base, int i, unsigned side) { const int w = dual(base, i); return w + near_half(w, side); }

constexpr int SPIN_LIMIT = 1 << 20;

__device__ __forceinline__ uint32_t smem_u32(const void* p) { return (uint32_t)__cvta_generic_to_shared(p); }
__device__ __forceinline__ void mbar_init(uint32_t bar, int cnt) {
    asm volatile("mbarrier.init.shared::cta.b64 [%0], %1;" ::"r"(bar), "r"(cnt) : "memory");
}
__device__ __forceinline__ void mbar_expect_tx(uint32_t bar, uint32_t bytes) {
    asm volatile("mbarrier.arrive.expect_tx.shared::cta.b64 _, [%0], %1;" ::"r"(bar), "r"(bytes) : "memory");
}
__device__ __forceinline__ void mbar_arrive(uint32_t bar) {
    asm volatile("mbarrier.arrive.shared::cta.b64 _, [%0];" ::"r"(bar) : "memory");
}
__device__ __forceinline__ void mbar_wait(uint32_t bar) {
    asm volatile("{\n.reg .pred p;\nW_%=:\nmbarrier.try_wait.parity.shared::cta.b64 p, [%0], 0;\n@!p bra W_%=;\n}"
                 ::"r"(bar) : "memory");
}
__device__ __forceinline__ uint32_t gtime32() { uint32_t t; asm volatile("mov.u32 %0, %%globaltimer_lo;" : "=r"(t)); return t; }
__device__ __forceinline__ uint64_t policy_stream() {
    uint64_t p; asm("createpolicy.fractional.L2::evict_first.b64 %0, 1.0;" : "=l"(p)); return p;
}
__device__ __forceinline__ void tma3d(uint32_t dst, const CUtensorMap* m, int x, int y, int z, uint32_t bar) {
    asm volatile("cp.async.bulk.tensor.3d.shared::cluster.global.mbarrier::complete_tx::bytes.L2::cache_hint [%0], [%1, {%3, %4, %5}], [%2], %6;"
                 ::"r"(dst), "l"(m), "r"(bar), "r"(x), "r"(y), "r"(z), "l"(policy_stream()) : "memory");
}
__device__ __forceinline__ void bar_consumers() { asm volatile("bar.sync 1, 288;" ::: "memory"); }

__device__ __forceinline__ void ldsm4(uint32_t (&a)[4], uint32_t addr) {
    asm volatile("ldmatrix.sync.aligned.m8n8.x4.shared.b16 {%0,%1,%2,%3}, [%4];"
                 : "=r"(a[0]), "=r"(a[1]), "=r"(a[2]), "=r"(a[3]) : "r"(addr) : "memory");
}
__device__ __forceinline__ void ldsm4t(uint32_t (&a)[4], uint32_t addr) {
    asm volatile("ldmatrix.sync.aligned.m8n8.x4.trans.shared.b16 {%0,%1,%2,%3}, [%4];"
                 : "=r"(a[0]), "=r"(a[1]), "=r"(a[2]), "=r"(a[3]) : "r"(addr) : "memory");
}
__device__ __forceinline__ void mma16816(float (&c)[4], const uint32_t (&a)[4], uint32_t b0, uint32_t b1) {
    asm volatile("mma.sync.aligned.m16n8k16.row.col.f32.bf16.bf16.f32 {%0,%1,%2,%3}, {%4,%5,%6,%7}, {%8,%9}, {%0,%1,%2,%3};"
                 : "+f"(c[0]), "+f"(c[1]), "+f"(c[2]), "+f"(c[3])
                 : "r"(a[0]), "r"(a[1]), "r"(a[2]), "r"(a[3]), "r"(b0), "r"(b1));
}
__device__ __forceinline__ float ldsf(uint32_t a) { float v; asm volatile("ld.shared.f32 %0, [%1];" : "=f"(v) : "r"(a) : "memory"); return v; }
__device__ __forceinline__ uint2 lds64(uint32_t a) {
    uint2 v; asm volatile("ld.shared.v2.u32 {%0,%1}, [%2];" : "=r"(v.x), "=r"(v.y) : "r"(a) : "memory"); return v;
}
__device__ __forceinline__ uint4 lds128(uint32_t a) {
    uint4 v; asm volatile("ld.shared.v4.u32 {%0,%1,%2,%3}, [%4];" : "=r"(v.x), "=r"(v.y), "=r"(v.z), "=r"(v.w) : "r"(a) : "memory"); return v;
}
__device__ __forceinline__ void sts16(uint32_t a, uint32_t v) { asm volatile("st.shared.u16 [%0], %1;" ::"r"(a), "h"((unsigned short)v) : "memory"); }
__device__ __forceinline__ void sts32(uint32_t a, uint32_t v) { asm volatile("st.shared.u32 [%0], %1;" ::"r"(a), "r"(v) : "memory"); }
__device__ __forceinline__ void sts64(uint32_t a, uint32_t x, uint32_t y) { asm volatile("st.shared.v2.u32 [%0], {%1,%2};" ::"r"(a), "r"(x), "r"(y) : "memory"); }
__device__ __forceinline__ void sts128(uint32_t a, uint32_t x, uint32_t y, uint32_t z, uint32_t w) {
    asm volatile("st.shared.v4.u32 [%0], {%1,%2,%3,%4};" ::"r"(a), "r"(x), "r"(y), "r"(z), "r"(w) : "memory");
}
__device__ __forceinline__ void sts128f(uint32_t a, const float (&c)[4]) {
    asm volatile("st.shared.v4.f32 [%0], {%1,%2,%3,%4};" ::"r"(a), "f"(c[0]), "f"(c[1]), "f"(c[2]), "f"(c[3]) : "memory");
}
__device__ __forceinline__ unsigned ldg_rlx1(const unsigned* p) {
    unsigned v; asm volatile("ld.relaxed.gpu.global.u32 %0, [%1];" : "=r"(v) : "l"(p) : "memory"); return v;
}
__device__ __forceinline__ uint4 ldg_rlx4(const unsigned* p) {
    uint4 v; asm volatile("ld.relaxed.gpu.global.v4.u32 {%0,%1,%2,%3}, [%4];" : "=r"(v.x), "=r"(v.y), "=r"(v.z), "=r"(v.w) : "l"(p) : "memory"); return v;
}
__device__ __forceinline__ uint4 ldg_pkt(const unsigned* p) {
    uint4 v;
    asm volatile("{\n.reg .b128 t;\n.reg .b64 lo, hi;\nld.relaxed.gpu.global.b128 t, [%4];\nmov.b128 {lo, hi}, t;\n"
                 "mov.b64 {%0,%1}, lo;\nmov.b64 {%2,%3}, hi;\n}"
                 : "=r"(v.x), "=r"(v.y), "=r"(v.z), "=r"(v.w) : "l"(p) : "memory");
    return v;
}
__device__ __forceinline__ void ldg_pkt_if(uint4& v, const unsigned* a, unsigned p) {
    asm volatile("{\n.reg .pred q;\n.reg .b128 t;\n.reg .b64 lo, hi;\nsetp.ne.u32 q, %5, 0;\n"
                 "mov.b64 lo, {%0,%1};\nmov.b64 hi, {%2,%3};\nmov.b128 t, {lo, hi};\n"
                 "@q ld.relaxed.gpu.global.b128 t, [%4];\nmov.b128 {lo, hi}, t;\n"
                 "mov.b64 {%0,%1}, lo;\nmov.b64 {%2,%3}, hi;\n}"
                 : "+r"(v.x), "+r"(v.y), "+r"(v.z), "+r"(v.w) : "l"(a), "r"(p) : "memory");
}
__device__ __forceinline__ bool any_lane(unsigned x) { return __any_sync(0xffffffffu, x != 0); }
__device__ __forceinline__ void stg_pkt(unsigned* p, float a, float b, float c, float d, unsigned tag) {
    unsigned x = (__float_as_uint(a) & ~7u) | tag;
    asm volatile("{\n.reg .b128 t;\n.reg .b64 lo, hi;\nmov.b64 lo, {%1,%2};\nmov.b64 hi, {%3,%4};\nmov.b128 t, {lo, hi};\n"
                 "st.relaxed.gpu.global.b128 [%0], t;\n}"
                 ::"l"(p), "r"(x), "r"(__float_as_uint(b)), "r"(__float_as_uint(c)), "r"(__float_as_uint(d)) : "memory");
}
__device__ __forceinline__ void stg_rlx1(unsigned* p, unsigned x) { asm volatile("st.relaxed.gpu.global.u32 [%0], %1;" ::"l"(p), "r"(x) : "memory"); }
__device__ __forceinline__ unsigned bad4(const uint4& v, unsigned tag) {
    return ((v.x ^ tag) | (v.y ^ tag)) | ((v.z ^ tag) | (v.w ^ tag));
}
__device__ __forceinline__ float untagf(unsigned w) { return __uint_as_float(w & ~7u); }
__device__ __forceinline__ uint32_t pack2(float lo, float hi) {
    uint32_t r; asm("cvt.rn.bf16x2.f32 %0, %1, %2;" : "=r"(r) : "f"(hi), "f"(lo)); return r;
}
__device__ __forceinline__ float bflo(uint32_t w) { return __uint_as_float(w << 16); }
__device__ __forceinline__ float bfhi(uint32_t w) { return __uint_as_float(w & 0xffff0000u); }
__device__ __forceinline__ uint32_t hi2(uint32_t a, uint32_t b) { return __byte_perm(a, b, 0x7632); }
__device__ __forceinline__ uint32_t badd2(uint32_t a, uint32_t b) { uint32_t r; asm("add.rn.bf16x2 %0, %1, %2;" : "=r"(r) : "r"(a), "r"(b)); return r; }
__device__ __forceinline__ uint32_t bsub2(uint32_t a, uint32_t b) { uint32_t r; asm("sub.rn.bf16x2 %0, %1, %2;" : "=r"(r) : "r"(a), "r"(b)); return r; }
__device__ __forceinline__ uint32_t bmul2(uint32_t a, uint32_t b) { uint32_t r; asm("mul.rn.bf16x2 %0, %1, %2;" : "=r"(r) : "r"(a), "r"(b)); return r; }
__device__ __forceinline__ uint32_t bmax2(uint32_t a, uint32_t b) { uint32_t r; asm("max.bf16x2 %0, %1, %2;" : "=r"(r) : "r"(a), "r"(b)); return r; }
__device__ __forceinline__ float ex2(float x) { float r; asm("ex2.approx.ftz.f32 %0, %1;" : "=f"(r) : "f"(x)); return r; }
__device__ __forceinline__ float rcp(float x) { float r; asm("rcp.approx.ftz.f32 %0, %1;" : "=f"(r) : "f"(x)); return r; }
__device__ __forceinline__ float fsqrt(float x) { float r; asm("sqrt.approx.ftz.f32 %0, %1;" : "=f"(r) : "f"(x)); return r; }
__device__ __forceinline__ float shx(float v, int m) { return __shfl_xor_sync(0xffffffffu, v, m); }

__device__ __forceinline__ uint32_t k_off(int i) { return i < 8 ? OFF_K0 + i * 16384 : (i - 8) * 16384; }
__device__ __forceinline__ uint32_t v_off(int i) { return i < 5 ? (8 + i) * 16384 : (i - 5) * 16384; }

__device__ __forceinline__ void stg_ph(unsigned* p) { stg_pkt(p, 0.f, 0.f, 0.f, 0.f, 2u); }

__device__ __forceinline__ void ln_stage1(uint32_t xw0, uint32_t xw1, uint32_t st, int vw, int lane) {
    const float piv = __shfl_sync(0xffffffffu, bflo(xw0), lane & 4);
    const float d0 = bflo(xw0) - piv, d1 = bfhi(xw0) - piv, d2 = bflo(xw1) - piv, d3 = bfhi(xw1) - piv;
    float s1 = (d0 + d1) + (d2 + d3), s2 = (d0 * d0 + d1 * d1) + (d2 * d2 + d3 * d3);
    s1 += shx(s1, 1); s2 += shx(s2, 1);
    s1 += shx(s1, 2); s2 += shx(s2, 2);
    s1 += shx(s1, 8); s2 += shx(s2, 8);
    s1 += shx(s1, 16); s2 += shx(s2, 16);
    if ((lane & 27) == 0)
        sts64(st + vw * 8, __float_as_uint(piv + s1 * (1.0f / 64.0f)), __float_as_uint(s2 - s1 * s1 * (1.0f / 64.0f)));
}
struct LnStat { uint4 a, b, c, d; uint2 e; };
__device__ __forceinline__ LnStat ln_load(uint32_t st) {
    LnStat s; s.a = lds128(st); s.b = lds128(st + 16); s.c = lds128(st + 32); s.d = lds128(st + 48); s.e = lds64(st + 64);
    return s;
}
__device__ __forceinline__ void ln_stage2(const LnStat& s, uint32_t xw0, uint32_t xw1, uint32_t& y0, uint32_t& y1) {
    const float m[9] = {__uint_as_float(s.a.x), __uint_as_float(s.a.z), __uint_as_float(s.b.x), __uint_as_float(s.b.z),
                        __uint_as_float(s.c.x), __uint_as_float(s.c.z), __uint_as_float(s.d.x), __uint_as_float(s.d.z), __uint_as_float(s.e.x)};
    const float mean = (((m[0] + m[1]) + (m[2] + m[3])) + ((m[4] + m[5]) + (m[6] + m[7])) + m[8]) * (1.0f / NCW);
    const float m2 = ((__uint_as_float(s.a.y) + __uint_as_float(s.a.w)) + (__uint_as_float(s.b.y) + __uint_as_float(s.b.w))) +
                     ((__uint_as_float(s.c.y) + __uint_as_float(s.c.w)) + (__uint_as_float(s.d.y) + __uint_as_float(s.d.w))) + __uint_as_float(s.e.y);
    float d[9];
#pragma unroll
    for (int w = 0; w < 9; w++) d[w] = m[w] - mean;
    const float acc = (d[0] * d[0] + d[1] * d[1] + d[2] * d[2]) + (d[3] * d[3] + d[4] * d[4] + d[5] * d[5]) + (d[6] * d[6] + d[7] * d[7] + d[8] * d[8]);
    const float var = (m2 + 64.0f * acc) * (1.0f / DM);
    const uint32_t mv = pack2(mean, var);
    const float ve = bflo(pack2(bfhi(mv) + 1e-5f, 0.f));
    const float rinv = rcp(bflo(pack2(fsqrt(ve), 0.f)));
    const uint32_t mm = __byte_perm(mv, mv, 0x1010);
    const uint32_t e0 = bsub2(xw0, mm), e1 = bsub2(xw1, mm);
    y0 = pack2(bflo(e0) * rinv, bfhi(e0) * rinv); y1 = pack2(bflo(e1) * rinv, bfhi(e1) * rinv);
}
__device__ __forceinline__ void make_bfrags(uint32_t (&bf)[4][2], uint32_t aw0, uint32_t aw1, int r) {
#pragma unroll
    for (int ks = 0; ks < 4; ks++) {
        bf[ks][0] = __shfl_sync(0xffffffffu, aw0, ks * 8 + r);
        bf[ks][1] = __shfl_sync(0xffffffffu, aw1, ks * 8 + r);
    }
}
__device__ __forceinline__ uint32_t gemv32(uint32_t s_w, uint32_t red, uint32_t fullbar, uint32_t emptybar,
                                           uint32_t aw0, uint32_t aw1, int tid) {
    const int vw = tid >> 5, lane = tid & 31, g = lane >> 2, t = lane & 3, mi = lane >> 3, r = lane & 7;
    uint32_t bf[4][2];
    make_bfrags(bf, aw0, aw1, r);
    if (vw <= 4) mbar_wait(fullbar);
    if (vw >= 4) mbar_wait(fullbar + 8);
    float cc[2][4] = {};
    const uint32_t abase = s_w + (vw * 64 + r + 8 * (mi >> 1)) * 64;
    const uint32_t sw = ((mi & 1) ^ (r >> 1)) << 4;
#pragma unroll
    for (int ks = 0; ks < 4; ks++) {
#pragma unroll
        for (int mt = 0; mt < 2; mt++) {
            uint32_t a[4];
            ldsm4t(a, abase + ks * 1024 + (sw ^ (mt * 32)));
            mma16816(cc[mt], a, bf[ks][0], bf[ks][1]);
        }
    }
    if (t == 0) { sts128f(red + vw * 256 + g * 16, cc[0]); sts128f(red + vw * 256 + 128 + g * 16, cc[1]); }
    __syncwarp();
    if (lane == 0) mbar_arrive(emptybar);
    bar_consumers();
    float s = 0.f;
    if (tid < 64) {
        const uint32_t ra = red + ((tid & 58) | ((tid & 1) << 2) | ((tid >> 2) & 1)) * 4;
#pragma unroll
        for (int w = 0; w < NCW; w++) s += ldsf(ra + w * 256);
    }
    return pack2(0.f, s);
}
__device__ __forceinline__ void publish_partials(unsigned* q, int t, const float (&cc)[4][4], unsigned tag) {
    float v[4];
#pragma unroll
    for (int i = 0; i < 4; i++) {
        const float lo = (t & 1) ? cc[1][i] : cc[0][i], hi = (t & 1) ? cc[3][i] : cc[2][i];
        v[i] = (t & 2) ? hi : lo;
    }
    stg_pkt(q, v[0], v[1], v[2], v[3], tag);
}
__device__ __forceinline__ void spin_cycles(unsigned n) {
    const unsigned c0 = clock();
    while ((unsigned)clock() - c0 < n) { }
}
__device__ __forceinline__ float reduce_unit(const unsigned* q, int lane, unsigned tag) {
    uint4 v[8];
#pragma unroll
    for (int i = 0; i < 8; i++) v[i] = ldg_pkt(q + i * 128);
    int it = 0;
    unsigned y[8];
    while (true) {
#pragma unroll
        for (int i = 0; i < 8; i++) y[i] = v[i].x ^ tag;
        const bool more = any_lane((((y[0] | y[1] | y[2]) | (y[3] | y[4] | y[5])) | (y[6] | y[7])) & 7u);
        if (!more || ++it >= SPIN_LIMIT) break;
#pragma unroll
        for (int i = 0; i < 8; i++) ldg_pkt_if(v[i], q + i * 128, y[i] & 7u);
    }
#define SUM8(e) (((e(0) + e(1)) + (e(2) + e(3))) + ((e(4) + e(5)) + (e(6) + e(7))))
#define EX(i) __uint_as_float(y[i])
#define EY(i) __uint_as_float(v[i].y)
#define EZ(i) __uint_as_float(v[i].z)
#define EW(i) __uint_as_float(v[i].w)
    const float s0 = SUM8(EX), s1 = SUM8(EY), s2 = SUM8(EZ), s3 = SUM8(EW);
    const bool h8 = lane & 2, bat = lane & 4;
    const float k0 = (h8 ? s2 : s0) + shx(h8 ? s0 : s2, 2);
    const float k1 = (h8 ? s3 : s1) + shx(h8 ? s1 : s3, 2);
    float k = (bat ? k1 : k0) + shx(bat ? k0 : k1, 4);
    k += shx(k, 8);
    k += shx(k, 16);
    return k;
}

__global__ void __launch_bounds__(NTHR, 1)
fused_block_kernel(const __grid_constant__ Maps maps, const __nv_bfloat16* __restrict__ xin,
                   const __nv_bfloat16* __restrict__ cin, const __nv_bfloat16* __restrict__ kcache,
                   __nv_bfloat16* __restrict__ out, unsigned* const scr) {
    extern __shared__ unsigned char smem_raw[];
    const int c = blockIdx.x;
    const int kvh = c >> 3, j = c & 7, bb = j & 1, sp = j >> 1;
    const bool wide = j >= 6;
    const int f0 = kvh * 288 + (wide ? 48 * j - 96 : 32 * j);
    const int kvrow0 = (bb * 16 + kvh) * 32768 + 28672 + sp * 64;
    const int kvstep = 256;
    if (threadIdx.x == 0)
        asm volatile("cp.async.bulk.prefetch.L2.global.L2::cache_hint [%0], %1, %2;"
                     ::"l"((const char*)kcache + (size_t)kvrow0 * 256), "r"(EARLY_PF), "l"(policy_stream()) : "memory");
    const uint32_t sb = (smem_u32(smem_raw) + 1023u) & ~1023u;
    const int warp = threadIdx.x >> 5, lane = threadIdx.x & 31;
    const uint32_t s_full = sb + OFF_BAR, s_empty = s_full + N_IT * 8;

    if (warp == NCW) {
        const uint32_t t0 = gtime32();
        const int first = (c < NMOD) ? 0 : 2;
        if (lane == 0) {
#pragma unroll
            for (int i = 0; i < 2; i++) mbar_init(s_full + (first + i) * 8, 1);
            asm volatile("fence.proxy.async.shared::cta;" ::: "memory");
#pragma unroll
            for (int i = 0; i < 2; i++) {
                const uint32_t bar = s_full + (first + i) * 8;
                mbar_expect_tx(bar, 18432);
                tma3d(sb + (first + i) * 18432, &maps.m[M_WMOD + (first >> 1)], c * 32, 0, i * 2, bar);
            }
        }
        __syncwarp();
        uint32_t w0[2], w1[2], w2[2];
#pragma unroll
        for (int h = 0; h < 2; h++) {
            const int i = lane + 32 * h;
            int off, map, dep = -1, x = 0, y = 0, z = 0, sz = 36, cum;
            if (i < IT_K) {
                off = i * 18432; map = M_WMOD + (i >> 1); x = c * 32; z = (i & 1) * 2; cum = 31104 + (i - 2) * 18432;
            } else if (i < IT_V) {
                const int k = i - IT_K;
                off = k_off(k); map = M_K; y = kvrow0 + k * kvstep; sz = 32; cum = 67968 + k * 16384;
                if (k == 8 && c < NMOD) dep = EM_WMOD;
                if (k == 10) dep = EM_WQ;
                if (k >= 12) dep = EM_K + k - 12;
            } else if (i < IT_WO) {
                const int k = i - IT_V;
                off = v_off(k); map = M_V; y = kvrow0 + k * kvstep; sz = 32; cum = 330112 + k * 16384;
                dep = EM_K + 3 + k + (k < 4);
            } else if (i < IT_GU) {
                const int k = i - IT_WO;
                off = k ? OFF_WO1 : OFF_WO0; map = M_WO; y = kvh * 256 + k * 128 + j * 16; dep = EM_V + 4 + 2 * k;
                cum = 592256 + k * 18432;
            } else if (i < IT_WD) {
                const int k = i - IT_GU;
                sz = wide ? 36 : 24;
                off = ((k & 1) ? OFF_U : OFF_G) + (k >> 1) * sz * 512; map = M_WG + (k & 1) + (wide ? 3 : 0);
                x = f0; y = (k >> 1) * 192; dep = EM_V + 5 + ((off + sz * 512 - 1) >> 14);
                cum = 629120 + k * 13824;
            } else {
                const int k = i - IT_WD;
                off = OFF_D + k * DSTR; map = wide ? M_WD48 : M_WD; y = f0; z = ((k + 2) % 3) * 3; sz = wide ? 36 : 24; dep = EM_V + (k ? 15 : 13);
                cum = 712064 + k * 13824;
            }
            const int stag = (i >= IT_K && i < IT_WO) ? (((kvh * 2 + bb) * 13) & 31) * 512
                           : i < IT_GU ? ((c * 37) & 127) * 128
                           : wide ? (((kvh * 2 + j) * 13) & 31) * 144 : 4608 + (((kvh * 6 + j) * 37) % 96) * 96;
            cum += EARLY_PF - min(max(cum - 67968, 0), EARLY_PF);
            const int due = (int)((float)max(cum + stag - PACE_LEAD, 0) * (128.0f / PACE_GBS));
            w0[h] = off | (map << 18) | ((dep + 1) << 22) | (z << 28);
            w1[h] = y | (sz << 24);
            w2[h] = x | (due << 13);
        }
        asm volatile("bar.sync 2, 384;" ::: "memory");
        uint32_t fb = s_full;
        asm volatile("" : "+r"(fb));
#pragma unroll 1
        for (int i = first + 2; i < N_IT; i++) {
            const bool hi = i >= 32;
            const uint32_t a = __shfl_sync(0xffffffffu, hi ? w0[1] : w0[0], i);
            const uint32_t b = __shfl_sync(0xffffffffu, hi ? w1[1] : w1[0], i);
            const uint32_t x = __shfl_sync(0xffffffffu, hi ? w2[1] : w2[0], i);
            if (lane == 0) {
                const uint32_t bar = fb + i * 8;
                const int win = (i >= IT_GU) ? WIN_TAIL : WIN_MAIN;
                const int dep = (a >> 22) & 63;
                const uint32_t due = t0 + (x >> 13);
                if (dep) mbar_wait(fb + (N_IT - 1 + dep) * 8);
                if (i - win >= first) mbar_wait(bar - win * 8);
                while ((int)(gtime32() - due) < 0) { }
                mbar_expect_tx(bar, (b >> 24) * 512);
                tma3d(fb - OFF_BAR + (a & 0x3ffff), &maps.m[(a >> 18) & 15], x & 0x1fff, b & 0xffffff, a >> 28, bar);
            }
            __syncwarp();
        }
        return;
    }

    const int g = lane >> 2, t = lane & 3, mi = lane >> 3, r = lane & 7;
    const int bat = g & 1;

    if (warp > NCW) {
        const bool first = warp == NCW + 1, active = first || c < 16;
        const int unit = first ? c : NCTA + c;
        const int rcol = (unit >> 2) * 16 + (unit & 3) * 2 + (lane & 1) + (lane & 2) * 4 + bat * DM;
        const unsigned ep = ldg_rlx1(scr + G_EPOCH);
        uint32_t xold = 0, ga = 0, gb = 0;
        if (active) xold = __ldg((const unsigned short*)xin + rcol);
        if (!first) asm volatile("bar.sync 2, 384;" ::: "memory");
        const unsigned tag = (ep + 1u) & 1u;
        unsigned side = 0;
        const int x1w = G_X1 + (unit >> 7) * 2048 + (unit & 127) * 8 + r + (lane & 8) * (HALF / 8) + (lane >> 4) * 4096;
        if (first) {
            unsigned* pr = scr + G_PROBE + c * 8;
            if (lane < 16) stg_rlx1(pr + r + (lane & 8) * (HALF / 8), 0u);
            __syncwarp();
            asm volatile("bar.arrive 2, 384;" ::: "memory");
            unsigned best0 = ~0u, best1 = ~0u, v = 0, cp = 0;
#pragma unroll 1
            for (int i = 0; i <= 2 * NPROBE; i++) {
                if (lane == 0) {
                    asm volatile("atom.relaxed.gpu.global.add.u32 %0, [%1], 1;" : "=r"(v) : "l"(pr + (i & 1) * HALF + (v >> 31)) : "memory");
                    const unsigned cn = clock(), d = cn - cp;
                    cp = cn;
                    if (i & 1) best0 = min(best0, d); else if (i) best1 = min(best1, d);
                    side = (best1 < best0) ^ (__popc(G_PROBE & 0x2C800) & 1);
                }
                if (i == 2 * NPROBE0) {
                    asm volatile("bar.sync 6, 64;" ::: "memory");
                    if (lane == 0) { sts32(sb + OFF_WMX + 116, side); mbar_arrive(s_empty + EM_SD * 8); }
                }
            }
            if (lane == 0) sts32(sb + OFF_WMX + 112, side);
            side = __shfl_sync(0xffffffffu, side, 0);
            mbar_wait(s_full + (IT_V + PH_V) * 8);
#pragma unroll 1
            for (int u = c; u < 144; u += NCTA) {
                unsigned* q = scr + G_PART + u * 2048 + near_half(G_PART + u * 2048, side) + lane * 4;
#pragma unroll
                for (int i = 0; i < 8; i++) stg_ph(q + i * 128);
#pragma unroll
                for (int i = 0; i < XREP; i += 2) stg_rlx1(scr + x1w + (u >> 7) * 2048 + i * 4096, 2u);
            }
            unsigned* o = scr + G_OP + kvh * 4096 + (j >> 2) * 2048 + (j & 3) * 256 + lane * 4;
            stg_ph(o); stg_ph(o + 128); stg_ph(o + HALF); stg_ph(o + HALF + 128);
            __threadfence();
            __syncwarp();
            if (lane < 8) stg_rlx1(scr + G_SIDE + c * 8 + lane, (side << 4) | tag);
            if (lane == 0) mbar_arrive(s_empty + EM_PH * 8);
        } else {
            asm volatile("bar.arrive 6, 64;" ::: "memory");
            if (lane < 8) asm volatile("prefetch.tensormap [%0];" ::"l"(&maps.m[lane + ((wide && lane >= M_WG) ? 3 : 0)]) : "memory");
            mbar_wait(s_empty + EM_PH * 8);
            side = __float_as_uint(ldsf(sb + OFF_WMX + 112));
        }
        if (active) {
            int it = 0;
            do {
                ga = ldg_rlx1(scr + dual_near(G_MOD, 2 * 1152 + unit * 8 + r, side));
                gb = ldg_rlx1(scr + dual_near(G_MOD, 5 * 1152 + unit * 8 + r, side));
            } while (any_lane(((ga ^ tag) | (gb ^ tag)) & 7u) && ++it < SPIN_LIMIT);
            ga >>= 16; gb >>= 16;
        }
        __syncwarp();
        if (first) {
            const int ow = G_OP + kvh * 4096 + (g >> 2) * 2048;
            const unsigned* q = scr + ow + near_half(ow, side) + (g & 3) * 256 + j * 32 + t * 8;
            mbar_wait(s_full + (IT_V + 15) * 8);
            uint4 lo, hi;
            int it = 0;
            do { lo = ldg_pkt(q); hi = ldg_pkt(q + 4); } while (any_lane(((lo.x ^ tag) | (hi.x ^ tag)) & 7u) && ++it < SPIN_LIMIT);
            float o[8] = {untagf(lo.x), __uint_as_float(lo.y), __uint_as_float(lo.z), __uint_as_float(lo.w),
                          untagf(hi.x), __uint_as_float(hi.y), __uint_as_float(hi.z), __uint_as_float(hi.w)};
            __syncwarp();
#pragma unroll
            for (int sft = 8; sft <= 16; sft <<= 1) {
#pragma unroll
                for (int i = 0; i < 8; i++) o[i] += shx(o[i], sft);
            }
            if (lane < 8)
                sts128(sb + OFF_FR + lane * 48, pack2(o[0], o[4]), pack2(o[2], o[6]), pack2(o[1], o[5]), pack2(o[3], o[7]));
        }
        asm volatile("bar.sync 3, 352;" ::: "memory");
        const unsigned* q = scr + G_PART + unit * 2048 + near_half(G_PART + unit * 2048, side) + lane * 4;
        if (!active) return;
#pragma unroll 1
        for (int ph = 0; ph < 2; ph++) {
            if (ph) asm volatile("bar.sync %0, 128;" ::"r"(first ? 5 : 7) : "memory");
            else spin_cycles(DELAY_B);
            const float k = reduce_unit(q, lane, tag | (ph * 4u));
            xold = badd2(xold, bmul2(ga, pack2(k, 0.f))) & 0xffffu;
            ga = gb;
            if (ph) {
                if (lane < 8) ((unsigned short*)out)[rcol] = (unsigned short)xold;
            } else {
#pragma unroll
                for (int i = 0; i < XREP; i += 2) stg_rlx1(scr + x1w + i * 4096, (xold << 16) | tag);
                if (first && lane == 0) mbar_arrive(s_empty + EM_X1 * 8);
            }
        }
        if (c == 0 && first && lane == 0) stg_rlx1(scr + G_EPOCH, ep + 1u);
        return;
    }

    const int vw = warp, tid = threadIdx.x;
    const int vecw = tid * 4 - (lane & 7) * 4 + t * 8 + bat * 4;
    unsigned* ppart = scr + G_PART + (vw * 16 + t * 4 + (g >> 1)) * 2048 + c * 8 + bat * 4;
    const unsigned* const pside = scr + G_SIDE + ((vw * 16 + t * 4 + (g >> 1)) & 127) * 8;
    const int qword = dual(G_Q, bat * 4096 + c * 32 + (tid >> 3) * 4 + t), mword = dual(G_MOD, c * 64 + (tid & 63));
    const uint32_t one2 = 0x3f803f80u;

    const unsigned ep = ldg_rlx1(scr + G_EPOCH);
    if (tid < 64) {
        if (c < NMOD) { stg_rlx1(scr + mword, 2u); stg_rlx1(scr + mword + HALF, 2u); }
        stg_rlx1(scr + qword, 2u); stg_rlx1(scr + qword + HALF, 2u);
    }
    uint32_t xw0, xw1, aw0, aw1;
    {
        const int col0 = bat * DM + (vw * 4 + mi) * 16 + 2 * t;
        const uint32_t cw0 = __ldg((const unsigned*)(cin + col0)), cw1 = __ldg((const unsigned*)(cin + col0 + 8));
        xw0 = __ldg((const unsigned*)(xin + col0)); xw1 = __ldg((const unsigned*)(xin + col0 + 8));
        if (lane == 0) {
            const int lo = (c < NMOD) ? 2 : 4;
#pragma unroll 1
            for (int i = vw; i < N_IT + N_EM; i += NCW) {
                const int e = i - N_IT;
                if (i >= lo) mbar_init(s_full + i * 8, (e < 0 || e >= EM_PH) ? 1 : (e < EM_K ? NCW : (e < EM_V ? 4 : 8)));
            }
            asm volatile("fence.proxy.async.shared::cta;" ::: "memory");
        }
        __syncwarp();
        asm volatile("bar.sync 2, 384;" ::: "memory");
        float cv[4] = {bflo(cw0), bfhi(cw0), bflo(cw1), bfhi(cw1)};
#pragma unroll
        for (int i = 0; i < 4; i++) cv[i] = cv[i] * rcp(1.0f + ex2(-1.4426950408889634f * cv[i]));
        aw0 = pack2(cv[0], cv[1]); aw1 = pack2(cv[2], cv[3]);
    }
    const unsigned tag = (ep + 1u) & 1u;
    const uint32_t st1 = sb + OFF_STAT + bat * 80, st2 = st1 + 160;
    ln_stage1(xw0, xw1, st1, vw, lane);

    if (c < NMOD) {
        const uint32_t m = gemv32(sb + OFF_WMOD, sb + OFF_RED, s_full + IT_WMOD * 8, s_empty + EM_WMOD * 8, aw0, aw1, tid);
        if (tid < 64) { stg_rlx1(scr + mword, m | tag); stg_rlx1(scr + mword + HALF, m | tag); }
    } else {
        bar_consumers();
    }
    mbar_wait(s_empty + EM_SD * 8);
    unsigned side = __float_as_uint(ldsf(sb + OFF_WMX + 116));
    {
        uint32_t y0, y1;
        ln_stage2(ln_load(st1), xw0, xw1, y0, y1);
        uint4 a, b;
        int it = 0;
        const unsigned *pa = scr + dual_near(G_MOD, vecw, side), *pb = scr + dual_near(G_MOD, 1152 + vecw, side);
        do { a = ldg_rlx4(pa); b = ldg_rlx4(pb); }
        while (any_lane((bad4(a, tag) | bad4(b, tag)) & 7u) && ++it < SPIN_LIMIT);
        __syncwarp();
        aw0 = badd2(bmul2(y0, badd2(one2, hi2(b.x, b.y))), hi2(a.x, a.y));
        aw1 = badd2(bmul2(y1, badd2(one2, hi2(b.z, b.w))), hi2(a.z, a.w));
        const uint32_t q = gemv32(sb + OFF_WQ, sb + OFF_RED + 2304, s_full + IT_WQ * 8, s_empty + EM_WQ * 8, aw0, aw1, tid);
        if (tid < 64) {
            stg_rlx1(scr + qword, q | tag); stg_rlx1(scr + qword + HALF, q | tag);
            uint4 v;
            int it = 0;
            const unsigned* pq = scr + dual_near(G_Q, bb * 4096 + kvh * 256 + tid * 4, side);
            do { v = ldg_rlx4(pq); } while (any_lane(bad4(v, tag) & 7u) && ++it < SPIN_LIMIT);
            sts64(sb + OFF_QS + (vw * 4 + t) * 80 + g * 8, hi2(v.x, v.y), hi2(v.z, v.w));
        }
        bar_consumers();
    }
    uint32_t sc0, sc1, sh0, sh1;
    {
        uint4 d, e;
        unsigned bad;
        int it = 0;
        do {
            d = ldg_rlx4(scr + dual_near(G_MOD, 3 * 1152 + vecw, side)); e = ldg_rlx4(scr + dual_near(G_MOD, 4 * 1152 + vecw, side));
            bad = bad4(d, tag) | bad4(e, tag);
        } while (any_lane(bad & 7u) && ++it < SPIN_LIMIT);
        __syncwarp();
        sh0 = hi2(d.x, d.y); sh1 = hi2(d.z, d.w);
        sc0 = badd2(one2, hi2(e.x, e.y)); sc1 = badd2(one2, hi2(e.z, e.w));
    }
    if (vw < 8) {
        uint4 qf[4];
#pragma unroll
        for (int i = 0; i < 4; i++) qf[i] = lds128(sb + OFF_QS + r * 80 + i * 16);
        const int mt = vw & 3;
        const uint32_t rowoff = (mt * 16 + r + 8 * (mi & 1)) * 128;
        const uint32_t sw = ((mi >> 1) ^ r) << 4;
        uint32_t mx = 0xff80ff80u;
#pragma unroll 1
        for (int i = (vw >> 2); i < 16; i += 2) {
            mbar_wait(s_full + (IT_K + i) * 8);
            const uint32_t base = sb + k_off(i) + rowoff;
            float c0[4] = {}, c1[4] = {};
            uint32_t a[4];
            ldsm4(a, base + sw);               mma16816(c0, a, qf[0].x, qf[0].y);
            ldsm4(a, base + 8192 + sw);        mma16816(c1, a, qf[2].x, qf[2].y);
            ldsm4(a, base + (sw ^ 32));        mma16816(c0, a, qf[0].z, qf[0].w);
            ldsm4(a, base + 8192 + (sw ^ 32)); mma16816(c1, a, qf[2].z, qf[2].w);
            ldsm4(a, base + (sw ^ 64));        mma16816(c0, a, qf[1].x, qf[1].y);
            ldsm4(a, base + 8192 + (sw ^ 64)); mma16816(c1, a, qf[3].x, qf[3].y);
            ldsm4(a, base + (sw ^ 96));        mma16816(c0, a, qf[1].z, qf[1].w);
            ldsm4(a, base + 8192 + (sw ^ 96)); mma16816(c1, a, qf[3].z, qf[3].w);
            __syncwarp();
            if (lane == 0) mbar_arrive(s_empty + (EM_K + i) * 8);
            const float scl = 0.08838834764831845f;
            uint32_t u0 = pack2(c0[0] + c1[0], c0[1] + c1[1]), u1 = pack2(c0[2] + c1[2], c0[3] + c1[3]);
            u0 = pack2(bflo(u0) * scl, bfhi(u0) * scl); u1 = pack2(bflo(u1) * scl, bfhi(u1) * scl);
            mx = bmax2(mx, bmax2(u0, u1));
            if (t == 0) {
                const uint32_t pa = sb + OFF_S + (i * 64 + 16 * (g >> 1) + 4 * mt + bat) * 4;
                sts32(pa, u0); sts32(pa + 8, u1);
            }
            if (i == PH_K && tid < 4) stg_ph(scr + G_ML + c * 8 + (tid & 1) * 4 + (tid & 2) * (HALF / 2));
        }
#pragma unroll
        for (int o = 4; o <= 16; o <<= 1) mx = bmax2(mx, __shfl_xor_sync(0xffffffffu, mx, o));
        if (lane == 0) sts32(sb + OFF_WMX + vw * 4, mx);
    }
    bar_consumers();
    {
        const float L2E = 1.4426950408889634f;
        uint4 sv = make_uint4(0, 0, 0, 0);
        float m0 = 0.f, m1 = 0.f;
        if (vw < 8) {
            uint4 ma = lds128(sb + OFF_WMX), mb = lds128(sb + OFF_WMX + 16);
            const uint32_t mx = bmax2(bmax2(bmax2(ma.x, ma.y), bmax2(ma.z, ma.w)), bmax2(bmax2(mb.x, mb.y), bmax2(mb.z, mb.w)));
            m0 = bflo(mx); m1 = bfhi(mx);
            sv = lds128(sb + OFF_S + tid * 16);
            float e0 = (ex2((bflo(sv.x) - m0) * L2E) + ex2((bflo(sv.y) - m0) * L2E)) + (ex2((bflo(sv.z) - m0) * L2E) + ex2((bflo(sv.w) - m0) * L2E));
            float e1 = (ex2((bfhi(sv.x) - m1) * L2E) + ex2((bfhi(sv.y) - m1) * L2E)) + (ex2((bfhi(sv.z) - m1) * L2E) + ex2((bfhi(sv.w) - m1) * L2E));
#pragma unroll
            for (int o = 16; o > 0; o >>= 1) { e0 += shx(e0, o); e1 += shx(e1, o); }
            if (lane == 0) sts64(sb + OFF_WMX + 32 + vw * 8, __float_as_uint(e0), __float_as_uint(e1));
        }
        bar_consumers();
        if (vw == 0) {
            float l0 = 0.f, l1 = 0.f;
#pragma unroll
            for (int w = 0; w < 4; w++) {
                uint4 s = lds128(sb + OFF_WMX + 32 + w * 16);
                l0 += __uint_as_float(s.x) + __uint_as_float(s.z); l1 += __uint_as_float(s.y) + __uint_as_float(s.w);
            }
            if (tid < 4) stg_pkt(scr + G_ML + c * 8 + (tid & 1) * 4 + (tid & 2) * (HALF / 2), m0, l0, m1, l1, tag);
            {
                const bool rd = lane < 4 && lane != sp;
                uint4 v = make_uint4(rd ? 2u : tag, 0, 0, 0);
                int it = 0;
                do { ldg_pkt_if(v, scr + G_ML + near_half(G_ML, side) + (kvh * 8 + (lane & 3) * 2 + bb) * 8, (v.x ^ tag) & 7u); }
                while (any_lane((v.x ^ tag) & 7u) && ++it < SPIN_LIMIT);
                if (rd) { m0 = untagf(v.x); l0 = __uint_as_float(v.y); m1 = __uint_as_float(v.z); l1 = __uint_as_float(v.w); }
            }
            float g0 = fmaxf(m0, shx(m0, 1)), g1 = fmaxf(m1, shx(m1, 1));
            g0 = fmaxf(g0, shx(g0, 2)); g1 = fmaxf(g1, shx(g1, 2));
            l0 *= ex2((m0 - g0) * L2E); l1 *= ex2((m1 - g1) * L2E);
            l0 += shx(l0, 1); l1 += shx(l1, 1);
            l0 += shx(l0, 2); l1 += shx(l1, 2);
            if (lane == 0)
                sts128(sb + OFF_WMX + 96, __float_as_uint(g0), __float_as_uint(g1), __float_as_uint(__frcp_rn(l0)), __float_as_uint(__frcp_rn(l1)));
        }
        bar_consumers();
        if (vw < 8) {
            const uint4 gs = lds128(sb + OFF_WMX + 96);
            const float g0 = __uint_as_float(gs.x), g1 = __uint_as_float(gs.y), i0 = __uint_as_float(gs.z), i1 = __uint_as_float(gs.w);
            const uint32_t a0 = pack2(ex2((bflo(sv.x) - g0) * L2E) * i0, ex2((bflo(sv.y) - g0) * L2E) * i0);
            const uint32_t a1 = pack2(ex2((bflo(sv.z) - g0) * L2E) * i0, ex2((bflo(sv.w) - g0) * L2E) * i0);
            const uint32_t b0 = pack2(ex2((bfhi(sv.x) - g1) * L2E) * i1, ex2((bfhi(sv.y) - g1) * L2E) * i1);
            const uint32_t b1 = pack2(ex2((bfhi(sv.z) - g1) * L2E) * i1, ex2((bfhi(sv.w) - g1) * L2E) * i1);
            sts64(sb + OFF_P + tid * 8, a0, a1); sts64(sb + OFF_P + PSTR + tid * 8, b0, b1);
        }
        bar_consumers();
    }
    const uint32_t rsw = ((mi & 1) ^ r) << 4;
    unsigned sidew = 2u;
    if (vw < 8) {
        float c0[4] = {}, c1[4] = {};
        const uint32_t vo = (vw >> 2) * 8192 + (r + 8 * (mi >> 1)) * 128 + ((((2 * vw + (mi & 1)) & 7) ^ r) << 4);
        const uint32_t pa = sb + OFF_P + bat * PSTR + t * 32;
#pragma unroll 1
        for (int i = 0; i < 16; i++) {
            uint4 pb0 = lds128(pa + i * 128), pb1 = lds128(pa + i * 128 + 16);
            mbar_wait(s_full + (IT_V + i) * 8);
            const uint32_t base = sb + v_off(i) + vo;
            uint32_t a0[4], a1[4], a2[4], a3[4];
            ldsm4t(a0, base); ldsm4t(a1, base + 2048); ldsm4t(a2, base + 4096); ldsm4t(a3, base + 6144);
            mma16816(c0, a0, pb0.x, pb0.y);
            mma16816(c1, a1, pb0.z, pb0.w);
            mma16816(c0, a2, pb1.x, pb1.y);
            mma16816(c1, a3, pb1.z, pb1.w);
            __syncwarp();
            if (lane == 0) mbar_arrive(s_empty + (EM_V + i) * 8);
            if (i == SIDE_V) { mbar_wait(s_empty + EM_PH * 8); sidew = ldg_rlx1(pside); }
        }
        if (t < 2)
            stg_pkt(scr + G_OP + kvh * 4096 + (j >> 2) * 2048 + t * HALF + (j & 3) * 256 + vw * 32 + g * 4,
                    c0[0] + c1[0], c0[1] + c1[1], c0[2] + c1[2], c0[3] + c1[3], tag);
    } else {
        mbar_wait(s_full + (IT_V + SIDE_V) * 8);
        mbar_wait(s_empty + EM_PH * 8);
    }
    {
        int it = 0;
        while (any_lane((sidew ^ tag) & 7u) && ++it < SPIN_LIMIT) sidew = ldg_rlx1(pside);
        ppart += near_half(G_PART + (vw * 16 + t * 4 + (g >> 1)) * 2048, sidew >> 4);
    }
    side = __float_as_uint(ldsf(sb + OFF_WMX + 112));
#pragma unroll 1
    for (int ph = 0; ph < 2; ph++) {
        if (ph) {
            mbar_wait(s_empty + EM_X1 * 8);
            {
                uint4 v;
                int it = 0;
                const int xw = G_X1 + (vw >> 3) * 2048 + (c & (XREP - 1)) * 4096;
                const unsigned* px = scr + xw + near_half(xw, side) + (vecw & 1023);
                do { v = ldg_rlx4(px); } while (any_lane(bad4(v, tag) & 7u) && ++it < SPIN_LIMIT);
                xw0 = hi2(v.x, v.y); xw1 = hi2(v.z, v.w);
                ln_stage1(xw0, xw1, st2, vw, lane);
                bar_consumers();
                uint32_t y0, y1;
                ln_stage2(ln_load(st2), xw0, xw1, y0, y1);
                aw0 = badd2(bmul2(y0, sc0), sh0); aw1 = badd2(bmul2(y1, sc1), sh1);
                uint32_t bf[4][2];
                make_bfrags(bf, aw0, aw1, r);
                const uint32_t gub = s_full + (IT_GU + 2 * (vw / 3)) * 8;
                const uint32_t gpitch = wide ? 96 : 64, gsw = wide ? 0 : (r >> 1) << 4;
                const uint32_t gbase = sb + ((mi & 1) ? OFF_U : OFF_G) + (vw * 64 + r + 8 * (mi >> 1)) * gpitch;
                mbar_wait(gub); mbar_wait(gub + 8);
                float cc[6][4] = {};
#pragma unroll
                for (int ks = 0; ks < 4; ks++)
#pragma unroll
                    for (int q = 0; q < 4; q++) {
                        uint32_t a[4];
                        ldsm4t(a, gbase + ks * 16 * gpitch + ((q << 4) ^ gsw));
                        mma16816(cc[q], a, bf[ks][0], bf[ks][1]);
                    }
                if (wide) {
#pragma unroll
                    for (int ks = 0; ks < 4; ks++)
#pragma unroll
                        for (int q = 4; q < 6; q++) {
                            uint32_t a[4];
                            ldsm4t(a, gbase + ks * 1536 + q * 16);
                            mma16816(cc[q], a, bf[ks][0], bf[ks][1]);
                        }
                }
                if (t == 0) {
#pragma unroll
                    for (int q = 0; q < 6; q++) sts128f(sb + OFF_RED + vw * 768 + q * 128 + g * 16, cc[q]);
                }
                bar_consumers();
                if (tid < 192) {
                    float sv[NCW];
#pragma unroll
                    for (int w = 0; w < NCW; w++) sv[w] = ldsf(sb + OFF_RED + w * 768 + tid * 4);
                    const float s = ((sv[0] + sv[1]) + (sv[2] + sv[3])) + ((sv[4] + sv[5]) + (sv[6] + sv[7])) + sv[8];
                    const uint32_t gu = pack2(s, __shfl_down_sync(0xffffffffu, s, 2));
                    const float gt = bflo(gu);
                    const uint32_t hh = pack2(((gt > 0.f) ? gt : gt * 0.0f) * bfhi(gu), 0.f);
                    const int rr = tid >> 2;
                    if ((tid & 2) == 0)
                        sts16(sb + OFF_FR + ((tid & 1) * 4 + ((rr & 7) >> 1)) * 48 + (rr >> 3) * 4 + (rr & 1) * 2, hh);
                }
            }
            bar_consumers();
        }
        {
            const int di = (vw / 3 + 1) % 3;
            const uint32_t rrow = (r + 8 * (mi >> 1)) * 128;
            const uint32_t b0 = sb + rrow + (ph ? OFF_D + di * DSTR + (vw % 3) * (wide ? 6144 : 4096) : OFF_WO0 + vw * 2048);
            const uint32_t b1 = ph ? b0 + 2048 : sb + rrow + OFF_WO1 + vw * 2048;
            const uint32_t fb0 = s_full + (ph ? IT_WD + di : IT_WO) * 8;
            const bool k3 = ph && wide;
            uint32_t ad[3][4][4];
            uint4 fr = lds128(sb + OFF_FR + r * 48);
            const uint2 f2 = lds64(sb + OFF_FR + r * 48 + 16);
            mbar_wait(fb0);
#pragma unroll
            for (int mt = 0; mt < 4; mt++) ldsm4t(ad[0][mt], b0 + (rsw ^ (mt * 32)));
            if (!ph) mbar_wait(fb0 + 8);
#pragma unroll
            for (int mt = 0; mt < 4; mt++) ldsm4t(ad[1][mt], b1 + (rsw ^ (mt * 32)));
            if (k3) {
#pragma unroll
                for (int mt = 0; mt < 4; mt++) ldsm4t(ad[2][mt], b0 + 4096 + (rsw ^ (mt * 32)));
            }
            if (!ph) {
                asm volatile("bar.sync 3, 352;" ::: "memory");
                fr = lds128(sb + OFF_FR + r * 48);
            }
            float cc[4][4] = {};
#pragma unroll
            for (int mt = 0; mt < 4; mt++) mma16816(cc[mt], ad[0][mt], fr.x, fr.y);
#pragma unroll
            for (int mt = 0; mt < 4; mt++) mma16816(cc[mt], ad[1][mt], fr.z, fr.w);
            if (k3) {
#pragma unroll
                for (int mt = 0; mt < 4; mt++) mma16816(cc[mt], ad[2][mt], f2.x, f2.y);
            }
            publish_partials(ppart, t, cc, tag | (ph * 4u));
        }
    }
    if (vw / 3 == c / 48) asm volatile("bar.arrive 5, 128;" ::: "memory");
    if (vw >= 6 && c < 16) asm volatile("bar.arrive 7, 128;" ::: "memory");
}

typedef CUresult (*EncodeFn)(CUtensorMap*, CUtensorMapDataType, cuuint32_t, void*, const cuuint64_t*, const cuuint64_t*,
                             const cuuint32_t*, const cuuint32_t*, CUtensorMapInterleave, CUtensorMapSwizzle,
                             CUtensorMapL2promotion, CUtensorMapFloatOOBfill);

void make_map(EncodeFn enc, CUtensorMap* m, const void* p, cuuint64_t d0, cuuint64_t d1, cuuint64_t d2,
              cuuint64_t s1, cuuint64_t s2, cuuint32_t b0, cuuint32_t b1, cuuint32_t b2, CUtensorMapSwizzle sw) {
    cuuint64_t dims[3] = {d0, d1, d2};
    cuuint64_t str[2] = {s1, s2};
    cuuint32_t box[3] = {b0, b1, b2};
    cuuint32_t es[3] = {1, 1, 1};
    enc(m, CU_TENSOR_MAP_DATA_TYPE_BFLOAT16, 3, const_cast<void*>(p), dims, str, box, es,
        CU_TENSOR_MAP_INTERLEAVE_NONE, sw, CU_TENSOR_MAP_L2_PROMOTION_L2_128B, CU_TENSOR_MAP_FLOAT_OOB_FILL_NONE);
}

}

extern "C" void kernel_launch(void* const* d_in, const int* in_sizes, int n_in, void* d_out, int out_size) {
    (void)in_sizes; (void)n_in; (void)out_size;
    void* fn = nullptr;
    cudaDriverEntryPointQueryResult qr;
    cudaGetDriverEntryPoint("cuTensorMapEncodeTiled", &fn, cudaEnableDefault, &qr);
    EncodeFn enc = (EncodeFn)fn;
    cudaFuncSetAttribute(fused_block_kernel, cudaFuncAttributeMaxDynamicSharedMemorySize, SMEM_BYTES);

    const void *x = d_in[0], *kc = d_in[1], *vc = d_in[2], *wq = d_in[3], *wo = d_in[4];
    const void *wg = d_in[6], *wu = d_in[7], *wd = d_in[8], *cc = d_in[9], *wmod = d_in[10];
    const CUtensorMapSwizzle S128 = CU_TENSOR_MAP_SWIZZLE_128B, S64 = CU_TENSOR_MAP_SWIZZLE_64B, S0 = CU_TENSOR_MAP_SWIZZLE_NONE;
    void* raw = nullptr;
    cudaGetSymbolAddress(&raw, g_raw);
    unsigned* scr = (unsigned*)(((uintptr_t)raw + 0x1fffff) & ~(uintptr_t)0x1fffff);
    Maps m;
    make_map(enc, &m.m[M_K], kc, 64, 32ull * 32768, 2, 256, 128, 64, 64, 2, S128);
    make_map(enc, &m.m[M_V], vc, 64, 32ull * 32768, 2, 256, 128, 64, 64, 2, S128);
    make_map(enc, &m.m[M_WMOD], wmod, 3456, 144, 4, 3456 * 2, 3456 * 2 * 144, 32, 144, 2, S64);
    make_map(enc, &m.m[M_WQ], wq, 4096, 144, 4, 4096 * 2, 4096 * 2 * 144, 32, 144, 2, S64);
    make_map(enc, &m.m[M_WG], wg, 4608, 576, 1, 4608 * 2, 4608 * 2 * 576, 32, 192, 1, S64);
    make_map(enc, &m.m[M_WU], wu, 4608, 576, 1, 4608 * 2, 4608 * 2 * 576, 32, 192, 1, S64);
    make_map(enc, &m.m[M_WG48], wg, 4608, 576, 1, 4608 * 2, 4608 * 2 * 576, 48, 192, 1, S0);
    make_map(enc, &m.m[M_WU48], wu, 4608, 576, 1, 4608 * 2, 4608 * 2 * 576, 48, 192, 1, S0);
    make_map(enc, &m.m[M_WO], wo, 64, 4096, 9, 1152, 128, 64, 16, 9, S128);
    make_map(enc, &m.m[M_WD], wd, 64, 4608, 9, 1152, 128, 64, 32, 3, S128);
    make_map(enc, &m.m[M_WD48], wd, 64, 4608, 9, 1152, 128, 64, 48, 3, S128);
    fused_block_kernel<<<NCTA, NTHR, SMEM_BYTES>>>(m, (const __nv_bfloat16*)x, (const __nv_bfloat16*)cc,
                                                   (const __nv_bfloat16*)kc, (__nv_bfloat16*)d_out, scr);
}
```
